```python
import torch

def _softmax(x, axis=-1):
    return torch.softmax(x, dim=axis)
def _gelu(x):
    return torch.nn.functional.gelu(x, approximate="tanh")
def _silu(x):
    return torch.nn.functional.silu(x)
def _sigmoid(x):
    return torch.sigmoid(x)
def _layernorm(x, axis=-1, eps=1e-5):
    m = x.mean(dim=axis, keepdim=True)
    v = x.var(dim=axis, keepdim=True, unbiased=False)
    return (x - m) / torch.sqrt(v + eps)
def _scatter_add(tgt, idx, src, axis=0):
    return tgt.clone().index_add_(axis, idx, src)
def _segment_sum(src, seg, n):
    out = torch.zeros((n,) + src.shape[1:], dtype=src.dtype)
    return out.index_add_(0, seg, src)
def _pad(x, pw):
    flat = tuple(v for pair in reversed(pw) for v in pair)
    return torch.nn.functional.pad(x, flat)

kernel_name = 'concat_heads__compressed_kv_cla__ssm_conv_s4d__prompt'

def setup_inputs():

    _w = (lambda a: (lambda t: t.to(torch.bfloat16) if t.is_floating_point() else t)(torch.as_tensor(a)))
    def _A_setup():
        B, H, Sq, Sk, D, M = 1, 32, 2048, 2048, 128, 512
        Dc = 4 * D
        return {
            "x": _w((lambda *s: torch.randn(*s, dtype=torch.bfloat16) * 3.2)(B, Sq, M)),
            "c_kv": _w((lambda *s: torch.randn(*s, dtype=torch.bfloat16) * 0.1)(B, Sk, Dc)),
            "w_q": _w((lambda *s: torch.randn(*s, dtype=torch.bfloat16) * 6.4)(M, H, D) * (M ** -0.5)),
            "w_uk": _w((lambda *s: torch.randn(*s, dtype=torch.bfloat16) * 6.4)(Dc, H, D) * (Dc ** -0.5)),
            "w_uv": _w((lambda *s: torch.randn(*s, dtype=torch.bfloat16) * 0.1)(Dc, H, D) * (Dc ** -0.5)),
            "w_o": _w((lambda *s: torch.randn(*s, dtype=torch.bfloat16) * 0.1)(H, D, M) * ((H * D) ** -0.5)),
        }
    _A_in = _A_setup()

    def _B_setup():
        Bsz, L, D, N = 1, 2048, 512, 128
        return {
            "u": _w((lambda *s: torch.randn(*s, dtype=torch.bfloat16) * 0.05)(Bsz, L, D)),
            "log_A_real": _w((lambda *s: torch.randn(*s, dtype=torch.bfloat16) * 6.4)(D, N) * 0.5),
            "A_imag": _w((lambda *s: torch.randn(*s, dtype=torch.bfloat16) * 0.05)(D, N) * 3.14),
            "C_real": _w((lambda *s: torch.randn(*s, dtype=torch.bfloat16) * 0.05)(D, N) / N ** 0.5),
            "C_imag": _w((lambda *s: torch.randn(*s, dtype=torch.bfloat16) * 0.05)(D, N) / N ** 0.5),
            "log_dt": _w((lambda *s: torch.randn(*s, dtype=torch.bfloat16) * 0.05)(D) * 0.5 - 4.0),
            "D_skip": _w((lambda *s: torch.randn(*s, dtype=torch.bfloat16) * 0.05)(D)),
        }
    _B_in = _B_setup()

    return {
        "A_x": _A_in["x"],
        "A_c_kv": _A_in["c_kv"],
        "A_w_q": _A_in["w_q"],
        "A_w_uk": _A_in["w_uk"],
        "A_w_uv": _A_in["w_uv"],
        "A_w_o": _A_in["w_o"],
        "B_u": _B_in["u"],
        "B_log_A_real": _B_in["log_A_real"],
        "B_A_imag": _B_in["A_imag"],
        "B_C_real": _B_in["C_real"],
        "B_C_imag": _B_in["C_imag"],
        "B_log_dt": _B_in["log_dt"],
        "B_D_skip": _B_in["D_skip"],
    }

def reference(A_x, A_c_kv, A_w_q, A_w_uk, A_w_uv, A_w_o, B_u, B_log_A_real, B_A_imag, B_C_real, B_C_imag, B_log_dt, B_D_skip):
    def _A_ref(x, c_kv, w_q, w_uk, w_uv, w_o):
        B, Sq, M = x.shape[0], x.shape[1], x.shape[2]
        Sk = c_kv.shape[1]
        H, D = w_q.shape[1], w_q.shape[2]
        q = torch.einsum("bqm,mhd->bhqd", x, w_q)
        k = torch.einsum("bkc,chd->bhkd", c_kv, w_uk)
        v = torch.einsum("bkc,chd->bhkd", c_kv, w_uv)
        scores = torch.einsum("bhqd,bhkd->bhqk", q, k) * (D ** -0.5)
        off = Sk - Sq
        qi = torch.arange(Sq)[:, None]
        kj = torch.arange(Sk)[None, :]
        cmask = kj <= (qi + off)
        scores = torch.where(cmask[None, None], scores, -1e9)
        p = _softmax(scores, axis=-1)
        ctx = torch.einsum("bhqk,bhkd->bhqd", p, v)
        return torch.einsum("bhqd,hdm->bqm", ctx, w_o)

    def _B_ref(u, log_A_real, A_imag, C_real, C_imag, log_dt, D_skip):
        L = u.shape[1]
        dt = torch.exp(log_dt)
        A = -torch.exp(log_A_real) + 1j * A_imag
        C = (C_real + 1j * C_imag) * dt[:, None]
        pos = (lambda x, dt: x.to(dt))(torch.arange(L), log_dt.dtype)
        P = torch.exp((A * dt[:, None])[:, :, None] * pos[None, None, :])
        K = 2.0 * torch.einsum("dn,dnl->dl", C, P).real
        L2 = 2 * L
        u_t = (lambda x, *d: x.permute(*d))(u, 0, 2, 1)
        Kf = (lambda x, *a, **k: torch.fft.rfft(x.float(), *a, **k))(K, L2)
        Uf = (lambda x, *a, **k: torch.fft.rfft(x.float(), *a, **k))(u_t, L2)
        y = (lambda x, *a, **k: torch.fft.irfft(x, *a, **k).to(torch.bfloat16))(Uf * Kf[None, :, :], L2)[:, :, :L]
        y = (lambda x, *d: x.permute(*d))(y, 0, 2, 1)
        return y + u * D_skip[None, None, :]

    a = _A_ref(A_x, A_c_kv, A_w_q, A_w_uk, A_w_uv, A_w_o)
    b = _B_ref(B_u, B_log_A_real, B_A_imag, B_C_real, B_C_imag, B_log_dt, B_D_skip)
    return torch.concatenate([a, b], axis=-1)
```

```cpp
#include <cuda_runtime.h>
#include <cuda_bf16.h>
#include <cuda.h>
#include <stdint.h>

typedef __nv_bfloat16 bf16;

#define DEVI __device__ __forceinline__

constexpr int SEQ = 2048, DM = 512, NH = 32, HD = 128, HDALL = NH * HD;
constexpr int SSM_D = 512, SSM_N = 128;
constexpr int WTAB = 2112;

__device__ bf16 g_kv[(size_t)SEQ * 2 * HDALL];
__device__ bf16 g_ctx[(size_t)SEQ * HDALL];
__device__ float g_kp[SSM_D * 648];
__device__ uint32_t g_wtab[SSM_D * WTAB];
__device__ unsigned int g_sched;

DEVI uint32_t smem_u32(const void* p) { return (uint32_t)__cvta_generic_to_shared(p); }
DEVI void mbar_init(uint32_t a, uint32_t cnt) { asm volatile("mbarrier.init.shared::cta.b64 [%0], %1;" ::"r"(a), "r"(cnt)); }
DEVI void mbar_expect_tx(uint32_t a, uint32_t bytes) {
    asm volatile("mbarrier.arrive.expect_tx.shared::cta.b64 _, [%0], %1;" ::"r"(a), "r"(bytes) : "memory");
}
DEVI void mbar_arrive(uint32_t a) { asm volatile("mbarrier.arrive.shared::cta.b64 _, [%0];" ::"r"(a) : "memory"); }
DEVI void mbar_arrive_cluster(uint32_t a, uint32_t cta) {
    asm volatile("{\n.reg .b32 r;\nmapa.shared::cluster.u32 r, %0, %1;\n"
                 "mbarrier.arrive.release.cluster.shared::cluster.b64 _, [r];\n}" ::"r"(a), "r"(cta) : "memory");
}
#define MBAR_WAIT_ASM(OP)                                                                              \
    asm volatile("{\n.reg .pred p, q;\n.reg .u32 t0, t1;\n" OP " p, [%0], %1;\n@p bra D_%=;\n"         \
                 "mov.u32 t0, %%globaltimer_lo;\nW_%=:\n" OP " p, [%0], %1;\n"                         \
                 "mov.u32 t1, %%globaltimer_lo;\nsub.u32 t1, t1, t0;\n"                                \
                 "setp.gt.or.u32 q, t1, 4000000, p;\n@!q bra W_%=;\nD_%=:\n}" ::"r"(a), "r"(parity) : "memory")
DEVI void mbar_wait(uint32_t a, uint32_t parity) { MBAR_WAIT_ASM("mbarrier.try_wait.parity.shared::cta.b64"); }
DEVI void mbar_wait_cluster(uint32_t a, uint32_t parity) { MBAR_WAIT_ASM("mbarrier.try_wait.parity.acquire.cluster.shared::cta.b64"); }
DEVI void fence_barrier_init() { asm volatile("fence.mbarrier_init.release.cluster;" ::: "memory"); }
DEVI void fence_proxy_async() { asm volatile("fence.proxy.async.shared::cta;" ::: "memory"); }
DEVI void cluster_sync_all() {
    asm volatile("barrier.cluster.arrive.release.aligned;\nbarrier.cluster.wait.acquire.aligned;" ::: "memory");
}
DEVI uint32_t cluster_rank() { uint32_t r; asm volatile("mov.u32 %0, %%cluster_ctarank;" : "=r"(r)); return r; }
DEVI void tma_load_2d(uint32_t dst, const CUtensorMap* m, int c0, int c1, uint32_t bar) {
    asm volatile("cp.async.bulk.tensor.2d.shared::cluster.global.mbarrier::complete_tx::bytes [%0], [%1, {%3, %4}], [%2];"
                 ::"r"(dst), "l"(m), "r"(bar), "r"(c0), "r"(c1) : "memory");
}
DEVI void tma_load_2d_mc(uint32_t dst, const CUtensorMap* m, int c0, int c1, uint32_t bar, uint16_t mask) {
    asm volatile("cp.async.bulk.tensor.2d.shared::cluster.global.mbarrier::complete_tx::bytes.multicast::cluster [%0], [%1, {%3, %4}], [%2], %5;"
                 ::"r"(dst), "l"(m), "r"(bar), "r"(c0), "r"(c1), "h"(mask) : "memory");
}
DEVI void tma_prefetch_2d(const CUtensorMap* m, int c0, int c1) {
    asm volatile("cp.async.bulk.prefetch.tensor.2d.L2.global [%0, {%1, %2}];" ::"l"(m), "r"(c0), "r"(c1) : "memory");
}
DEVI void tma_store_2d(const CUtensorMap* m, uint32_t src, int c0, int c1) {
    asm volatile("cp.async.bulk.tensor.2d.global.shared::cta.bulk_group [%0, {%2, %3}], [%1];"
                 ::"l"(m), "r"(src), "r"(c0), "r"(c1) : "memory");
}
DEVI void bulk_load(uint32_t dst, const void* src, uint32_t bytes, uint32_t bar) {
    asm volatile("cp.async.bulk.shared::cluster.global.mbarrier::complete_tx::bytes [%0], [%1], %2, [%3];"
                 ::"r"(dst), "l"(src), "r"(bytes), "r"(bar) : "memory");
}
DEVI void bulk_commit() { asm volatile("cp.async.bulk.commit_group;" ::: "memory"); }
template <int N> DEVI void bulk_wait_read() { asm volatile("cp.async.bulk.wait_group.read %0;" ::"n"(N) : "memory"); }
template <int N> DEVI void bulk_wait() { asm volatile("cp.async.bulk.wait_group %0;" ::"n"(N) : "memory"); }
DEVI void prefetch_tmap(const CUtensorMap* m) { asm volatile("prefetch.tensormap [%0];" ::"l"(m) : "memory"); }
DEVI void named_sync(int id, int n) { asm volatile("bar.sync %0, %1;" ::"r"(id), "r"(n) : "memory"); }
DEVI void named_arrive(int id, int n) { asm volatile("bar.arrive %0, %1;" ::"r"(id), "r"(n) : "memory"); }
DEVI void pdl_wait() { asm volatile("griddepcontrol.wait;" ::: "memory"); }
DEVI void pdl_launch() { asm volatile("griddepcontrol.launch_dependents;" ::: "memory"); }
template <int R> DEVI void reg_inc() { asm volatile("setmaxnreg.inc.sync.aligned.u32 %0;" ::"n"(R)); }
template <int R> DEVI void reg_dec() { asm volatile("setmaxnreg.dec.sync.aligned.u32 %0;" ::"n"(R)); }

DEVI void wg_fence() { asm volatile("wgmma.fence.sync.aligned;" ::: "memory"); }
DEVI void wg_commit() { asm volatile("wgmma.commit_group.sync.aligned;" ::: "memory"); }
template <int N> DEVI void wg_wait() { asm volatile("wgmma.wait_group.sync.aligned %0;" ::"n"(N) : "memory"); }

DEVI uint64_t make_desc(uint32_t addr, uint32_t lbo, uint32_t sbo, uint32_t swz) {
    return (uint64_t)((addr & 0x3FFFF) >> 4) | ((uint64_t)(lbo >> 4) << 16) | ((uint64_t)(sbo >> 4) << 32) | ((uint64_t)swz << 62);
}
DEVI uint64_t desc_kmajor(uint32_t addr) { return make_desc(addr, 16, 1024, 1); }
DEVI uint64_t desc_mnmajor(uint32_t addr, uint32_t lbo) { return make_desc(addr, lbo, 1024, 1); }

#define ACC8(d, o) "+f"(d[o + 0]), "+f"(d[o + 1]), "+f"(d[o + 2]), "+f"(d[o + 3]), "+f"(d[o + 4]), "+f"(d[o + 5]), "+f"(d[o + 6]), "+f"(d[o + 7])
#define ACC64(d) ACC8(d, 0), ACC8(d, 8), ACC8(d, 16), ACC8(d, 24), ACC8(d, 32), ACC8(d, 40), ACC8(d, 48), ACC8(d, 56)
#define R64 "{%0,%1,%2,%3,%4,%5,%6,%7,%8,%9,%10,%11,%12,%13,%14,%15,%16,%17,%18,%19,%20,%21,%22,%23,%24,%25,%26,%27,%28,%29,%30,%31," \
            "%32,%33,%34,%35,%36,%37,%38,%39,%40,%41,%42,%43,%44,%45,%46,%47,%48,%49,%50,%51,%52,%53,%54,%55,%56,%57,%58,%59,%60,%61,%62,%63}"

template <int TB> DEVI void wgmma_ss128(float* d, uint64_t da, uint64_t db, int acc) {
    asm volatile("{\n.reg .pred p;\nsetp.ne.b32 p, %66, 0;\n"
                 "wgmma.mma_async.sync.aligned.m64n128k16.f32.bf16.bf16 " R64 ", %64, %65, p, 1, 1, 0, %67;\n}"
                 : ACC64(d) : "l"(da), "l"(db), "r"(acc), "n"(TB));
}
template <int TB> DEVI void wgmma_rs128(float* d, const uint32_t* a, uint64_t db, int acc) {
    asm volatile("{\n.reg .pred p;\nsetp.ne.b32 p, %69, 0;\n"
                 "wgmma.mma_async.sync.aligned.m64n128k16.f32.bf16.bf16 " R64 ", {%64,%65,%66,%67}, %68, p, 1, 1, %70;\n}"
                 : ACC64(d) : "r"(a[0]), "r"(a[1]), "r"(a[2]), "r"(a[3]), "l"(db), "r"(acc), "n"(TB));
}
DEVI uint32_t pack_bf16(float lo, float hi) {
    uint32_t r;
    asm("cvt.rn.bf16x2.f32 %0, %1, %2;" : "=r"(r) : "f"(hi), "f"(lo));
    return r;
}
DEVI void stmatrix_x4(uint32_t addr, uint32_t r0, uint32_t r1, uint32_t r2, uint32_t r3) {
    asm volatile("stmatrix.sync.aligned.m8n8.x4.shared.b16 [%0], {%1,%2,%3,%4};" ::"r"(addr), "r"(r0), "r"(r1), "r"(r2), "r"(r3) : "memory");
}
DEVI float ex2(float x) { float y; asm("ex2.approx.ftz.f32 %0, %1;" : "=f"(y) : "f"(x)); return y; }

DEVI void store_slab64(uint32_t base, int row0, const float* d, float s0, float s1, int lane) {
    int mi = lane >> 3, r = lane & 7;
    int row = row0 + (mi & 1) * 8 + r;
#pragma unroll
    for (int j = 0; j < 8; j += 2) {
        uint32_t r0 = pack_bf16(d[4 * j + 0] * s0, d[4 * j + 1] * s0);
        uint32_t r1 = pack_bf16(d[4 * j + 2] * s1, d[4 * j + 3] * s1);
        uint32_t r2 = pack_bf16(d[4 * j + 4] * s0, d[4 * j + 5] * s0);
        uint32_t r3 = pack_bf16(d[4 * j + 6] * s1, d[4 * j + 7] * s1);
        int chunk = j + (mi >> 1);
        stmatrix_x4(base + row * 128 + ((chunk ^ (row & 7)) << 4), r0, r1, r2, r3);
    }
}
struct cf { float x, y; };
DEVI cf cmul(cf a, cf b) { cf r; r.x = fmaf(a.x, b.x, -a.y * b.y); r.y = fmaf(a.x, b.y, a.y * b.x); return r; }
DEVI cf csq(cf a) { cf r; r.x = fmaf(a.x, a.x, -a.y * a.y); r.y = (a.x + a.x) * a.y; return r; }
DEVI cf cexp_(float re, float im) {
    float m = expf(re), s, c;
    sincosf(im, &s, &c);
    cf r; r.x = m * c; r.y = m * s; return r;
}
DEVI uint32_t tf32(float x) { uint32_t r; asm("cvt.rna.tf32.f32 %0, %1;" : "=r"(r) : "f"(x)); return r; }
DEVI void mma_tf32(float* c, cf lo, cf hi, uint32_t b0, uint32_t b1) {
    asm volatile("mma.sync.aligned.m16n8k8.row.col.f32.tf32.tf32.f32 {%0,%1,%2,%3}, {%4,%5,%6,%7}, {%8,%9}, {%0,%1,%2,%3};"
                 : "+f"(c[0]), "+f"(c[1]), "+f"(c[2]), "+f"(c[3])
                 : "r"(tf32(lo.x)), "r"(tf32(hi.x)), "r"(tf32(lo.y)), "r"(tf32(hi.y)), "r"(b0), "r"(b1));
}
DEVI float bf2f(bf16 v) { return __bfloat162float(v); }
DEVI float rbf(float v) { return __bfloat162float(__float2bfloat16_rn(v)); }

struct SsmParams { const bf16 *lar, *aim, *cre, *cim, *ldt, *dskip, *u; };

DEVI int kp_index(int l) {
    int p = (int)rbf((float)l);
    return p < 256 ? p : (p < 512 ? 128 + (p >> 1) : (p < 1024 ? 256 + (p >> 2) : 384 + (p >> 3)));
}

DEVI void ssm_kgen_warp(const SsmParams& P, int d, int lane) {
    const int g = lane >> 2, t = lane & 3;
    const float dt = rbf(expf(bf2f(P.ldt[d])));
    float ar[4], ai[4], cr[4], ci[4], gr[4], gi[4];
#pragma unroll
    for (int q = 0; q < 4; q++) {
        int n = d * SSM_N + 32 * q + lane;
        ar[q] = -rbf(expf(bf2f(P.lar[n]))) * dt;
        ai[q] = bf2f(P.aim[n]) * dt;
        cr[q] = 2.f * (bf2f(P.cre[n]) * dt);
        ci[q] = 2.f * (bf2f(P.cim[n]) * dt);
        cf G = cexp_(ar[q] * 64.f, ai[q] * 64.f);
        gr[q] = G.x; gi[q] = G.y;
    }
    float acc[5][4];
#pragma unroll
    for (int s = 0; s < 5; s++) { acc[s][0] = acc[s][1] = acc[s][2] = acc[s][3] = 0.f; }
    float klast = 0.f;
    const float gf = (float)g;
#pragma unroll
    for (int q = 0; q < 4; q++) {
#pragma unroll 2
        for (int g0 = 0; g0 < 8; g0++) {
            int src = (g0 << 2) | t;
            float a_r = __shfl_sync(~0u, ar[q], src), a_i = __shfl_sync(~0u, ai[q], src);
            cf C, G;
            C.x = __shfl_sync(~0u, cr[q], src); C.y = __shfl_sync(~0u, ci[q], src);
            G.x = __shfl_sync(~0u, gr[q], src); G.y = __shfl_sync(~0u, gi[q], src);
            cf E = cexp_(a_r * gf, a_i * gf);
            cf B = csq(csq(csq(E)));
            cf Y = cmul(C, B);
            uint32_t b0 = tf32(Y.x), b1 = tf32(-Y.y);
            cf EG = cmul(E, G);
            mma_tf32(acc[0], E, EG, b0, b1);
            cf G2 = csq(G);
            cf X = cmul(E, G2), Xh = cmul(EG, G2);
            mma_tf32(acc[1], X, Xh, b0, b1);
#pragma unroll
            for (int s = 2; s < 5; s++) {
                B = csq(B); X = csq(X); Xh = csq(Xh);
                Y = cmul(C, B);
                mma_tf32(acc[s], X, Xh, tf32(Y.x), tf32(-Y.y));
            }
            X = csq(X);
            klast += fmaf(C.x, X.x, -C.y * X.y);
        }
    }
    klast += __shfl_xor_sync(~0u, klast, 1);
    klast += __shfl_xor_sync(~0u, klast, 2);
    float* kp = g_kp + d * 648;
#pragma unroll
    for (int s = 0; s < 5; s++) {
        int b = 128 * s + g + 16 * t;
        kp[b] = acc[s][0]; kp[b + 8] = acc[s][1]; kp[b + 64] = acc[s][2]; kp[b + 72] = acc[s][3];
    }
    if (lane == 0) kp[640] = klast;
    __threadfence_block();
    __syncwarp();
    uint4* wt = reinterpret_cast<uint4*>(g_wtab + d * WTAB);
    for (int qd = lane; qd < WTAB / 4; qd += 32) {
        int o = qd * 4 - 64;
        float k[5];
#pragma unroll
        for (int e = 0; e < 5; e++) {
            int l = o - 1 + e;
            k[e] = l < 0 ? 0.f : __ldcg(kp + kp_index(l));
        }
        uint4 w;
        w.x = pack_bf16(k[1], k[0]); w.y = pack_bf16(k[2], k[1]); w.z = pack_bf16(k[3], k[2]); w.w = pack_bf16(k[4], k[3]);
        wt[qd] = w;
    }
}

constexpr int G1_THREADS = 512;
constexpr int G1_SMEM = 131072 + 4 * 16384 + 2 * 16384 + 256 + 1024;

__global__ void __cluster_dims__(2, 1, 1) __launch_bounds__(G1_THREADS, 1)
gemm_kv_kernel(const __grid_constant__ CUtensorMap tm_c, const __grid_constant__ CUtensorMap tm_wk,
               const __grid_constant__ CUtensorMap tm_wv, const __grid_constant__ CUtensorMap tm_kv_st, SsmParams sp) {
    extern __shared__ uint8_t smem_raw[];
    const uint32_t sb = (smem_u32(smem_raw) + 1023) & ~1023u;
    const uint32_t sA = sb, sB = sb + 131072, sC = sB + 65536, bars = sC + 32768;
    const uint32_t a_full = bars, b_full = bars + 64, b_empty = bars + 96;
    const int tid = threadIdx.x, warp = tid >> 5, lane = tid & 31, wg = tid >> 7;
    const uint32_t rank = cluster_rank();
    const int cl = blockIdx.x >> 1;
    const int m0 = ((cl & 7) * 2 + rank) * 128;
    const int ng = cl >> 3;
    if (tid == 0) {
        for (int i = 0; i < 8; i++) mbar_init(a_full + 8 * i, 1);
        for (int i = 0; i < 4; i++) { mbar_init(b_full + 8 * i, 1); mbar_init(b_empty + 8 * i, 8); }
        fence_barrier_init();
    }
    __syncthreads();
    cluster_sync_all();
    pdl_launch();
    if (wg == 3) {
        reg_dec<24>();
        if (tid == 384) {
            const CUtensorMap* tw = ng < 4 ? &tm_wk : &tm_wv;
            const int n0 = (ng & 3) * 1024 + rank * 64;
            for (int it = 0; it < 64; it++) {
                int st = it & 3;
                if (it < 8) {
                    mbar_expect_tx(a_full + 8 * it, 16384);
                    tma_load_2d(sA + it * 16384, &tm_c, it * 64, m0, a_full + 8 * it);
                }
                mbar_wait_cluster(b_empty + 8 * st, ((it >> 2) & 1) ^ 1);
                mbar_expect_tx(b_full + 8 * st, 16384);
                tma_load_2d_mc(sB + st * 16384 + rank * 8192, tw, n0 + (it >> 3) * 128, (it & 7) * 64, b_full + 8 * st, 3);
                if (it + 8 < 64) tma_prefetch_2d(tw, n0 + ((it + 8) >> 3) * 128, (it & 7) * 64);
            }
        }
        __syncwarp();
        cluster_sync_all();
    } else if (wg == 2) {
        reg_dec<96>();
        ssm_kgen_warp(sp, blockIdx.x * 4 + (warp & 3), lane);
        cluster_sync_all();
    } else {
        reg_inc<192>();
        float acc[2][64];
        const uint32_t stg = sC + wg * 16384;
        if (wg == 1) named_arrive(3, 256);
        for (int tt = 0; tt < 4; tt++) {
            const int t = 2 * tt + wg;
            named_sync(3 + wg, 256);
#pragma unroll 1
            for (int kc = 0; kc < 8; kc++) {
                const int it = t * 8 + kc, st = it & 3;
                if (tt == 0) mbar_wait(a_full + 8 * kc, 0);
                mbar_wait(b_full + 8 * st, (it >> 2) & 1);
                wg_fence();
                const uint64_t da = desc_kmajor(sA + kc * 16384), db = desc_mnmajor(sB + st * 16384, 8192);
#pragma unroll
                for (int k = 0; k < 4; k++) {
                    wgmma_ss128<1>(acc[0], da + k * 2, db + k * 128, (kc | k) != 0);
                    wgmma_ss128<1>(acc[1], da + 512 + k * 2, db + k * 128, (kc | k) != 0);
                }
                wg_commit();
                if (kc == 7 && t < 7) named_arrive(3 + (wg ^ 1), 256);
                if (kc > 0) {
                    wg_wait<1>();
                    if (lane < 2) mbar_arrive_cluster(b_empty + 8 * ((it - 1) & 3), lane);
                }
            }
            wg_wait<0>();
            if (lane < 2) mbar_arrive_cluster(b_empty + 8 * ((t * 8 + 7) & 3), lane);
#pragma unroll
            for (int nh = 0; nh < 2; nh++) {
                if ((tid & 127) == 0) bulk_wait_read<0>();
                named_sync(1 + wg, 128);
                store_slab64(stg, (warp & 3) * 16, acc[0] + nh * 32, 1.f, 1.f, lane);
                store_slab64(stg, 64 + (warp & 3) * 16, acc[1] + nh * 32, 1.f, 1.f, lane);
                fence_proxy_async();
                named_sync(1 + wg, 128);
                if ((tid & 127) == 0) {
                    tma_store_2d(&tm_kv_st, stg, ng * 1024 + t * 128 + nh * 64, m0);
                    bulk_commit();
                }
            }
        }
        if ((tid & 127) == 0) bulk_wait<0>();
        __syncwarp();
        cluster_sync_all();
    }
}
constexpr int AT_NS = 6;
constexpr int AT_SMEM = AT_NS * 32768 + 32768 + 256 + 1024;
constexpr int AT_ITEMS = 512;

DEVI uint32_t hmax2(uint32_t a, uint32_t b) { uint32_t r; asm("max.bf16x2 %0, %1, %2;" : "=r"(r) : "r"(a), "r"(b)); return r; }
DEVI uint32_t hmul2(uint32_t a, uint32_t b) { uint32_t r; asm("mul.rn.bf16x2 %0, %1, %2;" : "=r"(r) : "r"(a), "r"(b)); return r; }
DEVI uint32_t hfma2(uint32_t a, uint32_t b, uint32_t c) { uint32_t r; asm("fma.rn.bf16x2 %0, %1, %2, %3;" : "=r"(r) : "r"(a), "r"(b), "r"(c)); return r; }
DEVI float blo(uint32_t v) { return __uint_as_float(v << 16); }
DEVI float bhi(uint32_t v) { return __uint_as_float(v & 0xffff0000u); }

template <bool FIRST>
DEVI void softmax_tile(float* s, float& m0, float& m1, float& l0, float& l1, float& al0, float& al1) {
    const uint32_t HI = 0x3DB53DB5u;
    const uint32_t LO = 0x371E371Eu;
    const float L2E = 1.4426950408889634f;
    uint32_t x0 = 0xFF80FF80u, x1 = 0xFF80FF80u;
#pragma unroll
    for (int j = 0; j < 16; j++) {
        uint32_t a = pack_bf16(s[4 * j], s[4 * j + 1]), b = pack_bf16(s[4 * j + 2], s[4 * j + 3]);
        a = hfma2(a, HI, hmul2(a, LO));
        b = hfma2(b, HI, hmul2(b, LO));
        s[4 * j] = __uint_as_float(a); s[4 * j + 2] = __uint_as_float(b);
        x0 = hmax2(x0, a); x1 = hmax2(x1, b);
    }
    uint32_t x = hmax2(__byte_perm(x0, x1, 0x5410), __byte_perm(x0, x1, 0x7632));
    x = hmax2(x, __shfl_xor_sync(~0u, x, 1));
    x = hmax2(x, __shfl_xor_sync(~0u, x, 2));
    float n0 = blo(x), n1 = bhi(x);
    if (!FIRST) {
        n0 = fmaxf(n0, m0); n1 = fmaxf(n1, m1);
        al0 = ex2((m0 - n0) * L2E); al1 = ex2((m1 - n1) * L2E);
    }
    m0 = n0; m1 = n1;
    const float c0 = -n0 * L2E, c1 = -n1 * L2E;
    float s0 = 0.f, s1 = 0.f;
#pragma unroll
    for (int j = 0; j < 16; j++) {
        uint32_t a = __float_as_uint(s[4 * j]), b = __float_as_uint(s[4 * j + 2]);
        float e0 = ex2(fmaf(blo(a), L2E, c0)), e1 = ex2(fmaf(bhi(a), L2E, c0));
        float e2 = ex2(fmaf(blo(b), L2E, c1)), e3 = ex2(fmaf(bhi(b), L2E, c1));
        s0 += e0 + e1; s1 += e2 + e3;
        s[4 * j] = e0; s[4 * j + 1] = e1; s[4 * j + 2] = e2; s[4 * j + 3] = e3;
    }
    if (FIRST) { l0 = s0; l1 = s1; }
    else { l0 = fmaf(l0, al0, s0); l1 = fmaf(l1, al1, s1); }
}

struct Ring {
    int st; uint32_t ph;
    DEVI void next() { if (++st == AT_NS) { st = 0; ph ^= 1; } }
};

__global__ void __launch_bounds__(384, 1)
attn_kernel(const __grid_constant__ CUtensorMap tm_x, const __grid_constant__ CUtensorMap tm_wq,
            const __grid_constant__ CUtensorMap tm_kv, const __grid_constant__ CUtensorMap tm_ctx_st) {
    extern __shared__ uint8_t smem_raw[];
    const uint32_t sb = (smem_u32(smem_raw) + 1023) & ~1023u;
    const uint32_t sO = sb + AT_NS * 32768, bars = sO + 32768;
    const uint32_t full = bars, empty = bars + 64;
    volatile int* slots = reinterpret_cast<volatile int*>(smem_raw + (bars + 128 - smem_u32(smem_raw)));
    const int tid = threadIdx.x, warp = tid >> 5, lane = tid & 31, wg = tid >> 7;
    if (tid == 0) {
        for (int i = 0; i < AT_NS; i++) { mbar_init(full + 8 * i, 1); mbar_init(empty + 8 * i, 8); }
        fence_barrier_init();
    }
    __syncthreads();
    if (wg == 2) {
        reg_dec<24>();
        if (warp == 8 && lane == 0) {
            Ring r{0, 1};
            int n = 0;
            while (true) {
                int idx = (int)atomicInc(&g_sched, AT_ITEMS + gridDim.x - 1);
                mbar_wait(empty + 8 * r.st, r.ph);
                if (idx >= AT_ITEMS) {
                    slots[n & 3] = -1;
                    mbar_arrive(full + 8 * r.st);
                    break;
                }
                slots[n & 3] = idx;
                const int qi = 15 - (idx >> 5), h = idx & 31;
                for (int kc = 0; kc < 8; kc++) {
                    if (kc) mbar_wait(empty + 8 * r.st, r.ph);
                    const uint32_t fb = full + 8 * r.st, dst = sb + r.st * 32768;
                    mbar_expect_tx(fb, 32768);
                    tma_load_2d(dst, &tm_x, kc * 64, qi * 128, fb);
                    tma_load_2d(dst + 16384, &tm_wq, h * 128, kc * 64, fb);
                    tma_load_2d(dst + 24576, &tm_wq, h * 128 + 64, kc * 64, fb);
                    r.next();
                }
                if (n == 0) { pdl_wait(); pdl_launch(); }
                for (int j = qi; j >= -1; j--) {
#pragma unroll
                    for (int v = 0; v < 2; v++) {
                        const int jj = j + v;
                        if (jj < 0 || jj > qi || (v == 0 && j < 0)) continue;
                        mbar_wait(empty + 8 * r.st, r.ph);
                        const uint32_t fb = full + 8 * r.st, dst = sb + r.st * 32768;
                        mbar_expect_tx(fb, 32768);
                        tma_load_2d(dst, &tm_kv, v * HDALL + h * 128, jj * 128, fb);
                        tma_load_2d(dst + 16384, &tm_kv, v * HDALL + h * 128 + 64, jj * 128, fb);
                        r.next();
                    }
                }
                n++;
            }
            if (n == 0) { pdl_wait(); pdl_launch(); }
        }
    } else {
        reg_inc<240>();
        Ring r{0, 0};
        float o[64], s[64];
        uint32_t qf[32], pa[32];
        const int g = lane >> 2, t = lane & 3, wq = warp & 3;
        const uint32_t stg = sO + wg * 16384;
        if (wg == 1) named_arrive(3, 256);
        for (int n = 0;; n++) {
            mbar_wait(full + 8 * r.st, r.ph);
            const int idx = slots[n & 3];
            if (idx < 0) break;
            const int qi = 15 - (idx >> 5), h = idx & 31;
#pragma unroll 1
            for (int kc = 0; kc < 8; kc++) {
                if (kc) mbar_wait(full + 8 * r.st, r.ph);
                wg_fence();
                const uint32_t base = sb + r.st * 32768;
                const uint64_t da = desc_kmajor(base + wg * 8192), db = desc_mnmajor(base + 16384, 8192);
#pragma unroll
                for (int k = 0; k < 4; k++) wgmma_ss128<1>(s, da + k * 2, db + k * 128, (kc | k) != 0);
                wg_commit();
                if (kc) {
                    wg_wait<1>();
                    if (lane == 0) mbar_arrive(empty + 8 * (r.st == 0 ? AT_NS - 1 : r.st - 1));
                }
                r.next();
            }
            wg_wait<0>();
            if (lane == 0) mbar_arrive(empty + 8 * (r.st == 0 ? AT_NS - 1 : r.st - 1));
#pragma unroll
            for (int i = 0; i < 32; i++) qf[i] = pack_bf16(s[2 * i], s[2 * i + 1]);
            float m0, m1, l0, l1, al0, al1;
            auto issue_qk = [&]() {
                mbar_wait(full + 8 * r.st, r.ph);
                wg_fence();
                const uint64_t db = desc_kmajor(sb + r.st * 32768);
#pragma unroll
                for (int k = 0; k < 8; k++) wgmma_rs128<0>(s, qf + 4 * k, db + (k >> 2) * 1024 + (k & 3) * 2, k != 0);
                wg_commit();
            };
            auto issue_pv = [&](const uint32_t* p, int st, uint32_t ph, int acc) {
                mbar_wait(full + 8 * st, ph);
                wg_fence();
                const uint64_t db = desc_mnmajor(sb + st * 32768, 16384);
#pragma unroll
                for (int k = 0; k < 8; k++) wgmma_rs128<1>(o, p + 4 * k, db + k * 128, acc | k);
                wg_commit();
            };
            issue_qk();
            wg_wait<0>();
            if (lane == 0) mbar_arrive(empty + 8 * r.st);
            r.next();
            {
                const int row = wg * 64 + wq * 16 + g;
#pragma unroll
                for (int j = 0; j < 16; j++) {
                    const int c = 8 * j + 2 * t;
                    if (c > row) s[4 * j] = -INFINITY;
                    if (c + 1 > row) s[4 * j + 1] = -INFINITY;
                    if (c > row + 8) s[4 * j + 2] = -INFINITY;
                    if (c + 1 > row + 8) s[4 * j + 3] = -INFINITY;
                }
            }
            softmax_tile<true>(s, m0, m1, l0, l1, al0, al1);
#pragma unroll
            for (int i = 0; i < 32; i++) pa[i] = pack_bf16(s[2 * i], s[2 * i + 1]);
            int first = 0;
#pragma unroll 1
            for (int j = qi; j >= 1; j--) {
                named_sync(3 + wg, 256);
                issue_qk();
                const int kst = r.st;
                r.next();
                issue_pv(pa, r.st, r.ph, first);
                named_arrive(3 + (wg ^ 1), 256);
                wg_wait<1>();
                if (lane == 0) mbar_arrive(empty + 8 * kst);
                softmax_tile<false>(s, m0, m1, l0, l1, al0, al1);
                wg_wait<0>();
                if (lane == 0) mbar_arrive(empty + 8 * r.st);
                r.next();
#pragma unroll
                for (int i = 0; i < 32; i++) pa[i] = pack_bf16(s[2 * i], s[2 * i + 1]);
#pragma unroll
                for (int i = 0; i < 16; i++) {
                    o[4 * i] *= al0; o[4 * i + 1] *= al0; o[4 * i + 2] *= al1; o[4 * i + 3] *= al1;
                }
                first = 1;
            }
            issue_pv(pa, r.st, r.ph, first);
            l0 += __shfl_xor_sync(~0u, l0, 1); l0 += __shfl_xor_sync(~0u, l0, 2);
            l1 += __shfl_xor_sync(~0u, l1, 1); l1 += __shfl_xor_sync(~0u, l1, 2);
            const float i0 = 1.f / l0, i1 = 1.f / l1;
            if ((tid & 127) == 0) bulk_wait_read<0>();
            named_sync(1 + wg, 128);
            wg_wait<0>();
            if (lane == 0) mbar_arrive(empty + 8 * r.st);
            r.next();
            store_slab64(stg, wq * 16, o, i0, i1, lane);
            store_slab64(stg + 8192, wq * 16, o + 32, i0, i1, lane);
            fence_proxy_async();
            named_sync(1 + wg, 128);
            if ((tid & 127) == 0) {
                tma_store_2d(&tm_ctx_st, stg, h * 128, qi * 128 + wg * 64);
                tma_store_2d(&tm_ctx_st, stg + 8192, h * 128 + 64, qi * 128 + wg * 64);
                bulk_commit();
            }
        }
        if ((tid & 127) == 0) bulk_wait<0>();
    }
}
constexpr int OP_NS = 4;
constexpr int OP_ULD = 41 * 16;
constexpr int OP_UCH = 8 * OP_ULD;
constexpr int OP_SMEM = OP_NS * 32768 + 32768 + 4 * WTAB * 4 + 4 * OP_UCH + 256 + 1024;

template <int N> DEVI void wgmma_conv(float* d, const uint32_t* a, uint64_t db);
template <> DEVI void wgmma_conv<32>(float* d, const uint32_t* a, uint64_t db) {
    asm volatile("wgmma.mma_async.sync.aligned.m64n32k16.f32.bf16.bf16 {%0,%1,%2,%3,%4,%5,%6,%7,%8,%9,%10,%11,%12,%13,%14,%15}, "
                 "{%16,%17,%18,%19}, %20, 1, 1, 1, 0;"
                 : ACC8(d, 0), ACC8(d, 8) : "r"(a[0]), "r"(a[1]), "r"(a[2]), "r"(a[3]), "l"(db));
}
template <> DEVI void wgmma_conv<24>(float* d, const uint32_t* a, uint64_t db) {
    asm volatile("wgmma.mma_async.sync.aligned.m64n24k16.f32.bf16.bf16 {%0,%1,%2,%3,%4,%5,%6,%7,%8,%9,%10,%11}, "
                 "{%12,%13,%14,%15}, %16, 1, 1, 1, 0;"
                 : ACC8(d, 0), "+f"(d[8]), "+f"(d[9]), "+f"(d[10]), "+f"(d[11]) : "r"(a[0]), "r"(a[1]), "r"(a[2]), "r"(a[3]), "l"(db));
}
template <> DEVI void wgmma_conv<16>(float* d, const uint32_t* a, uint64_t db) {
    asm volatile("wgmma.mma_async.sync.aligned.m64n16k16.f32.bf16.bf16 {%0,%1,%2,%3,%4,%5,%6,%7}, "
                 "{%8,%9,%10,%11}, %12, 1, 1, 1, 0;"
                 : ACC8(d, 0) : "r"(a[0]), "r"(a[1]), "r"(a[2]), "r"(a[3]), "l"(db));
}
template <> DEVI void wgmma_conv<8>(float* d, const uint32_t* a, uint64_t db) {
    asm volatile("wgmma.mma_async.sync.aligned.m64n8k16.f32.bf16.bf16 {%0,%1,%2,%3}, "
                 "{%4,%5,%6,%7}, %8, 1, 1, 1, 0;"
                 : "+f"(d[0]), "+f"(d[1]), "+f"(d[2]), "+f"(d[3]) : "r"(a[0]), "r"(a[1]), "r"(a[2]), "r"(a[3]), "l"(db));
}
DEVI uint32_t lds32(uint32_t a) { uint32_t v; asm volatile("ld.shared.b32 %0, [%1];" : "=r"(v) : "r"(a)); return v; }
DEVI uint32_t lds16(uint32_t a) { uint16_t v; asm volatile("ld.shared.b16 %0, [%1];" : "=h"(v) : "r"(a)); return v; }

template <int J> DEVI void conv_pair(float* acc, uint32_t* f, uint32_t wa, uint64_t du, int c) {
#pragma unroll
    for (int i = 0; i < 8; i++) {
        f[4 * i] = lds32(wa + i * 64); f[4 * i + 1] = lds32(wa + i * 64 + 32);
        f[4 * i + 2] = lds32(wa + i * 64 - 32); f[4 * i + 3] = lds32(wa + i * 64);
    }
    wg_fence();
#pragma unroll
    for (int i = 0; i < 8; i++) {
        const int kk = 3 - (i & 3);
        const uint64_t db = du + (uint64_t)(kk * 2 * (OP_ULD / 16) + (i >> 2) + c);
        wgmma_conv<32 - 8 * J>(acc, f + 4 * i, db);
    }
    wg_commit();
}
template <int J> DEVI void conv_group(float* acc, uint32_t wa, uint64_t du) {
    uint32_t fa[32], fb[32];
#pragma unroll
    for (int h = 0; h < 2; h++) {
        const int c = 8 * J + 4 * h;
        conv_pair<J>(acc, fa, wa + c * 256, du, c);
        wg_wait<1>();
        conv_pair<J>(acc, fb, wa + (c + 2) * 256, du, c + 2);
        wg_wait<1>();
    }
    wg_wait<0>();
}

__global__ void __cluster_dims__(4, 1, 1) __launch_bounds__(512, 1)
outproj_kernel(const __grid_constant__ CUtensorMap tm_ctx, const __grid_constant__ CUtensorMap tm_wo,
               const __grid_constant__ CUtensorMap tm_out, SsmParams sp, bf16* __restrict__ out) {
    extern __shared__ uint8_t smem_raw[];
    const uint32_t sb = (smem_u32(smem_raw) + 1023) & ~1023u;
    const uint32_t sX = sb + OP_NS * 32768, sW = sX + 32768, sU = sW + 4 * WTAB * 4, bars = sU + 4 * OP_UCH;
    const uint32_t full = bars, empty = bars + 64, xfull = bars + 128, wfull = bars + 136;
    const int tid = threadIdx.x, warp = tid >> 5, lane = tid & 31, wg = tid >> 7;
    const uint32_t rank = cluster_rank();
    const uint32_t kr = rank & 1, nr = rank >> 1;
    const int cl = blockIdx.x >> 2;
    const int m0 = (cl >> 1) * 128, n0 = ((cl & 1) * 2 + nr) * 128, k0 = kr * 2048;
    if (tid == 0) {
        for (int i = 0; i < OP_NS; i++) { mbar_init(full + 8 * i, 1); mbar_init(empty + 8 * i, 16); }
        mbar_init(xfull, 256);
        mbar_init(wfull, 1);
        fence_barrier_init();
    }
    __syncthreads();
    cluster_sync_all();
    if (wg == 3) {
        reg_dec<40>();
        if (tid == 384) {
            mbar_expect_tx(wfull, 4 * WTAB * 4);
            bulk_load(sW, g_wtab + blockIdx.x * 4 * WTAB, 4 * WTAB * 4, wfull);
            const uint16_t mask = (uint16_t)(5u << kr);
            for (int it = 0; it < OP_NS; it++) {
                const uint32_t dst = sb + it * 32768, fb = full + 8 * it;
                mbar_expect_tx(fb, 32768);
                tma_load_2d(dst + 16384, &tm_wo, n0, k0 + it * 64, fb);
                tma_load_2d(dst + 24576, &tm_wo, n0 + 64, k0 + it * 64, fb);
            }
            for (int it = OP_NS; it < 32; it++) {
                tma_prefetch_2d(&tm_wo, n0 + (cl >> 4) * 64, k0 + it * 64);
            }
            pdl_wait();
            for (int it = 0; it < 32; it++) {
                const int st = it & (OP_NS - 1);
                const uint32_t dst = sb + st * 32768, fb = full + 8 * st;
                if (it >= OP_NS) {
                    mbar_wait_cluster(empty + 8 * st, ((it / OP_NS) & 1) ^ 1);
                    mbar_expect_tx(fb, 32768);
                    tma_load_2d(dst + 16384, &tm_wo, n0, k0 + it * 64, fb);
                    tma_load_2d(dst + 24576, &tm_wo, n0 + 64, k0 + it * 64, fb);
                }
                tma_load_2d_mc(dst + nr * 8192, &tm_ctx, k0 + it * 64, m0 + nr * 64, fb, mask);
            }
        }
        __syncwarp();
    } else if (wg == 2) {
        reg_inc<208>();
        const int ct = tid & 127, wq = warp & 3, g = lane >> 2, t = lane & 3;
        const int d0 = blockIdx.x * 4;
        uint2 v[2][8];
#pragma unroll
        for (int h = 0; h < 2; h++)
#pragma unroll
            for (int i = 0; i < 8; i++)
                v[h][i] = __ldg(reinterpret_cast<const uint2*>(sp.u + (size_t)((ct + 128 * h) * 8 + i) * SSM_D + d0));
        for (int i = ct; i < 4 * 8 * 8; i += 128) {
            const uint32_t a = sU + (i >> 3) * OP_ULD + (32 + (i & 7)) * 16;
            asm volatile("st.shared.v4.b32 [%0], {%1,%1,%1,%1};" ::"r"(a), "r"(0) : "memory");
        }
#pragma unroll
        for (int h = 0; h < 2; h++) {
            const int q = ct + 128 * h;
            const uint32_t a = sU + (q & 7) * OP_ULD + (31 - (q >> 3)) * 16;
#pragma unroll
            for (int c = 0; c < 4; c++) {
                uint32_t w[4];
#pragma unroll
                for (int i = 0; i < 4; i++) {
                    const uint32_t lo = (c & 2) ? v[h][2 * i].y : v[h][2 * i].x, hi = (c & 2) ? v[h][2 * i + 1].y : v[h][2 * i + 1].x;
                    w[i] = __byte_perm(lo, hi, (c & 1) ? 0x7632 : 0x5410);
                }
                asm volatile("st.shared.v4.b32 [%0], {%1,%2,%3,%4};" ::"r"(a + c * OP_UCH), "r"(w[0]), "r"(w[1]), "r"(w[2]), "r"(w[3]) : "memory");
            }
        }
        const uint2 dsk = __ldg(reinterpret_cast<const uint2*>(sp.dskip + d0));
        fence_proxy_async();
        named_sync(3, 128);
        mbar_wait(wfull, 0);
        uint32_t res[16][2];
#pragma unroll
        for (int c = 0; c < 4; c++) {
            float acc[16];
#pragma unroll
            for (int i = 0; i < 16; i++) acc[i] = 0.f;
            const uint32_t wa = sW + (c * WTAB + 64 + 16 * (wq - 3) + g - 2 * t) * 4;
            const uint64_t du = make_desc(sU + c * OP_UCH, OP_ULD, 128, 0);
            conv_group<0>(acc, wa, du);
            conv_group<1>(acc, wa, du);
            conv_group<2>(acc, wa, du);
            conv_group<3>(acc, wa, du);
            const uint32_t dw = (c & 2) ? dsk.y : dsk.x;
            const float D = (c & 1) ? bhi(dw) : blo(dw);
#pragma unroll
            for (int i = 0; i < 16; i++) {
                const int n = 8 * (i >> 2) + 2 * t + (i & 1), j = 2 * wq + ((i >> 1) & 1);
                const float u = __uint_as_float(lds16(sU + c * OP_UCH + j * OP_ULD + n * 16 + g * 2) << 16);
                const uint32_t o = __bfloat16_as_ushort(__float2bfloat16_rn(rbf(acc[i]) + rbf(u * D)));
                if (c & 1) res[i][c >> 1] |= o << 16; else res[i][c >> 1] = o;
            }
        }
#pragma unroll
        for (int i = 0; i < 16; i++) {
            const int a = 31 - (8 * (i >> 2) + 2 * t + (i & 1)), b = 16 * wq + g + 8 * ((i >> 1) & 1);
            *reinterpret_cast<uint2*>(out + (size_t)(64 * a + b) * 1024 + 512 + d0) = make_uint2(res[i][0], res[i][1]);
        }
    } else {
        float acc[64];
#pragma unroll 1
        for (int it = 0; it < 32; it++) {
            const int st = it & (OP_NS - 1);
            mbar_wait(full + 8 * st, (it / OP_NS) & 1);
            wg_fence();
            const uint32_t base = sb + st * 32768;
            const uint64_t da = desc_kmajor(base + wg * 8192), db = desc_mnmajor(base + 16384, 8192);
#pragma unroll
            for (int k = 0; k < 4; k++) wgmma_ss128<1>(acc, da + k * 2, db + k * 128, (it | k) != 0);
            wg_commit();
            if (it > 0 && it + OP_NS - 1 < 32) {
                wg_wait<1>();
                if (lane < 2) mbar_arrive_cluster(empty + 8 * ((it - 1) & (OP_NS - 1)), kr + 2 * lane);
            }
        }
        wg_wait<0>();
        uint32_t peer;
        asm volatile("mapa.shared::cluster.u32 %0, %1, %2;" : "=r"(peer) : "r"(sX + tid * 16), "r"(rank ^ 1));
#pragma unroll
        for (int i = 0; i < 8; i++) {
            const float* s = acc + 4 * i;
            const float a = kr ? s[0] : s[32], b = kr ? s[1] : s[33], c = kr ? s[2] : s[34], d = kr ? s[3] : s[35];
            asm volatile("st.shared::cluster.v4.f32 [%0], {%1,%2,%3,%4};" ::"r"(peer + i * 4096), "f"(a), "f"(b), "f"(c), "f"(d) : "memory");
        }
        mbar_arrive_cluster(xfull, rank ^ 1);
        mbar_wait_cluster(xfull, 0);
        float r[32];
#pragma unroll
        for (int i = 0; i < 8; i++) {
            float a, b, c, d;
            asm volatile("ld.shared.v4.f32 {%0,%1,%2,%3}, [%4];" : "=f"(a), "=f"(b), "=f"(c), "=f"(d) : "r"(sX + tid * 16 + i * 4096));
            const float* s = acc + 4 * i;
            r[4 * i] = a + (kr ? s[32] : s[0]); r[4 * i + 1] = b + (kr ? s[33] : s[1]);
            r[4 * i + 2] = c + (kr ? s[34] : s[2]); r[4 * i + 3] = d + (kr ? s[35] : s[3]);
        }
        const uint32_t stg = sb + wg * 8192;
        store_slab64(stg, (warp & 3) * 16, r, 1.f, 1.f, lane);
        fence_proxy_async();
        named_sync(1 + wg, 128);
        if ((tid & 127) == 0) {
            tma_store_2d(&tm_out, stg, n0 + kr * 64, m0 + wg * 64);
            bulk_commit();
            bulk_wait<0>();
        }
    }
    __syncwarp();
    cluster_sync_all();
}

typedef CUresult (*EncodeFn)(CUtensorMap*, CUtensorMapDataType, cuuint32_t, void*, const cuuint64_t*, const cuuint64_t*,
                             const cuuint32_t*, const cuuint32_t*, CUtensorMapInterleave, CUtensorMapSwizzle,
                             CUtensorMapL2promotion, CUtensorMapFloatOOBfill);

static void make_map(EncodeFn fn, CUtensorMap* m, const void* p, uint64_t cols, uint64_t rows, uint32_t box_rows) {
    cuuint64_t dims[2] = {cols, rows};
    cuuint64_t strides[1] = {cols * 2};
    cuuint32_t box[2] = {64, box_rows};
    cuuint32_t es[2] = {1, 1};
    fn(m, CU_TENSOR_MAP_DATA_TYPE_BFLOAT16, 2, const_cast<void*>(p), dims, strides, box, es, CU_TENSOR_MAP_INTERLEAVE_NONE,
       CU_TENSOR_MAP_SWIZZLE_128B, CU_TENSOR_MAP_L2_PROMOTION_L2_256B, CU_TENSOR_MAP_FLOAT_OOB_FILL_NONE);
}

extern "C" void kernel_launch(void* const* d_in, const int* in_sizes, int n_in, void* d_out, int out_size) {
    void* fp = nullptr;
    cudaDriverEntryPointQueryResult qr;
    cudaGetDriverEntryPoint("cuTensorMapEncodeTiled", &fp, cudaEnableDefault, &qr);
    EncodeFn fn = (EncodeFn)fp;
    void *p_kv, *p_ctx;
    cudaGetSymbolAddress(&p_kv, g_kv);
    cudaGetSymbolAddress(&p_ctx, g_ctx);
    CUtensorMap tm_x, tm_c, tm_wq, tm_wk, tm_wv, tm_wo, tm_kv, tm_ctx, tm_out;
    make_map(fn, &tm_x, d_in[0], DM, SEQ, 128);
    make_map(fn, &tm_c, d_in[1], DM, SEQ, 128);
    make_map(fn, &tm_wq, d_in[2], HDALL, DM, 64);
    make_map(fn, &tm_wk, d_in[3], HDALL, DM, 64);
    make_map(fn, &tm_wv, d_in[4], HDALL, DM, 64);
    make_map(fn, &tm_wo, d_in[5], DM, HDALL, 64);
    make_map(fn, &tm_kv, p_kv, 2 * HDALL, SEQ, 128);
    make_map(fn, &tm_ctx, p_ctx, HDALL, SEQ, 64);
    make_map(fn, &tm_out, d_out, 1024, SEQ, 64);
    SsmParams sp;
    sp.u = (const bf16*)d_in[6]; sp.lar = (const bf16*)d_in[7]; sp.aim = (const bf16*)d_in[8];
    sp.cre = (const bf16*)d_in[9]; sp.cim = (const bf16*)d_in[10]; sp.ldt = (const bf16*)d_in[11]; sp.dskip = (const bf16*)d_in[12];
    cudaFuncSetAttribute(gemm_kv_kernel, cudaFuncAttributeMaxDynamicSharedMemorySize, G1_SMEM);
    cudaFuncSetAttribute(attn_kernel, cudaFuncAttributeMaxDynamicSharedMemorySize, AT_SMEM);
    cudaFuncSetAttribute(outproj_kernel, cudaFuncAttributeMaxDynamicSharedMemorySize, OP_SMEM);
    cudaStream_t st = cudaStreamPerThread;
    gemm_kv_kernel<<<128, G1_THREADS, G1_SMEM, st>>>(tm_c, tm_wk, tm_wv, tm_kv, sp);
    cudaLaunchAttribute at[1];
    at[0].id = cudaLaunchAttributeProgrammaticStreamSerialization;
    at[0].val.programmaticStreamSerializationAllowed = 1;
    cudaLaunchConfig_t cfg = {};
    cfg.stream = st; cfg.attrs = at; cfg.numAttrs = 1;
    cfg.gridDim = dim3(132); cfg.blockDim = dim3(384); cfg.dynamicSmemBytes = AT_SMEM;
    cudaLaunchKernelEx(&cfg, attn_kernel, tm_x, tm_wq, tm_kv, tm_ctx);
    cfg.gridDim = dim3(128); cfg.blockDim = dim3(512); cfg.dynamicSmemBytes = OP_SMEM;
    cudaLaunchKernelEx(&cfg, outproj_kernel, tm_ctx, tm_wo, tm_out, sp, (bf16*)d_out);
}
```

```cpp
#include <cuda_runtime.h>
#include <cuda_bf16.h>
#include <cuda.h>
#include <stdint.h>

typedef __nv_bfloat16 bf16;

#define DEVI __device__ __forceinline__

constexpr int SEQ = 2048, DM = 512, NH = 32, HD = 128, HDALL = NH * HD;
constexpr int SSM_D = 512, SSM_N = 128;
constexpr int WTAB = 2112;

__device__ bf16 g_kv[(size_t)SEQ * 2 * HDALL];
__device__ bf16 g_ctx[(size_t)SEQ * HDALL];
__device__ float g_kp[SSM_D * 648];
__device__ uint32_t g_wtab[SSM_D * WTAB];
__device__ unsigned int g_sched;

DEVI uint32_t smem_u32(const void* p) { return (uint32_t)__cvta_generic_to_shared(p); }
DEVI void mbar_init(uint32_t a, uint32_t cnt) { asm volatile("mbarrier.init.shared::cta.b64 [%0], %1;" ::"r"(a), "r"(cnt)); }
DEVI void mbar_expect_tx(uint32_t a, uint32_t bytes) {
    asm volatile("mbarrier.arrive.expect_tx.shared::cta.b64 _, [%0], %1;" ::"r"(a), "r"(bytes) : "memory");
}
DEVI void mbar_arrive(uint32_t a) { asm volatile("mbarrier.arrive.shared::cta.b64 _, [%0];" ::"r"(a) : "memory"); }
DEVI void mbar_arrive_cluster(uint32_t a, uint32_t cta) {
    asm volatile("{\n.reg .b32 r;\nmapa.shared::cluster.u32 r, %0, %1;\n"
                 "mbarrier.arrive.shared::cluster.b64 _, [r];\n}" ::"r"(a), "r"(cta) : "memory");
}
#define MBAR_WAIT_ASM(OP)                                                                              \
    asm volatile("{\n.reg .pred p, q;\n.reg .u32 t0, t1;\n" OP " p, [%0], %1;\n@p bra D_%=;\n"         \
                 "mov.u32 t0, %%globaltimer_lo;\nW_%=:\n" OP " p, [%0], %1;\n"                         \
                 "mov.u32 t1, %%globaltimer_lo;\nsub.u32 t1, t1, t0;\n"                                \
                 "setp.gt.or.u32 q, t1, 4000000, p;\n@!q bra W_%=;\nD_%=:\n}" ::"r"(a), "r"(parity) : "memory")
DEVI void mbar_wait(uint32_t a, uint32_t parity) { MBAR_WAIT_ASM("mbarrier.try_wait.parity.shared::cta.b64"); }
DEVI void mbar_wait_cluster(uint32_t a, uint32_t parity) { MBAR_WAIT_ASM("mbarrier.try_wait.parity.acquire.cluster.shared::cta.b64"); }
DEVI void fence_barrier_init() { asm volatile("fence.mbarrier_init.release.cluster;" ::: "memory"); }
DEVI void fence_proxy_async() { asm volatile("fence.proxy.async.shared::cta;" ::: "memory"); }
DEVI void cluster_sync_all() {
    asm volatile("barrier.cluster.arrive.release.aligned;\nbarrier.cluster.wait.acquire.aligned;" ::: "memory");
}
DEVI uint32_t cluster_rank() { uint32_t r; asm volatile("mov.u32 %0, %%cluster_ctarank;" : "=r"(r)); return r; }
DEVI void tma_load_2d(uint32_t dst, const CUtensorMap* m, int c0, int c1, uint32_t bar) {
    asm volatile("cp.async.bulk.tensor.2d.shared::cluster.global.mbarrier::complete_tx::bytes [%0], [%1, {%3, %4}], [%2];"
                 ::"r"(dst), "l"(m), "r"(bar), "r"(c0), "r"(c1) : "memory");
}
DEVI void tma_load_2d_mc(uint32_t dst, const CUtensorMap* m, int c0, int c1, uint32_t bar, uint16_t mask) {
    asm volatile("cp.async.bulk.tensor.2d.shared::cluster.global.mbarrier::complete_tx::bytes.multicast::cluster [%0], [%1, {%3, %4}], [%2], %5;"
                 ::"r"(dst), "l"(m), "r"(bar), "r"(c0), "r"(c1), "h"(mask) : "memory");
}
DEVI void tma_prefetch_2d(const CUtensorMap* m, int c0, int c1) {
    asm volatile("cp.async.bulk.prefetch.tensor.2d.L2.global [%0, {%1, %2}];" ::"l"(m), "r"(c0), "r"(c1) : "memory");
}
DEVI void tma_store_2d(const CUtensorMap* m, uint32_t src, int c0, int c1) {
    asm volatile("cp.async.bulk.tensor.2d.global.shared::cta.bulk_group [%0, {%2, %3}], [%1];"
                 ::"l"(m), "r"(src), "r"(c0), "r"(c1) : "memory");
}
DEVI void bulk_load(uint32_t dst, const void* src, uint32_t bytes, uint32_t bar) {
    asm volatile("cp.async.bulk.shared::cluster.global.mbarrier::complete_tx::bytes [%0], [%1], %2, [%3];"
                 ::"r"(dst), "l"(src), "r"(bytes), "r"(bar) : "memory");
}
DEVI void bulk_commit() { asm volatile("cp.async.bulk.commit_group;" ::: "memory"); }
template <int N> DEVI void bulk_wait_read() { asm volatile("cp.async.bulk.wait_group.read %0;" ::"n"(N) : "memory"); }
template <int N> DEVI void bulk_wait() { asm volatile("cp.async.bulk.wait_group %0;" ::"n"(N) : "memory"); }
DEVI void prefetch_tmap(const CUtensorMap* m) { asm volatile("prefetch.tensormap [%0];" ::"l"(m) : "memory"); }
DEVI void named_sync(int id, int n) { asm volatile("bar.sync %0, %1;" ::"r"(id), "r"(n) : "memory"); }
DEVI void named_arrive(int id, int n) { asm volatile("bar.arrive %0, %1;" ::"r"(id), "r"(n) : "memory"); }
DEVI void pdl_wait() { asm volatile("griddepcontrol.wait;" ::: "memory"); }
DEVI void pdl_launch() { asm volatile("griddepcontrol.launch_dependents;" ::: "memory"); }
template <int R> DEVI void reg_inc() { asm volatile("setmaxnreg.inc.sync.aligned.u32 %0;" ::"n"(R)); }
template <int R> DEVI void reg_dec() { asm volatile("setmaxnreg.dec.sync.aligned.u32 %0;" ::"n"(R)); }

DEVI void wg_fence() { asm volatile("wgmma.fence.sync.aligned;" ::: "memory"); }
DEVI void wg_commit() { asm volatile("wgmma.commit_group.sync.aligned;" ::: "memory"); }
template <int N> DEVI void wg_wait() { asm volatile("wgmma.wait_group.sync.aligned %0;" ::"n"(N) : "memory"); }

DEVI uint64_t make_desc(uint32_t addr, uint32_t lbo, uint32_t sbo, uint32_t swz) {
    return (uint64_t)((addr & 0x3FFFF) >> 4) | ((uint64_t)(lbo >> 4) << 16) | ((uint64_t)(sbo >> 4) << 32) | ((uint64_t)swz << 62);
}
DEVI uint64_t desc_kmajor(uint32_t addr) { return make_desc(addr, 16, 1024, 1); }
DEVI uint64_t desc_mnmajor(uint32_t addr, uint32_t lbo) { return make_desc(addr, lbo, 1024, 1); }

#define ACC8(d, o) "+f"(d[o + 0]), "+f"(d[o + 1]), "+f"(d[o + 2]), "+f"(d[o + 3]), "+f"(d[o + 4]), "+f"(d[o + 5]), "+f"(d[o + 6]), "+f"(d[o + 7])
#define ACC64(d) ACC8(d, 0), ACC8(d, 8), ACC8(d, 16), ACC8(d, 24), ACC8(d, 32), ACC8(d, 40), ACC8(d, 48), ACC8(d, 56)
#define R64 "{%0,%1,%2,%3,%4,%5,%6,%7,%8,%9,%10,%11,%12,%13,%14,%15,%16,%17,%18,%19,%20,%21,%22,%23,%24,%25,%26,%27,%28,%29,%30,%31," \
            "%32,%33,%34,%35,%36,%37,%38,%39,%40,%41,%42,%43,%44,%45,%46,%47,%48,%49,%50,%51,%52,%53,%54,%55,%56,%57,%58,%59,%60,%61,%62,%63}"

template <int TB> DEVI void wgmma_ss128(float* d, uint64_t da, uint64_t db, int acc) {
    asm volatile("{\n.reg .pred p;\nsetp.ne.b32 p, %66, 0;\n"
                 "wgmma.mma_async.sync.aligned.m64n128k16.f32.bf16.bf16 " R64 ", %64, %65, p, 1, 1, 0, %67;\n}"
                 : ACC64(d) : "l"(da), "l"(db), "r"(acc), "n"(TB));
}
template <int TB> DEVI void wgmma_rs128(float* d, const uint32_t* a, uint64_t db, int acc) {
    asm volatile("{\n.reg .pred p;\nsetp.ne.b32 p, %69, 0;\n"
                 "wgmma.mma_async.sync.aligned.m64n128k16.f32.bf16.bf16 " R64 ", {%64,%65,%66,%67}, %68, p, 1, 1, %70;\n}"
                 : ACC64(d) : "r"(a[0]), "r"(a[1]), "r"(a[2]), "r"(a[3]), "l"(db), "r"(acc), "n"(TB));
}
DEVI uint32_t pack_bf16(float lo, float hi) {
    uint32_t r;
    asm("cvt.rn.bf16x2.f32 %0, %1, %2;" : "=r"(r) : "f"(hi), "f"(lo));
    return r;
}
DEVI void stmatrix_x4(uint32_t addr, uint32_t r0, uint32_t r1, uint32_t r2, uint32_t r3) {
    asm volatile("stmatrix.sync.aligned.m8n8.x4.shared.b16 [%0], {%1,%2,%3,%4};" ::"r"(addr), "r"(r0), "r"(r1), "r"(r2), "r"(r3) : "memory");
}
DEVI float ex2(float x) { float y; asm("ex2.approx.ftz.f32 %0, %1;" : "=f"(y) : "f"(x)); return y; }

DEVI void store_slab64(uint32_t base, int row0, const float* d, float s0, float s1, int lane) {
    int mi = lane >> 3, r = lane & 7;
    int row = row0 + (mi & 1) * 8 + r;
#pragma unroll
    for (int j = 0; j < 8; j += 2) {
        uint32_t r0 = pack_bf16(d[4 * j + 0] * s0, d[4 * j + 1] * s0);
        uint32_t r1 = pack_bf16(d[4 * j + 2] * s1, d[4 * j + 3] * s1);
        uint32_t r2 = pack_bf16(d[4 * j + 4] * s0, d[4 * j + 5] * s0);
        uint32_t r3 = pack_bf16(d[4 * j + 6] * s1, d[4 * j + 7] * s1);
        int chunk = j + (mi >> 1);
        stmatrix_x4(base + row * 128 + ((chunk ^ (row & 7)) << 4), r0, r1, r2, r3);
    }
}
struct cf { float x, y; };
DEVI cf cmul(cf a, cf b) { cf r; r.x = fmaf(a.x, b.x, -a.y * b.y); r.y = fmaf(a.x, b.y, a.y * b.x); return r; }
DEVI cf csq(cf a) { cf r; r.x = fmaf(a.x, a.x, -a.y * a.y); r.y = (a.x + a.x) * a.y; return r; }
DEVI cf cexp_(float re, float im) {
    float m = expf(re), s, c;
    sincosf(im, &s, &c);
    cf r; r.x = m * c; r.y = m * s; return r;
}
DEVI uint32_t tf32(float x) { uint32_t r; asm("cvt.rna.tf32.f32 %0, %1;" : "=r"(r) : "f"(x)); return r; }
DEVI void mma_tf32(float* c, cf lo, cf hi, uint32_t b0, uint32_t b1) {
    asm volatile("mma.sync.aligned.m16n8k8.row.col.f32.tf32.tf32.f32 {%0,%1,%2,%3}, {%4,%5,%6,%7}, {%8,%9}, {%0,%1,%2,%3};"
                 : "+f"(c[0]), "+f"(c[1]), "+f"(c[2]), "+f"(c[3])
                 : "r"(tf32(lo.x)), "r"(tf32(hi.x)), "r"(tf32(lo.y)), "r"(tf32(hi.y)), "r"(b0), "r"(b1));
}
DEVI float bf2f(bf16 v) { return __bfloat162float(v); }
DEVI float rbf(float v) { return __bfloat162float(__float2bfloat16_rn(v)); }

struct SsmParams { const bf16 *lar, *aim, *cre, *cim, *ldt, *dskip, *u; };

DEVI int kp_index(int l) {
    int p = (int)rbf((float)l);
    return p < 256 ? p : (p < 512 ? 128 + (p >> 1) : (p < 1024 ? 256 + (p >> 2) : 384 + (p >> 3)));
}

DEVI void ssm_kgen_warp(const SsmParams& P, int d, int lane) {
    const int g = lane >> 2, t = lane & 3;
    const float dt = rbf(expf(bf2f(P.ldt[d])));
    float ar[4], ai[4], cr[4], ci[4], gr[4], gi[4];
#pragma unroll
    for (int q = 0; q < 4; q++) {
        int n = d * SSM_N + 32 * q + lane;
        ar[q] = -rbf(expf(bf2f(P.lar[n]))) * dt;
        ai[q] = bf2f(P.aim[n]) * dt;
        cr[q] = 2.f * (bf2f(P.cre[n]) * dt);
        ci[q] = 2.f * (bf2f(P.cim[n]) * dt);
        cf G = cexp_(ar[q] * 64.f, ai[q] * 64.f);
        gr[q] = G.x; gi[q] = G.y;
    }
    float acc[5][4];
#pragma unroll
    for (int s = 0; s < 5; s++) { acc[s][0] = acc[s][1] = acc[s][2] = acc[s][3] = 0.f; }
    float klast = 0.f;
    const float gf = (float)g;
#pragma unroll
    for (int q = 0; q < 4; q++) {
#pragma unroll 2
        for (int g0 = 0; g0 < 8; g0++) {
            int src = (g0 << 2) | t;
            float a_r = __shfl_sync(~0u, ar[q], src), a_i = __shfl_sync(~0u, ai[q], src);
            cf C, G;
            C.x = __shfl_sync(~0u, cr[q], src); C.y = __shfl_sync(~0u, ci[q], src);
            G.x = __shfl_sync(~0u, gr[q], src); G.y = __shfl_sync(~0u, gi[q], src);
            cf E = cexp_(a_r * gf, a_i * gf);
            cf B = csq(csq(csq(E)));
            cf Y = cmul(C, B);
            uint32_t b0 = tf32(Y.x), b1 = tf32(-Y.y);
            cf EG = cmul(E, G);
            mma_tf32(acc[0], E, EG, b0, b1);
            cf G2 = csq(G);
            cf X = cmul(E, G2), Xh = cmul(EG, G2);
            mma_tf32(acc[1], X, Xh, b0, b1);
#pragma unroll
            for (int s = 2; s < 5; s++) {
                B = csq(B); X = csq(X); Xh = csq(Xh);
                Y = cmul(C, B);
                mma_tf32(acc[s], X, Xh, tf32(Y.x), tf32(-Y.y));
            }
            X = csq(X);
            klast += fmaf(C.x, X.x, -C.y * X.y);
        }
    }
    klast += __shfl_xor_sync(~0u, klast, 1);
    klast += __shfl_xor_sync(~0u, klast, 2);
    float* kp = g_kp + d * 648;
#pragma unroll
    for (int s = 0; s < 5; s++) {
        int b = 128 * s + g + 16 * t;
        kp[b] = acc[s][0]; kp[b + 8] = acc[s][1]; kp[b + 64] = acc[s][2]; kp[b + 72] = acc[s][3];
    }
    if (lane == 0) kp[640] = klast;
    __threadfence_block();
    __syncwarp();
    uint4* wt = reinterpret_cast<uint4*>(g_wtab + d * WTAB);
    for (int qd = lane; qd < WTAB / 4; qd += 32) {
        int o = qd * 4 - 64;
        float k[5];
#pragma unroll
        for (int e = 0; e < 5; e++) {
            int l = o - 1 + e;
            k[e] = l < 0 ? 0.f : __ldcg(kp + kp_index(l));
        }
        uint4 w;
        w.x = pack_bf16(k[1], k[0]); w.y = pack_bf16(k[2], k[1]); w.z = pack_bf16(k[3], k[2]); w.w = pack_bf16(k[4], k[3]);
        wt[qd] = w;
    }
}

constexpr int G1_THREADS = 512;
constexpr int G1_SMEM = 131072 + 4 * 16384 + 2 * 16384 + 256 + 1024;

__global__ void __cluster_dims__(2, 1, 1) __launch_bounds__(G1_THREADS, 1)
gemm_kv_kernel(const __grid_constant__ CUtensorMap tm_c, const __grid_constant__ CUtensorMap tm_wk,
               const __grid_constant__ CUtensorMap tm_wv, const __grid_constant__ CUtensorMap tm_kv_st, SsmParams sp) {
    extern __shared__ uint8_t smem_raw[];
    const uint32_t sb = (smem_u32(smem_raw) + 1023) & ~1023u;
    const uint32_t sA = sb, sB = sb + 131072, sC = sB + 65536, bars = sC + 32768;
    const uint32_t a_full = bars, b_full = bars + 64, b_empty = bars + 96;
    const int tid = threadIdx.x, warp = tid >> 5, lane = tid & 31, wg = tid >> 7;
    const uint32_t rank = cluster_rank();
    const int cl = blockIdx.x >> 1;
    const int m0 = ((cl & 7) * 2 + rank) * 128;
    const int ng = cl >> 3;
    if (tid == 0) {
        for (int i = 0; i < 8; i++) mbar_init(a_full + 8 * i, 1);
        for (int i = 0; i < 4; i++) { mbar_init(b_full + 8 * i, 1); mbar_init(b_empty + 8 * i, 8); }
        fence_barrier_init();
    }
    __syncthreads();
    cluster_sync_all();
    pdl_launch();
    if (wg == 3) {
        reg_dec<24>();
        if (tid == 384) {
            const CUtensorMap* tw = ng < 4 ? &tm_wk : &tm_wv;
            const int n0 = (ng & 3) * 1024 + rank * 64;
            for (int it = 0; it < 64; it++) {
                int st = it & 3;
                if (it < 8) {
                    mbar_expect_tx(a_full + 8 * it, 16384);
                    tma_load_2d(sA + it * 16384, &tm_c, it * 64, m0, a_full + 8 * it);
                }
                mbar_wait(b_empty + 8 * st, ((it >> 2) & 1) ^ 1);
                mbar_expect_tx(b_full + 8 * st, 16384);
                tma_load_2d_mc(sB + st * 16384 + rank * 8192, tw, n0 + (it >> 3) * 128, (it & 7) * 64, b_full + 8 * st, 3);
                if (it + 8 < 64) tma_prefetch_2d(tw, n0 + ((it + 8) >> 3) * 128, (it & 7) * 64);
            }
        }
        __syncwarp();
        cluster_sync_all();
    } else if (wg == 2) {
        reg_dec<96>();
        ssm_kgen_warp(sp, blockIdx.x * 4 + (warp & 3), lane);
        cluster_sync_all();
    } else {
        reg_inc<192>();
        float acc[2][64];
        const uint32_t stg = sC + wg * 16384;
        if (wg == 1) named_arrive(3, 256);
        for (int tt = 0; tt < 4; tt++) {
            const int t = 2 * tt + wg;
            named_sync(3 + wg, 256);
#pragma unroll 1
            for (int kc = 0; kc < 8; kc++) {
                const int it = t * 8 + kc, st = it & 3;
                if (tt == 0) mbar_wait(a_full + 8 * kc, 0);
                mbar_wait(b_full + 8 * st, (it >> 2) & 1);
                wg_fence();
                const uint64_t da = desc_kmajor(sA + kc * 16384), db = desc_mnmajor(sB + st * 16384, 8192);
#pragma unroll
                for (int k = 0; k < 4; k++) {
                    wgmma_ss128<1>(acc[0], da + k * 2, db + k * 128, (kc | k) != 0);
                    wgmma_ss128<1>(acc[1], da + 512 + k * 2, db + k * 128, (kc | k) != 0);
                }
                wg_commit();
                if (kc == 7 && t < 7) named_arrive(3 + (wg ^ 1), 256);
                if (kc > 0) {
                    wg_wait<1>();
                    if (lane < 2) mbar_arrive_cluster(b_empty + 8 * ((it - 1) & 3), lane);
                }
            }
            wg_wait<0>();
            if (lane < 2) mbar_arrive_cluster(b_empty + 8 * ((t * 8 + 7) & 3), lane);
#pragma unroll
            for (int nh = 0; nh < 2; nh++) {
                if ((tid & 127) == 0) bulk_wait_read<0>();
                named_sync(1 + wg, 128);
                store_slab64(stg, (warp & 3) * 16, acc[0] + nh * 32, 1.f, 1.f, lane);
                store_slab64(stg, 64 + (warp & 3) * 16, acc[1] + nh * 32, 1.f, 1.f, lane);
                fence_proxy_async();
                named_sync(1 + wg, 128);
                if ((tid & 127) == 0) {
                    tma_store_2d(&tm_kv_st, stg, ng * 1024 + t * 128 + nh * 64, m0);
                    bulk_commit();
                }
            }
        }
        if ((tid & 127) == 0) bulk_wait<0>();
        __syncwarp();
        cluster_sync_all();
    }
}
constexpr int AT_NS = 6;
constexpr int AT_SMEM = AT_NS * 32768 + 32768 + 256 + 1024;
constexpr int AT_ITEMS = 512;

DEVI uint32_t hmax2(uint32_t a, uint32_t b) { uint32_t r; asm("max.bf16x2 %0, %1, %2;" : "=r"(r) : "r"(a), "r"(b)); return r; }
DEVI uint32_t hmul2(uint32_t a, uint32_t b) { uint32_t r; asm("mul.rn.bf16x2 %0, %1, %2;" : "=r"(r) : "r"(a), "r"(b)); return r; }
DEVI uint32_t hfma2(uint32_t a, uint32_t b, uint32_t c) { uint32_t r; asm("fma.rn.bf16x2 %0, %1, %2, %3;" : "=r"(r) : "r"(a), "r"(b), "r"(c)); return r; }
DEVI float blo(uint32_t v) { return __uint_as_float(v << 16); }
DEVI float bhi(uint32_t v) { return __uint_as_float(v & 0xffff0000u); }

template <bool FIRST>
DEVI void softmax_tile(float* s, float& m0, float& m1, float& l0, float& l1, float& al0, float& al1) {
    const uint32_t HI = 0x3DB53DB5u;
    const uint32_t LO = 0x371E371Eu;
    const float L2E = 1.4426950408889634f;
    uint32_t x0 = 0xFF80FF80u, x1 = 0xFF80FF80u;
#pragma unroll
    for (int j = 0; j < 16; j++) {
        uint32_t a = pack_bf16(s[4 * j], s[4 * j + 1]), b = pack_bf16(s[4 * j + 2], s[4 * j + 3]);
        a = hfma2(a, HI, hmul2(a, LO));
        b = hfma2(b, HI, hmul2(b, LO));
        s[4 * j] = __uint_as_float(a); s[4 * j + 2] = __uint_as_float(b);
        x0 = hmax2(x0, a); x1 = hmax2(x1, b);
    }
    uint32_t x = hmax2(__byte_perm(x0, x1, 0x5410), __byte_perm(x0, x1, 0x7632));
    x = hmax2(x, __shfl_xor_sync(~0u, x, 1));
    x = hmax2(x, __shfl_xor_sync(~0u, x, 2));
    float n0 = blo(x), n1 = bhi(x);
    if (!FIRST) {
        n0 = fmaxf(n0, m0); n1 = fmaxf(n1, m1);
        al0 = ex2((m0 - n0) * L2E); al1 = ex2((m1 - n1) * L2E);
    }
    m0 = n0; m1 = n1;
    const float c0 = -n0 * L2E, c1 = -n1 * L2E;
    float s0 = 0.f, s1 = 0.f;
#pragma unroll
    for (int j = 0; j < 16; j++) {
        uint32_t a = __float_as_uint(s[4 * j]), b = __float_as_uint(s[4 * j + 2]);
        float e0 = ex2(fmaf(blo(a), L2E, c0)), e1 = ex2(fmaf(bhi(a), L2E, c0));
        float e2 = ex2(fmaf(blo(b), L2E, c1)), e3 = ex2(fmaf(bhi(b), L2E, c1));
        s0 += e0 + e1; s1 += e2 + e3;
        s[4 * j] = e0; s[4 * j + 1] = e1; s[4 * j + 2] = e2; s[4 * j + 3] = e3;
    }
    if (FIRST) { l0 = s0; l1 = s1; }
    else { l0 = fmaf(l0, al0, s0); l1 = fmaf(l1, al1, s1); }
}

struct Ring {
    int st; uint32_t ph;
    DEVI void next() { if (++st == AT_NS) { st = 0; ph ^= 1; } }
};

__global__ void __launch_bounds__(384, 1)
attn_kernel(const __grid_constant__ CUtensorMap tm_x, const __grid_constant__ CUtensorMap tm_wq,
            const __grid_constant__ CUtensorMap tm_kv, const __grid_constant__ CUtensorMap tm_ctx_st) {
    extern __shared__ uint8_t smem_raw[];
    const uint32_t sb = (smem_u32(smem_raw) + 1023) & ~1023u;
    const uint32_t sO = sb + AT_NS * 32768, bars = sO + 32768;
    const uint32_t full = bars, empty = bars + 64;
    volatile int* slots = reinterpret_cast<volatile int*>(smem_raw + (bars + 128 - smem_u32(smem_raw)));
    const int tid = threadIdx.x, warp = tid >> 5, lane = tid & 31, wg = tid >> 7;
    if (tid == 0) {
        for (int i = 0; i < AT_NS; i++) { mbar_init(full + 8 * i, 1); mbar_init(empty + 8 * i, 8); }
        fence_barrier_init();
    }
    __syncthreads();
    if (wg == 2) {
        reg_dec<24>();
        if (warp == 8 && lane == 0) {
            Ring r{0, 1};
            int n = 0;
            while (true) {
                int idx = (int)atomicInc(&g_sched, AT_ITEMS + gridDim.x - 1);
                mbar_wait(empty + 8 * r.st, r.ph);
                if (idx >= AT_ITEMS) {
                    slots[n & 3] = -1;
                    mbar_arrive(full + 8 * r.st);
                    break;
                }
                slots[n & 3] = idx;
                const int qi = 15 - (idx >> 5), h = idx & 31;
                for (int kc = 0; kc < 8; kc++) {
                    if (kc) mbar_wait(empty + 8 * r.st, r.ph);
                    const uint32_t fb = full + 8 * r.st, dst = sb + r.st * 32768;
                    mbar_expect_tx(fb, 32768);
                    tma_load_2d(dst, &tm_x, kc * 64, qi * 128, fb);
                    tma_load_2d(dst + 16384, &tm_wq, h * 128, kc * 64, fb);
                    tma_load_2d(dst + 24576, &tm_wq, h * 128 + 64, kc * 64, fb);
                    r.next();
                }
                if (n == 0) { pdl_wait(); pdl_launch(); }
                for (int j = qi; j >= -1; j--) {
#pragma unroll
                    for (int v = 0; v < 2; v++) {
                        const int jj = j + v;
                        if (jj < 0 || jj > qi || (v == 0 && j < 0)) continue;
                        mbar_wait(empty + 8 * r.st, r.ph);
                        const uint32_t fb = full + 8 * r.st, dst = sb + r.st * 32768;
                        mbar_expect_tx(fb, 32768);
                        tma_load_2d(dst, &tm_kv, v * HDALL + h * 128, jj * 128, fb);
                        tma_load_2d(dst + 16384, &tm_kv, v * HDALL + h * 128 + 64, jj * 128, fb);
                        r.next();
                    }
                }
                n++;
            }
            if (n == 0) { pdl_wait(); pdl_launch(); }
        }
    } else {
        reg_inc<240>();
        Ring r{0, 0};
        float o[64], s[64];
        uint32_t qf[32], pa[32];
        const int g = lane >> 2, t = lane & 3, wq = warp & 3;
        const uint32_t stg = sO + wg * 16384;
        if (wg == 1) named_arrive(3, 256);
        for (int n = 0;; n++) {
            mbar_wait(full + 8 * r.st, r.ph);
            const int idx = slots[n & 3];
            if (idx < 0) break;
            const int qi = 15 - (idx >> 5), h = idx & 31;
#pragma unroll 1
            for (int kc = 0; kc < 8; kc++) {
                if (kc) mbar_wait(full + 8 * r.st, r.ph);
                wg_fence();
                const uint32_t base = sb + r.st * 32768;
                const uint64_t da = desc_kmajor(base + wg * 8192), db = desc_mnmajor(base + 16384, 8192);
#pragma unroll
                for (int k = 0; k < 4; k++) wgmma_ss128<1>(s, da + k * 2, db + k * 128, (kc | k) != 0);
                wg_commit();
                if (kc) {
                    wg_wait<1>();
                    if (lane == 0) mbar_arrive(empty + 8 * (r.st == 0 ? AT_NS - 1 : r.st - 1));
                }
                r.next();
            }
            wg_wait<0>();
            if (lane == 0) mbar_arrive(empty + 8 * (r.st == 0 ? AT_NS - 1 : r.st - 1));
#pragma unroll
            for (int i = 0; i < 32; i++) qf[i] = pack_bf16(s[2 * i], s[2 * i + 1]);
            float m0, m1, l0, l1, al0, al1;
            auto issue_qk = [&]() {
                mbar_wait(full + 8 * r.st, r.ph);
                wg_fence();
                const uint64_t db = desc_kmajor(sb + r.st * 32768);
#pragma unroll
                for (int k = 0; k < 8; k++) wgmma_rs128<0>(s, qf + 4 * k, db + (k >> 2) * 1024 + (k & 3) * 2, k != 0);
                wg_commit();
            };
            auto issue_pv = [&](const uint32_t* p, int st, uint32_t ph, int acc) {
                mbar_wait(full + 8 * st, ph);
                wg_fence();
                const uint64_t db = desc_mnmajor(sb + st * 32768, 16384);
#pragma unroll
                for (int k = 0; k < 8; k++) wgmma_rs128<1>(o, p + 4 * k, db + k * 128, acc | k);
                wg_commit();
            };
            issue_qk();
            wg_wait<0>();
            if (lane == 0) mbar_arrive(empty + 8 * r.st);
            r.next();
            {
                const int row = wg * 64 + wq * 16 + g;
#pragma unroll
                for (int j = 0; j < 16; j++) {
                    const int c = 8 * j + 2 * t;
                    if (c > row) s[4 * j] = -INFINITY;
                    if (c + 1 > row) s[4 * j + 1] = -INFINITY;
                    if (c > row + 8) s[4 * j + 2] = -INFINITY;
                    if (c + 1 > row + 8) s[4 * j + 3] = -INFINITY;
                }
            }
            softmax_tile<true>(s, m0, m1, l0, l1, al0, al1);
#pragma unroll
            for (int i = 0; i < 32; i++) pa[i] = pack_bf16(s[2 * i], s[2 * i + 1]);
            int first = 0;
#pragma unroll 1
            for (int j = qi; j >= 1; j--) {
                named_sync(3 + wg, 256);
                issue_qk();
                const int kst = r.st;
                r.next();
                issue_pv(pa, r.st, r.ph, first);
                named_arrive(3 + (wg ^ 1), 256);
                wg_wait<1>();
                if (lane == 0) mbar_arrive(empty + 8 * kst);
                softmax_tile<false>(s, m0, m1, l0, l1, al0, al1);
                wg_wait<0>();
                if (lane == 0) mbar_arrive(empty + 8 * r.st);
                r.next();
#pragma unroll
                for (int i = 0; i < 32; i++) pa[i] = pack_bf16(s[2 * i], s[2 * i + 1]);
#pragma unroll
                for (int i = 0; i < 16; i++) {
                    o[4 * i] *= al0; o[4 * i + 1] *= al0; o[4 * i + 2] *= al1; o[4 * i + 3] *= al1;
                }
                first = 1;
            }
            issue_pv(pa, r.st, r.ph, first);
            l0 += __shfl_xor_sync(~0u, l0, 1); l0 += __shfl_xor_sync(~0u, l0, 2);
            l1 += __shfl_xor_sync(~0u, l1, 1); l1 += __shfl_xor_sync(~0u, l1, 2);
            const float i0 = 1.f / l0, i1 = 1.f / l1;
            if ((tid & 127) == 0) bulk_wait_read<0>();
            named_sync(1 + wg, 128);
            wg_wait<0>();
            if (lane == 0) mbar_arrive(empty + 8 * r.st);
            r.next();
            store_slab64(stg, wq * 16, o, i0, i1, lane);
            store_slab64(stg + 8192, wq * 16, o + 32, i0, i1, lane);
            fence_proxy_async();
            named_sync(1 + wg, 128);
            if ((tid & 127) == 0) {
                tma_store_2d(&tm_ctx_st, stg, h * 128, qi * 128 + wg * 64);
                tma_store_2d(&tm_ctx_st, stg + 8192, h * 128 + 64, qi * 128 + wg * 64);
                bulk_commit();
            }
        }
        if ((tid & 127) == 0) bulk_wait<0>();
    }
}
constexpr int OP_NS = 4;
constexpr int OP_ULD = 41 * 16;
constexpr int OP_UCH = 8 * OP_ULD;
constexpr int OP_SMEM = OP_NS * 32768 + 32768 + 4 * WTAB * 4 + 4 * OP_UCH + 256 + 1024;

template <int N> DEVI void wgmma_conv(float* d, const uint32_t* a, uint64_t db);
template <> DEVI void wgmma_conv<32>(float* d, const uint32_t* a, uint64_t db) {
    asm volatile("wgmma.mma_async.sync.aligned.m64n32k16.f32.bf16.bf16 {%0,%1,%2,%3,%4,%5,%6,%7,%8,%9,%10,%11,%12,%13,%14,%15}, "
                 "{%16,%17,%18,%19}, %20, 1, 1, 1, 0;"
                 : ACC8(d, 0), ACC8(d, 8) : "r"(a[0]), "r"(a[1]), "r"(a[2]), "r"(a[3]), "l"(db));
}
template <> DEVI void wgmma_conv<24>(float* d, const uint32_t* a, uint64_t db) {
    asm volatile("wgmma.mma_async.sync.aligned.m64n24k16.f32.bf16.bf16 {%0,%1,%2,%3,%4,%5,%6,%7,%8,%9,%10,%11}, "
                 "{%12,%13,%14,%15}, %16, 1, 1, 1, 0;"
                 : ACC8(d, 0), "+f"(d[8]), "+f"(d[9]), "+f"(d[10]), "+f"(d[11]) : "r"(a[0]), "r"(a[1]), "r"(a[2]), "r"(a[3]), "l"(db));
}
template <> DEVI void wgmma_conv<16>(float* d, const uint32_t* a, uint64_t db) {
    asm volatile("wgmma.mma_async.sync.aligned.m64n16k16.f32.bf16.bf16 {%0,%1,%2,%3,%4,%5,%6,%7}, "
                 "{%8,%9,%10,%11}, %12, 1, 1, 1, 0;"
                 : ACC8(d, 0) : "r"(a[0]), "r"(a[1]), "r"(a[2]), "r"(a[3]), "l"(db));
}
template <> DEVI void wgmma_conv<8>(float* d, const uint32_t* a, uint64_t db) {
    asm volatile("wgmma.mma_async.sync.aligned.m64n8k16.f32.bf16.bf16 {%0,%1,%2,%3}, "
                 "{%4,%5,%6,%7}, %8, 1, 1, 1, 0;"
                 : "+f"(d[0]), "+f"(d[1]), "+f"(d[2]), "+f"(d[3]) : "r"(a[0]), "r"(a[1]), "r"(a[2]), "r"(a[3]), "l"(db));
}
DEVI uint32_t lds32(uint32_t a) { uint32_t v; asm volatile("ld.shared.b32 %0, [%1];" : "=r"(v) : "r"(a)); return v; }
DEVI uint32_t lds16(uint32_t a) { uint16_t v; asm volatile("ld.shared.b16 %0, [%1];" : "=h"(v) : "r"(a)); return v; }

template <int J> DEVI void conv_pair(float* acc, uint32_t* f, uint32_t wa, uint64_t du, int c) {
#pragma unroll
    for (int i = 0; i < 8; i++) {
        f[4 * i] = lds32(wa + i * 64); f[4 * i + 1] = lds32(wa + i * 64 + 32);
        f[4 * i + 2] = lds32(wa + i * 64 - 32); f[4 * i + 3] = lds32(wa + i * 64);
    }
    wg_fence();
#pragma unroll
    for (int i = 0; i < 8; i++) {
        const int kk = 3 - (i & 3);
        const uint64_t db = du + (uint64_t)(kk * 2 * (OP_ULD / 16) + (i >> 2) + c);
        wgmma_conv<32 - 8 * J>(acc, f + 4 * i, db);
    }
    wg_commit();
}
template <int J> DEVI void conv_group(float* acc, uint32_t wa, uint64_t du) {
    uint32_t fa[32], fb[32];
#pragma unroll
    for (int h = 0; h < 2; h++) {
        const int c = 8 * J + 4 * h;
        conv_pair<J>(acc, fa, wa + c * 256, du, c);
        wg_wait<1>();
        conv_pair<J>(acc, fb, wa + (c + 2) * 256, du, c + 2);
        wg_wait<1>();
    }
    wg_wait<0>();
}

__global__ void __cluster_dims__(2, 1, 1) __launch_bounds__(512, 1)
outproj_kernel(const __grid_constant__ CUtensorMap tm_ctx, const __grid_constant__ CUtensorMap tm_wo,
               const __grid_constant__ CUtensorMap tm_out, SsmParams sp, bf16* __restrict__ out) {
    extern __shared__ uint8_t smem_raw[];
    const uint32_t sb = (smem_u32(smem_raw) + 1023) & ~1023u;
    const uint32_t sX = sb + OP_NS * 32768, sW = sX + 32768, sU = sW + 4 * WTAB * 4, bars = sU + 4 * OP_UCH;
    const uint32_t full = bars, empty = bars + 64, xfull = bars + 128, wfull = bars + 136;
    const int tid = threadIdx.x, warp = tid >> 5, lane = tid & 31, wg = tid >> 7;
    const uint32_t rank = cluster_rank();
    const uint32_t kr = rank;
    const int cl = blockIdx.x >> 1;
    const int m0 = (cl >> 2) * 128, n0 = (cl & 3) * 128, k0 = kr * 2048;
    if (tid == 0) {
        for (int i = 0; i < OP_NS; i++) { mbar_init(full + 8 * i, 1); mbar_init(empty + 8 * i, 8); }
        mbar_init(xfull, 1);
        mbar_init(wfull, 1);
        fence_barrier_init();
    }
    __syncthreads();
    cluster_sync_all();
    if (wg == 3) {
        reg_dec<40>();
        if (tid == 384) {
            mbar_expect_tx(wfull, 4 * WTAB * 4);
            bulk_load(sW, g_wtab + blockIdx.x * 4 * WTAB, 4 * WTAB * 4, wfull);
            mbar_expect_tx(xfull, 32768);
            for (int it = 0; it < OP_NS; it++) {
                const uint32_t dst = sb + it * 32768, fb = full + 8 * it;
                mbar_expect_tx(fb, 32768);
                tma_load_2d(dst + 16384, &tm_wo, n0, k0 + it * 64, fb);
                tma_load_2d(dst + 24576, &tm_wo, n0 + 64, k0 + it * 64, fb);
            }
            for (int it = OP_NS; it < 32; it++) {
                if ((it & 7) == ((cl >> 2) & 7)) tma_prefetch_2d(&tm_wo, n0 + (cl >> 5) * 64, k0 + it * 64);
            }
            pdl_wait();
            for (int it = 0; it < 32; it++) {
                const int st = it & (OP_NS - 1);
                const uint32_t dst = sb + st * 32768, fb = full + 8 * st;
                if (it >= OP_NS) {
                    mbar_wait(empty + 8 * st, ((it / OP_NS) & 1) ^ 1);
                    mbar_expect_tx(fb, 32768);
                    tma_load_2d(dst + 16384, &tm_wo, n0, k0 + it * 64, fb);
                    tma_load_2d(dst + 24576, &tm_wo, n0 + 64, k0 + it * 64, fb);
                }
                tma_load_2d(dst, &tm_ctx, k0 + it * 64, m0, fb);
                tma_load_2d(dst + 8192, &tm_ctx, k0 + it * 64, m0 + 64, fb);
            }
        }
        __syncwarp();
    } else if (wg == 2) {
        reg_inc<208>();
        const int ct = tid & 127, wq = warp & 3, g = lane >> 2, t = lane & 3;
        const int d0 = blockIdx.x * 4;
        uint2 v[2][8];
#pragma unroll
        for (int h = 0; h < 2; h++)
#pragma unroll
            for (int i = 0; i < 8; i++)
                v[h][i] = __ldg(reinterpret_cast<const uint2*>(sp.u + (size_t)((ct + 128 * h) * 8 + i) * SSM_D + d0));
        for (int i = ct; i < 4 * 8 * 8; i += 128) {
            const uint32_t a = sU + (i >> 3) * OP_ULD + (32 + (i & 7)) * 16;
            asm volatile("st.shared.v4.b32 [%0], {%1,%1,%1,%1};" ::"r"(a), "r"(0) : "memory");
        }
#pragma unroll
        for (int h = 0; h < 2; h++) {
            const int q = ct + 128 * h;
            const uint32_t a = sU + (q & 7) * OP_ULD + (31 - (q >> 3)) * 16;
#pragma unroll
            for (int c = 0; c < 4; c++) {
                uint32_t w[4];
#pragma unroll
                for (int i = 0; i < 4; i++) {
                    const uint32_t lo = (c & 2) ? v[h][2 * i].y : v[h][2 * i].x, hi = (c & 2) ? v[h][2 * i + 1].y : v[h][2 * i + 1].x;
                    w[i] = __byte_perm(lo, hi, (c & 1) ? 0x7632 : 0x5410);
                }
                asm volatile("st.shared.v4.b32 [%0], {%1,%2,%3,%4};" ::"r"(a + c * OP_UCH), "r"(w[0]), "r"(w[1]), "r"(w[2]), "r"(w[3]) : "memory");
            }
        }
        const uint2 dsk = __ldg(reinterpret_cast<const uint2*>(sp.dskip + d0));
        fence_proxy_async();
        named_sync(3, 128);
        mbar_wait(wfull, 0);
        uint32_t res[16][2];
#pragma unroll
        for (int c = 0; c < 4; c++) {
            float acc[16];
#pragma unroll
            for (int i = 0; i < 16; i++) acc[i] = 0.f;
            const uint32_t wa = sW + (c * WTAB + 64 + 16 * (wq - 3) + g - 2 * t) * 4;
            const uint64_t du = make_desc(sU + c * OP_UCH, OP_ULD, 128, 0);
            conv_group<0>(acc, wa, du);
            conv_group<1>(acc, wa, du);
            conv_group<2>(acc, wa, du);
            conv_group<3>(acc, wa, du);
            const uint32_t dw = (c & 2) ? dsk.y : dsk.x;
            const float D = (c & 1) ? bhi(dw) : blo(dw);
#pragma unroll
            for (int i = 0; i < 16; i++) {
                const int n = 8 * (i >> 2) + 2 * t + (i & 1), j = 2 * wq + ((i >> 1) & 1);
                const float u = __uint_as_float(lds16(sU + c * OP_UCH + j * OP_ULD + n * 16 + g * 2) << 16);
                const uint32_t o = __bfloat16_as_ushort(__float2bfloat16_rn(rbf(acc[i]) + rbf(u * D)));
                if (c & 1) res[i][c >> 1] |= o << 16; else res[i][c >> 1] = o;
            }
        }
#pragma unroll
        for (int i = 0; i < 16; i++) {
            const int a = 31 - (8 * (i >> 2) + 2 * t + (i & 1)), b = 16 * wq + g + 8 * ((i >> 1) & 1);
            *reinterpret_cast<uint2*>(out + (size_t)(64 * a + b) * 1024 + 512 + d0) = make_uint2(res[i][0], res[i][1]);
        }
    } else {
        float acc[64];
#pragma unroll 1
        for (int it = 0; it < 32; it++) {
            const int st = it & (OP_NS - 1);
            mbar_wait(full + 8 * st, (it / OP_NS) & 1);
            wg_fence();
            const uint32_t base = sb + st * 32768;
            const uint64_t da = desc_kmajor(base + wg * 8192), db = desc_mnmajor(base + 16384, 8192);
#pragma unroll
            for (int k = 0; k < 4; k++) wgmma_ss128<1>(acc, da + k * 2, db + k * 128, (it | k) != 0);
            wg_commit();
            if (it > 0 && it + OP_NS - 1 < 32) {
                wg_wait<1>();
                if (lane == 0) mbar_arrive(empty + 8 * ((it - 1) & (OP_NS - 1)));
            }
        }
        wg_wait<0>();
        uint32_t peer, pbar;
        asm volatile("mapa.shared::cluster.u32 %0, %1, %2;" : "=r"(peer) : "r"(sX + tid * 16), "r"(rank ^ 1));
        asm volatile("mapa.shared::cluster.u32 %0, %1, %2;" : "=r"(pbar) : "r"(xfull), "r"(rank ^ 1));
#pragma unroll
        for (int i = 0; i < 8; i++) {
            const float* s = acc + 4 * i;
            const float a = kr ? s[0] : s[32], b = kr ? s[1] : s[33], c = kr ? s[2] : s[34], d = kr ? s[3] : s[35];
            asm volatile("st.async.weak.shared::cluster.mbarrier::complete_tx::bytes.v4.f32 [%0], {%1,%2,%3,%4}, [%5];"
                         ::"r"(peer + i * 4096), "f"(a), "f"(b), "f"(c), "f"(d), "r"(pbar) : "memory");
        }
        mbar_wait(xfull, 0);
        float r[32];
#pragma unroll
        for (int i = 0; i < 8; i++) {
            float a, b, c, d;
            asm volatile("ld.shared.v4.f32 {%0,%1,%2,%3}, [%4];" : "=f"(a), "=f"(b), "=f"(c), "=f"(d) : "r"(sX + tid * 16 + i * 4096));
            const float* s = acc + 4 * i;
            r[4 * i] = a + (kr ? s[32] : s[0]); r[4 * i + 1] = b + (kr ? s[33] : s[1]);
            r[4 * i + 2] = c + (kr ? s[34] : s[2]); r[4 * i + 3] = d + (kr ? s[35] : s[3]);
        }
        const uint32_t stg = sb + wg * 8192;
        store_slab64(stg, (warp & 3) * 16, r, 1.f, 1.f, lane);
        fence_proxy_async();
        named_sync(1 + wg, 128);
        if ((tid & 127) == 0) {
            tma_store_2d(&tm_out, stg, n0 + kr * 64, m0 + wg * 64);
            bulk_commit();
            bulk_wait<0>();
        }
    }
    __syncwarp();
    cluster_sync_all();
}

typedef CUresult (*EncodeFn)(CUtensorMap*, CUtensorMapDataType, cuuint32_t, void*, const cuuint64_t*, const cuuint64_t*,
                             const cuuint32_t*, const cuuint32_t*, CUtensorMapInterleave, CUtensorMapSwizzle,
                             CUtensorMapL2promotion, CUtensorMapFloatOOBfill);

static void make_map(EncodeFn fn, CUtensorMap* m, const void* p, uint64_t cols, uint64_t rows, uint32_t box_rows) {
    cuuint64_t dims[2] = {cols, rows};
    cuuint64_t strides[1] = {cols * 2};
    cuuint32_t box[2] = {64, box_rows};
    cuuint32_t es[2] = {1, 1};
    fn(m, CU_TENSOR_MAP_DATA_TYPE_BFLOAT16, 2, const_cast<void*>(p), dims, strides, box, es, CU_TENSOR_MAP_INTERLEAVE_NONE,
       CU_TENSOR_MAP_SWIZZLE_128B, CU_TENSOR_MAP_L2_PROMOTION_L2_256B, CU_TENSOR_MAP_FLOAT_OOB_FILL_NONE);
}

extern "C" void kernel_launch(void* const* d_in, const int* in_sizes, int n_in, void* d_out, int out_size) {
    void* fp = nullptr;
    cudaDriverEntryPointQueryResult qr;
    cudaGetDriverEntryPoint("cuTensorMapEncodeTiled", &fp, cudaEnableDefault, &qr);
    EncodeFn fn = (EncodeFn)fp;
    void *p_kv, *p_ctx;
    cudaGetSymbolAddress(&p_kv, g_kv);
    cudaGetSymbolAddress(&p_ctx, g_ctx);
    CUtensorMap tm_x, tm_c, tm_wq, tm_wk, tm_wv, tm_wo, tm_kv, tm_ctx, tm_out;
    make_map(fn, &tm_x, d_in[0], DM, SEQ, 128);
    make_map(fn, &tm_c, d_in[1], DM, SEQ, 128);
    make_map(fn, &tm_wq, d_in[2], HDALL, DM, 64);
    make_map(fn, &tm_wk, d_in[3], HDALL, DM, 64);
    make_map(fn, &tm_wv, d_in[4], HDALL, DM, 64);
    make_map(fn, &tm_wo, d_in[5], DM, HDALL, 64);
    make_map(fn, &tm_kv, p_kv, 2 * HDALL, SEQ, 128);
    make_map(fn, &tm_ctx, p_ctx, HDALL, SEQ, 64);
    make_map(fn, &tm_out, d_out, 1024, SEQ, 64);
    SsmParams sp;
    sp.u = (const bf16*)d_in[6]; sp.lar = (const bf16*)d_in[7]; sp.aim = (const bf16*)d_in[8];
    sp.cre = (const bf16*)d_in[9]; sp.cim = (const bf16*)d_in[10]; sp.ldt = (const bf16*)d_in[11]; sp.dskip = (const bf16*)d_in[12];
    cudaFuncSetAttribute(gemm_kv_kernel, cudaFuncAttributeMaxDynamicSharedMemorySize, G1_SMEM);
    cudaFuncSetAttribute(attn_kernel, cudaFuncAttributeMaxDynamicSharedMemorySize, AT_SMEM);
    cudaFuncSetAttribute(outproj_kernel, cudaFuncAttributeMaxDynamicSharedMemorySize, OP_SMEM);
    cudaStream_t st = cudaStreamPerThread;
    gemm_kv_kernel<<<128, G1_THREADS, G1_SMEM, st>>>(tm_c, tm_wk, tm_wv, tm_kv, sp);
    cudaLaunchAttribute at[1];
    at[0].id = cudaLaunchAttributeProgrammaticStreamSerialization;
    at[0].val.programmaticStreamSerializationAllowed = 1;
    cudaLaunchConfig_t cfg = {};
    cfg.stream = st; cfg.attrs = at; cfg.numAttrs = 1;
    cfg.gridDim = dim3(132); cfg.blockDim = dim3(384); cfg.dynamicSmemBytes = AT_SMEM;
    cudaLaunchKernelEx(&cfg, attn_kernel, tm_x, tm_wq, tm_kv, tm_ctx);
    cfg.gridDim = dim3(128); cfg.blockDim = dim3(512); cfg.dynamicSmemBytes = OP_SMEM;
    cudaLaunchKernelEx(&cfg, outproj_kernel, tm_ctx, tm_wo, tm_out, sp, (bf16*)d_out);
}
```

```cpp
#include <cuda_runtime.h>
#include <cuda_bf16.h>
#include <cuda.h>
#include <stdint.h>

typedef __nv_bfloat16 bf16;

#define DEVI __device__ __forceinline__

constexpr int SEQ = 2048, DM = 512, NH = 32, HD = 128, HDALL = NH * HD;
constexpr int SSM_D = 512, SSM_N = 128;
constexpr int WTAB = 2112;

__device__ bf16 g_kv[(size_t)SEQ * 2 * HDALL];
__device__ bf16 g_ctx[(size_t)SEQ * HDALL];
__device__ __align__(128) float g_kp[SSM_D * 648];
__device__ unsigned int g_sched;

DEVI uint32_t smem_u32(const void* p) { return (uint32_t)__cvta_generic_to_shared(p); }
DEVI void mbar_init(uint32_t a, uint32_t cnt) { asm volatile("mbarrier.init.shared::cta.b64 [%0], %1;" ::"r"(a), "r"(cnt)); }
DEVI void mbar_expect_tx(uint32_t a, uint32_t bytes) {
    asm volatile("mbarrier.arrive.expect_tx.shared::cta.b64 _, [%0], %1;" ::"r"(a), "r"(bytes) : "memory");
}
DEVI void mbar_arrive(uint32_t a) { asm volatile("mbarrier.arrive.shared::cta.b64 _, [%0];" ::"r"(a) : "memory"); }
DEVI void mbar_arrive_cluster(uint32_t a, uint32_t cta) {
    asm volatile("{\n.reg .b32 r;\nmapa.shared::cluster.u32 r, %0, %1;\n"
                 "mbarrier.arrive.shared::cluster.b64 _, [r];\n}" ::"r"(a), "r"(cta) : "memory");
}
#define MBAR_WAIT_ASM(OP)                                                                              \
    asm volatile("{\n.reg .pred p, q;\n.reg .u32 t0, t1;\n" OP " p, [%0], %1;\n@p bra D_%=;\n"         \
                 "mov.u32 t0, %%globaltimer_lo;\nW_%=:\n" OP " p, [%0], %1;\n"                         \
                 "mov.u32 t1, %%globaltimer_lo;\nsub.u32 t1, t1, t0;\n"                                \
                 "setp.gt.or.u32 q, t1, 4000000, p;\n@!q bra W_%=;\nD_%=:\n}" ::"r"(a), "r"(parity) : "memory")
DEVI void mbar_wait(uint32_t a, uint32_t parity) { MBAR_WAIT_ASM("mbarrier.try_wait.parity.shared::cta.b64"); }
DEVI void mbar_wait_cluster(uint32_t a, uint32_t parity) { MBAR_WAIT_ASM("mbarrier.try_wait.parity.acquire.cluster.shared::cta.b64"); }
DEVI void fence_barrier_init() { asm volatile("fence.mbarrier_init.release.cluster;" ::: "memory"); }
DEVI void fence_proxy_async() { asm volatile("fence.proxy.async.shared::cta;" ::: "memory"); }
DEVI void cluster_sync_all() {
    asm volatile("barrier.cluster.arrive.release.aligned;\nbarrier.cluster.wait.acquire.aligned;" ::: "memory");
}
DEVI uint32_t cluster_rank() { uint32_t r; asm volatile("mov.u32 %0, %%cluster_ctarank;" : "=r"(r)); return r; }
DEVI void tma_load_2d(uint32_t dst, const CUtensorMap* m, int c0, int c1, uint32_t bar) {
    asm volatile("cp.async.bulk.tensor.2d.shared::cluster.global.mbarrier::complete_tx::bytes [%0], [%1, {%3, %4}], [%2];"
                 ::"r"(dst), "l"(m), "r"(bar), "r"(c0), "r"(c1) : "memory");
}
DEVI void tma_load_2d_mc(uint32_t dst, const CUtensorMap* m, int c0, int c1, uint32_t bar, uint16_t mask) {
    asm volatile("cp.async.bulk.tensor.2d.shared::cluster.global.mbarrier::complete_tx::bytes.multicast::cluster [%0], [%1, {%3, %4}], [%2], %5;"
                 ::"r"(dst), "l"(m), "r"(bar), "r"(c0), "r"(c1), "h"(mask) : "memory");
}
DEVI void tma_prefetch_2d(const CUtensorMap* m, int c0, int c1) {
    asm volatile("cp.async.bulk.prefetch.tensor.2d.L2.global [%0, {%1, %2}];" ::"l"(m), "r"(c0), "r"(c1) : "memory");
}
DEVI void tma_store_2d(const CUtensorMap* m, uint32_t src, int c0, int c1) {
    asm volatile("cp.async.bulk.tensor.2d.global.shared::cta.bulk_group [%0, {%2, %3}], [%1];"
                 ::"l"(m), "r"(src), "r"(c0), "r"(c1) : "memory");
}
DEVI void bulk_load(uint32_t dst, const void* src, uint32_t bytes, uint32_t bar) {
    asm volatile("cp.async.bulk.shared::cluster.global.mbarrier::complete_tx::bytes [%0], [%1], %2, [%3];"
                 ::"r"(dst), "l"(src), "r"(bytes), "r"(bar) : "memory");
}
DEVI void bulk_prefetch(const void* src, uint32_t bytes) {
    asm volatile("cp.async.bulk.prefetch.L2.global [%0], %1;" ::"l"(src), "r"(bytes) : "memory");
}
DEVI void bulk_commit() { asm volatile("cp.async.bulk.commit_group;" ::: "memory"); }
template <int N> DEVI void bulk_wait_read() { asm volatile("cp.async.bulk.wait_group.read %0;" ::"n"(N) : "memory"); }
template <int N> DEVI void bulk_wait() { asm volatile("cp.async.bulk.wait_group %0;" ::"n"(N) : "memory"); }
DEVI void prefetch_tmap(const CUtensorMap* m) { asm volatile("prefetch.tensormap [%0];" ::"l"(m) : "memory"); }
DEVI void named_sync(int id, int n) { asm volatile("bar.sync %0, %1;" ::"r"(id), "r"(n) : "memory"); }
DEVI void named_arrive(int id, int n) { asm volatile("bar.arrive %0, %1;" ::"r"(id), "r"(n) : "memory"); }
DEVI void pdl_wait() { asm volatile("griddepcontrol.wait;" ::: "memory"); }
DEVI void pdl_launch() { asm volatile("griddepcontrol.launch_dependents;" ::: "memory"); }
template <int R> DEVI void reg_inc() { asm volatile("setmaxnreg.inc.sync.aligned.u32 %0;" ::"n"(R)); }
template <int R> DEVI void reg_dec() { asm volatile("setmaxnreg.dec.sync.aligned.u32 %0;" ::"n"(R)); }

DEVI void wg_fence() { asm volatile("wgmma.fence.sync.aligned;" ::: "memory"); }
DEVI void wg_commit() { asm volatile("wgmma.commit_group.sync.aligned;" ::: "memory"); }
template <int N> DEVI void wg_wait() { asm volatile("wgmma.wait_group.sync.aligned %0;" ::"n"(N) : "memory"); }

DEVI uint64_t make_desc(uint32_t addr, uint32_t lbo, uint32_t sbo, uint32_t swz) {
    return (uint64_t)((addr & 0x3FFFF) >> 4) | ((uint64_t)(lbo >> 4) << 16) | ((uint64_t)(sbo >> 4) << 32) | ((uint64_t)swz << 62);
}
DEVI uint64_t desc_kmajor(uint32_t addr) { return make_desc(addr, 16, 1024, 1); }
DEVI uint64_t desc_mnmajor(uint32_t addr, uint32_t lbo) { return make_desc(addr, lbo, 1024, 1); }

#define ACC8(d, o) "+f"(d[o + 0]), "+f"(d[o + 1]), "+f"(d[o + 2]), "+f"(d[o + 3]), "+f"(d[o + 4]), "+f"(d[o + 5]), "+f"(d[o + 6]), "+f"(d[o + 7])
#define ACC64(d) ACC8(d, 0), ACC8(d, 8), ACC8(d, 16), ACC8(d, 24), ACC8(d, 32), ACC8(d, 40), ACC8(d, 48), ACC8(d, 56)
#define R64 "{%0,%1,%2,%3,%4,%5,%6,%7,%8,%9,%10,%11,%12,%13,%14,%15,%16,%17,%18,%19,%20,%21,%22,%23,%24,%25,%26,%27,%28,%29,%30,%31," \
            "%32,%33,%34,%35,%36,%37,%38,%39,%40,%41,%42,%43,%44,%45,%46,%47,%48,%49,%50,%51,%52,%53,%54,%55,%56,%57,%58,%59,%60,%61,%62,%63}"

template <int TB> DEVI void wgmma_ss128(float* d, uint64_t da, uint64_t db, int acc) {
    asm volatile("{\n.reg .pred p;\nsetp.ne.b32 p, %66, 0;\n"
                 "wgmma.mma_async.sync.aligned.m64n128k16.f32.bf16.bf16 " R64 ", %64, %65, p, 1, 1, 0, %67;\n}"
                 : ACC64(d) : "l"(da), "l"(db), "r"(acc), "n"(TB));
}
template <int TB> DEVI void wgmma_rs128(float* d, const uint32_t* a, uint64_t db, int acc) {
    asm volatile("{\n.reg .pred p;\nsetp.ne.b32 p, %69, 0;\n"
                 "wgmma.mma_async.sync.aligned.m64n128k16.f32.bf16.bf16 " R64 ", {%64,%65,%66,%67}, %68, p, 1, 1, %70;\n}"
                 : ACC64(d) : "r"(a[0]), "r"(a[1]), "r"(a[2]), "r"(a[3]), "l"(db), "r"(acc), "n"(TB));
}
DEVI uint32_t pack_bf16(float lo, float hi) {
    uint32_t r;
    asm("cvt.rn.bf16x2.f32 %0, %1, %2;" : "=r"(r) : "f"(hi), "f"(lo));
    return r;
}
DEVI void stmatrix_x4(uint32_t addr, uint32_t r0, uint32_t r1, uint32_t r2, uint32_t r3) {
    asm volatile("stmatrix.sync.aligned.m8n8.x4.shared.b16 [%0], {%1,%2,%3,%4};" ::"r"(addr), "r"(r0), "r"(r1), "r"(r2), "r"(r3) : "memory");
}
DEVI float ex2(float x) { float y; asm("ex2.approx.ftz.f32 %0, %1;" : "=f"(y) : "f"(x)); return y; }

DEVI void store_slab64(uint32_t base, int row0, const float* d, float s0, float s1, int lane) {
    int mi = lane >> 3, r = lane & 7;
    int row = row0 + (mi & 1) * 8 + r;
#pragma unroll
    for (int j = 0; j < 8; j += 2) {
        uint32_t r0 = pack_bf16(d[4 * j + 0] * s0, d[4 * j + 1] * s0);
        uint32_t r1 = pack_bf16(d[4 * j + 2] * s1, d[4 * j + 3] * s1);
        uint32_t r2 = pack_bf16(d[4 * j + 4] * s0, d[4 * j + 5] * s0);
        uint32_t r3 = pack_bf16(d[4 * j + 6] * s1, d[4 * j + 7] * s1);
        int chunk = j + (mi >> 1);
        stmatrix_x4(base + row * 128 + ((chunk ^ (row & 7)) << 4), r0, r1, r2, r3);
    }
}
struct cf { float x, y; };
DEVI cf cmul(cf a, cf b) { cf r; r.x = fmaf(a.x, b.x, -a.y * b.y); r.y = fmaf(a.x, b.y, a.y * b.x); return r; }
DEVI cf csq(cf a) { cf r; r.x = fmaf(a.x, a.x, -a.y * a.y); r.y = (a.x + a.x) * a.y; return r; }
DEVI cf cexp_(float re, float im) {
    float m = __expf(re), s, c;
    __sincosf(im, &s, &c);
    cf r; r.x = m * c; r.y = m * s; return r;
}
DEVI uint32_t tf32(float x) { uint32_t r; asm("cvt.rna.tf32.f32 %0, %1;" : "=r"(r) : "f"(x)); return r; }
DEVI void mma_tf32(float* c, cf lo, cf hi, uint32_t b0, uint32_t b1) {
    asm volatile("mma.sync.aligned.m16n8k8.row.col.f32.tf32.tf32.f32 {%0,%1,%2,%3}, {%4,%5,%6,%7}, {%8,%9}, {%0,%1,%2,%3};"
                 : "+f"(c[0]), "+f"(c[1]), "+f"(c[2]), "+f"(c[3])
                 : "r"(tf32(lo.x)), "r"(tf32(hi.x)), "r"(tf32(lo.y)), "r"(tf32(hi.y)), "r"(b0), "r"(b1));
}
DEVI float bf2f(bf16 v) { return __bfloat162float(v); }
DEVI float rbf(float v) { return __bfloat162float(__float2bfloat16_rn(v)); }

struct SsmParams { const bf16 *lar, *aim, *cre, *cim, *ldt, *dskip, *u; };

DEVI int kp_index(int l) {
    int p = (int)rbf((float)l);
    return p < 256 ? p : (p < 512 ? 128 + (p >> 1) : (p < 1024 ? 256 + (p >> 2) : 384 + (p >> 3)));
}

DEVI void ssm_kgen_warp(const SsmParams& P, int d, int lane) {
    const int g = lane >> 2, t = lane & 3;
    float ar[4], ai[4], cr[4], ci[4], gr[4], gi[4];
    bf16 raw[4][4];
    const bf16 rdt = P.ldt[d];
#pragma unroll
    for (int q = 0; q < 4; q++) {
        const int n = d * SSM_N + 32 * q + lane;
        raw[q][0] = P.lar[n]; raw[q][1] = P.aim[n]; raw[q][2] = P.cre[n]; raw[q][3] = P.cim[n];
    }
    const float dt = rbf(expf(bf2f(rdt)));
#pragma unroll
    for (int q = 0; q < 4; q++) {
        ar[q] = -rbf(expf(bf2f(raw[q][0]))) * dt;
        ai[q] = bf2f(raw[q][1]) * dt;
        cr[q] = 2.f * (bf2f(raw[q][2]) * dt);
        ci[q] = 2.f * (bf2f(raw[q][3]) * dt);
        float m = expf(ar[q] * 64.f), sn, cs;
        sincosf(ai[q] * 64.f, &sn, &cs);
        gr[q] = m * cs; gi[q] = m * sn;
    }
    float acc[5][4];
#pragma unroll
    for (int s = 0; s < 5; s++) { acc[s][0] = acc[s][1] = acc[s][2] = acc[s][3] = 0.f; }
    float klast = 0.f;
    const float gf = (float)g;
#pragma unroll
    for (int q = 0; q < 4; q++) {
#pragma unroll 2
        for (int g0 = 0; g0 < 8; g0++) {
            int src = (g0 << 2) | t;
            float a_r = __shfl_sync(~0u, ar[q], src), a_i = __shfl_sync(~0u, ai[q], src);
            cf C, G;
            C.x = __shfl_sync(~0u, cr[q], src); C.y = __shfl_sync(~0u, ci[q], src);
            G.x = __shfl_sync(~0u, gr[q], src); G.y = __shfl_sync(~0u, gi[q], src);
            cf E = cexp_(a_r * gf, a_i * gf);
            cf B = csq(csq(csq(E)));
            cf Y = cmul(C, B);
            uint32_t b0 = tf32(Y.x), b1 = tf32(-Y.y);
            cf EG = cmul(E, G);
            mma_tf32(acc[0], E, EG, b0, b1);
            cf G2 = csq(G);
            cf X = cmul(E, G2), Xh = cmul(EG, G2);
            mma_tf32(acc[1], X, Xh, b0, b1);
#pragma unroll
            for (int s = 2; s < 5; s++) {
                B = csq(B); X = csq(X); Xh = csq(Xh);
                Y = cmul(C, B);
                mma_tf32(acc[s], X, Xh, tf32(Y.x), tf32(-Y.y));
            }
            X = csq(X);
            klast += fmaf(C.x, X.x, -C.y * X.y);
        }
    }
    klast += __shfl_xor_sync(~0u, klast, 1);
    klast += __shfl_xor_sync(~0u, klast, 2);
    float* kp = g_kp + d * 648;
#pragma unroll
    for (int s = 0; s < 5; s++) {
        int b = 128 * s + g + 16 * t;
        kp[b] = acc[s][0]; kp[b + 8] = acc[s][1]; kp[b + 64] = acc[s][2]; kp[b + 72] = acc[s][3];
    }
    if (lane == 0) kp[640] = klast;
}

constexpr int G1_THREADS = 512;
constexpr int G1_NS = 5;
constexpr int G1_SMEM = 131072 + G1_NS * 16384 + 16384 + 256 + 1024;

__global__ void __cluster_dims__(2, 1, 1) __launch_bounds__(G1_THREADS, 1)
gemm_kv_kernel(const __grid_constant__ CUtensorMap tm_c, const __grid_constant__ CUtensorMap tm_wk,
               const __grid_constant__ CUtensorMap tm_wv, const __grid_constant__ CUtensorMap tm_kv_st, SsmParams sp,
               const bf16* __restrict__ px, const bf16* __restrict__ pwq) {
    extern __shared__ uint8_t smem_raw[];
    const uint32_t sb = (smem_u32(smem_raw) + 1023) & ~1023u;
    const uint32_t sA = sb, sB = sb + 131072, sC = sB + G1_NS * 16384, bars = sC + 16384;
    const uint32_t a_full = bars, b_full = bars + 64, b_empty = bars + 128, c_free = bars + 192;
    const int tid = threadIdx.x, warp = tid >> 5, lane = tid & 31, wg = tid >> 7;
    const uint32_t rank = cluster_rank();
    const int cl = blockIdx.x >> 1;
    const int m0 = ((cl & 7) * 2 + rank) * 128;
    const int ng = cl >> 3;
    if (tid == 0) {
        for (int i = 0; i < 8; i++) mbar_init(a_full + 8 * i, 1);
        for (int i = 0; i < G1_NS; i++) { mbar_init(b_full + 8 * i, 1); mbar_init(b_empty + 8 * i, 8); }
        mbar_init(c_free, 1);
        fence_barrier_init();
    }
    __syncthreads();
    cluster_sync_all();
    pdl_launch();
    if (wg == 3) {
        reg_dec<24>();
        if (tid == 384) {
            const CUtensorMap* tw = ng < 4 ? &tm_wk : &tm_wv;
            const int n0 = (ng & 3) * 1024 + rank * 64;
            for (int it = 0; it < 64; it++) {
                const int st = it % G1_NS;
                if (it < 8) {
                    mbar_expect_tx(a_full + 8 * it, 16384);
                    tma_load_2d(sA + it * 16384, &tm_c, it * 64, m0, a_full + 8 * it);
                }
                mbar_wait(b_empty + 8 * st, ((it / G1_NS) & 1) ^ 1);
                mbar_expect_tx(b_full + 8 * st, 16384);
                tma_load_2d_mc(sB + st * 16384 + rank * 8192, tw, n0 + (it >> 3) * 128, (it & 7) * 64, b_full + 8 * st, 3);
                if (it + 8 < 64 && (it & 7) == (cl & 7)) tma_prefetch_2d(tw, n0 + ((it + 8) >> 3) * 128, (it & 7) * 64);
                if (it == 24) bulk_prefetch(px + blockIdx.x * 8192, 16384);
                if (it == 32) bulk_prefetch(pwq + blockIdx.x * 16384, 32768);
            }
        }
        __syncwarp();
        cluster_sync_all();
    } else if (wg == 2) {
        reg_dec<96>();
        ssm_kgen_warp(sp, blockIdx.x * 4 + (warp & 3), lane);
        cluster_sync_all();
    } else {
        reg_inc<192>();
        float acc[2][64];
        const uint32_t stg = sC;
        if (wg == 1) named_arrive(3, 256);
        for (int tt = 0; tt < 4; tt++) {
            const int t = 2 * tt + wg;
            named_sync(3 + wg, 256);
#pragma unroll 1
            for (int kc = 0; kc < 8; kc++) {
                const int it = t * 8 + kc, st = it % G1_NS;
                if (tt == 0) mbar_wait(a_full + 8 * kc, 0);
                mbar_wait(b_full + 8 * st, (it / G1_NS) & 1);
                wg_fence();
                const uint64_t da = desc_kmajor(sA + kc * 16384), db = desc_mnmajor(sB + st * 16384, 8192);
#pragma unroll
                for (int k = 0; k < 4; k++) {
                    wgmma_ss128<1>(acc[0], da + k * 2, db + k * 128, (kc | k) != 0);
                    wgmma_ss128<1>(acc[1], da + 512 + k * 2, db + k * 128, (kc | k) != 0);
                }
                wg_commit();
                if (kc == 7 && t < 7) named_arrive(3 + (wg ^ 1), 256);
                if (kc > 0) {
                    wg_wait<1>();
                    if (lane < 2) mbar_arrive_cluster(b_empty + 8 * ((it - 1) % G1_NS), lane);
                }
            }
            wg_wait<0>();
            if (lane < 2) mbar_arrive_cluster(b_empty + 8 * ((t * 8 + 7) % G1_NS), lane);
#pragma unroll
            for (int nh = 0; nh < 2; nh++) {
                if (nh == 0) {
                    if (t > 0) mbar_wait(c_free, (t - 1) & 1);
                } else {
                    if ((tid & 127) == 0) bulk_wait_read<0>();
                    named_sync(1 + wg, 128);
                }
                store_slab64(stg, (warp & 3) * 16, acc[0] + nh * 32, 1.f, 1.f, lane);
                store_slab64(stg, 64 + (warp & 3) * 16, acc[1] + nh * 32, 1.f, 1.f, lane);
                fence_proxy_async();
                named_sync(1 + wg, 128);
                if ((tid & 127) == 0) {
                    tma_store_2d(&tm_kv_st, stg, ng * 1024 + t * 128 + nh * 64, m0);
                    bulk_commit();
                    if (nh == 1) { bulk_wait_read<0>(); mbar_arrive(c_free); }
                }
            }
        }
        if ((tid & 127) == 0) bulk_wait<0>();
        __syncwarp();
        cluster_sync_all();
    }
}
constexpr int AT_NS = 6;
constexpr int AT_SMEM = AT_NS * 32768 + 32768 + 256 + 1024;
constexpr int AT_ITEMS = 512;

DEVI uint32_t hmax2(uint32_t a, uint32_t b) { uint32_t r; asm("max.bf16x2 %0, %1, %2;" : "=r"(r) : "r"(a), "r"(b)); return r; }
DEVI uint32_t hmul2(uint32_t a, uint32_t b) { uint32_t r; asm("mul.rn.bf16x2 %0, %1, %2;" : "=r"(r) : "r"(a), "r"(b)); return r; }
DEVI uint32_t hfma2(uint32_t a, uint32_t b, uint32_t c) { uint32_t r; asm("fma.rn.bf16x2 %0, %1, %2, %3;" : "=r"(r) : "r"(a), "r"(b), "r"(c)); return r; }
DEVI float blo(uint32_t v) { return __uint_as_float(v << 16); }
DEVI float bhi(uint32_t v) { return __uint_as_float(v & 0xffff0000u); }

template <bool FIRST>
DEVI void softmax_tile(float* s, float& m0, float& m1, float& l0, float& l1, float& al0, float& al1) {
    const uint32_t HI = 0x3DB53DB5u;
    const uint32_t LO = 0x371E371Eu;
    const float L2E = 1.4426950408889634f;
    uint32_t x0 = 0xFF80FF80u, x1 = 0xFF80FF80u;
#pragma unroll
    for (int j = 0; j < 16; j++) {
        uint32_t a = pack_bf16(s[4 * j], s[4 * j + 1]), b = pack_bf16(s[4 * j + 2], s[4 * j + 3]);
        a = hfma2(a, HI, hmul2(a, LO));
        b = hfma2(b, HI, hmul2(b, LO));
        s[4 * j] = __uint_as_float(a); s[4 * j + 2] = __uint_as_float(b);
        x0 = hmax2(x0, a); x1 = hmax2(x1, b);
    }
    uint32_t x = hmax2(__byte_perm(x0, x1, 0x5410), __byte_perm(x0, x1, 0x7632));
    x = hmax2(x, __shfl_xor_sync(~0u, x, 1));
    x = hmax2(x, __shfl_xor_sync(~0u, x, 2));
    float n0 = blo(x), n1 = bhi(x);
    if (!FIRST) {
        n0 = fmaxf(n0, m0); n1 = fmaxf(n1, m1);
        al0 = ex2((m0 - n0) * L2E); al1 = ex2((m1 - n1) * L2E);
    }
    m0 = n0; m1 = n1;
    const float c0 = -n0 * L2E, c1 = -n1 * L2E;
    float s0 = 0.f, s1 = 0.f;
#pragma unroll
    for (int j = 0; j < 16; j++) {
        uint32_t a = __float_as_uint(s[4 * j]), b = __float_as_uint(s[4 * j + 2]);
        float e0 = ex2(fmaf(blo(a), L2E, c0)), e1 = ex2(fmaf(bhi(a), L2E, c0));
        float e2 = ex2(fmaf(blo(b), L2E, c1)), e3 = ex2(fmaf(bhi(b), L2E, c1));
        s0 += e0 + e1; s1 += e2 + e3;
        s[4 * j] = e0; s[4 * j + 1] = e1; s[4 * j + 2] = e2; s[4 * j + 3] = e3;
    }
    if (FIRST) { l0 = s0; l1 = s1; }
    else { l0 = fmaf(l0, al0, s0); l1 = fmaf(l1, al1, s1); }
}

struct Ring {
    int st; uint32_t ph;
    DEVI void next() { if (++st == AT_NS) { st = 0; ph ^= 1; } }
};

__global__ void __launch_bounds__(384, 1)
attn_kernel(const __grid_constant__ CUtensorMap tm_x, const __grid_constant__ CUtensorMap tm_wq,
            const __grid_constant__ CUtensorMap tm_kv, const __grid_constant__ CUtensorMap tm_ctx_st,
            const bf16* __restrict__ pu, const bf16* __restrict__ pwo) {
    extern __shared__ uint8_t smem_raw[];
    const uint32_t sb = (smem_u32(smem_raw) + 1023) & ~1023u;
    const uint32_t sO = sb + AT_NS * 32768, bars = sO + 32768;
    const uint32_t full = bars, empty = bars + 64;
    volatile int* slots = reinterpret_cast<volatile int*>(smem_raw + (bars + 128 - smem_u32(smem_raw)));
    const int tid = threadIdx.x, warp = tid >> 5, lane = tid & 31, wg = tid >> 7;
    if (tid == 0) {
        for (int i = 0; i < AT_NS; i++) { mbar_init(full + 8 * i, 1); mbar_init(empty + 8 * i, 8); }
        fence_barrier_init();
    }
    __syncthreads();
    if (wg == 2) {
        reg_dec<24>();
        if (warp == 8 && lane == 0) {
            Ring r{0, 1};
            int n = 0;
            while (true) {
                int idx = (int)atomicInc(&g_sched, AT_ITEMS + gridDim.x - 1);
                if (idx >= AT_ITEMS - 128 && idx < AT_ITEMS) {
                    bulk_prefetch(pu + (idx - (AT_ITEMS - 128)) * 8192, 16384);
                    bulk_prefetch(pwo + (idx - (AT_ITEMS - 128)) * 16384, 32768);
                }
                mbar_wait(empty + 8 * r.st, r.ph);
                if (idx >= AT_ITEMS) {
                    slots[n & 3] = -1;
                    mbar_arrive(full + 8 * r.st);
                    break;
                }
                slots[n & 3] = idx;
                const int qi = 15 - (idx >> 5), h = idx & 31;
                for (int kc = 0; kc < 8; kc++) {
                    if (kc) mbar_wait(empty + 8 * r.st, r.ph);
                    const uint32_t fb = full + 8 * r.st, dst = sb + r.st * 32768;
                    mbar_expect_tx(fb, 32768);
                    tma_load_2d(dst, &tm_x, kc * 64, qi * 128, fb);
                    tma_load_2d(dst + 16384, &tm_wq, h * 128, kc * 64, fb);
                    tma_load_2d(dst + 24576, &tm_wq, h * 128 + 64, kc * 64, fb);
                    r.next();
                }
                if (n == 0) { pdl_wait(); pdl_launch(); }
                for (int j = qi; j >= -1; j--) {
#pragma unroll
                    for (int v = 0; v < 2; v++) {
                        const int jj = j + v;
                        if (jj < 0 || jj > qi || (v == 0 && j < 0)) continue;
                        mbar_wait(empty + 8 * r.st, r.ph);
                        const uint32_t fb = full + 8 * r.st, dst = sb + r.st * 32768;
                        mbar_expect_tx(fb, 32768);
                        tma_load_2d(dst, &tm_kv, v * HDALL + h * 128, jj * 128, fb);
                        tma_load_2d(dst + 16384, &tm_kv, v * HDALL + h * 128 + 64, jj * 128, fb);
                        r.next();
                    }
                }
                n++;
            }
            if (n == 0) { pdl_wait(); pdl_launch(); }
        }
    } else {
        reg_inc<240>();
        Ring r{0, 0};
        float o[64], s[64];
        uint32_t qf[32], pa[32];
        const int g = lane >> 2, t = lane & 3, wq = warp & 3;
        const uint32_t stg = sO + wg * 16384;
        if (wg == 1) named_arrive(3, 256);
        for (int n = 0;; n++) {
            mbar_wait(full + 8 * r.st, r.ph);
            const int idx = slots[n & 3];
            if (idx < 0) break;
            const int qi = 15 - (idx >> 5), h = idx & 31;
#pragma unroll 1
            for (int kc = 0; kc < 8; kc++) {
                if (kc) mbar_wait(full + 8 * r.st, r.ph);
                wg_fence();
                const uint32_t base = sb + r.st * 32768;
                const uint64_t da = desc_kmajor(base + wg * 8192), db = desc_mnmajor(base + 16384, 8192);
#pragma unroll
                for (int k = 0; k < 4; k++) wgmma_ss128<1>(s, da + k * 2, db + k * 128, (kc | k) != 0);
                wg_commit();
                if (kc) {
                    wg_wait<1>();
                    if (lane == 0) mbar_arrive(empty + 8 * (r.st == 0 ? AT_NS - 1 : r.st - 1));
                }
                r.next();
            }
            wg_wait<0>();
            if (lane == 0) mbar_arrive(empty + 8 * (r.st == 0 ? AT_NS - 1 : r.st - 1));
#pragma unroll
            for (int i = 0; i < 32; i++) qf[i] = pack_bf16(s[2 * i], s[2 * i + 1]);
            float m0, m1, l0, l1, al0, al1;
            auto issue_qk = [&]() {
                mbar_wait(full + 8 * r.st, r.ph);
                wg_fence();
                const uint64_t db = desc_kmajor(sb + r.st * 32768);
#pragma unroll
                for (int k = 0; k < 8; k++) wgmma_rs128<0>(s, qf + 4 * k, db + (k >> 2) * 1024 + (k & 3) * 2, k != 0);
                wg_commit();
            };
            auto issue_pv = [&](const uint32_t* p, int st, uint32_t ph, int acc) {
                mbar_wait(full + 8 * st, ph);
                wg_fence();
                const uint64_t db = desc_mnmajor(sb + st * 32768, 16384);
#pragma unroll
                for (int k = 0; k < 8; k++) wgmma_rs128<1>(o, p + 4 * k, db + k * 128, acc | k);
                wg_commit();
            };
            issue_qk();
            wg_wait<0>();
            if (lane == 0) mbar_arrive(empty + 8 * r.st);
            r.next();
            {
                const int row = wg * 64 + wq * 16 + g;
#pragma unroll
                for (int j = 0; j < 16; j++) {
                    const int c = 8 * j + 2 * t;
                    if (c > row) s[4 * j] = -INFINITY;
                    if (c + 1 > row) s[4 * j + 1] = -INFINITY;
                    if (c > row + 8) s[4 * j + 2] = -INFINITY;
                    if (c + 1 > row + 8) s[4 * j + 3] = -INFINITY;
                }
            }
            softmax_tile<true>(s, m0, m1, l0, l1, al0, al1);
#pragma unroll
            for (int i = 0; i < 32; i++) pa[i] = pack_bf16(s[2 * i], s[2 * i + 1]);
            int first = 0;
#pragma unroll 1
            for (int j = qi; j >= 1; j--) {
                named_sync(3 + wg, 256);
                issue_qk();
                const int kst = r.st;
                r.next();
                issue_pv(pa, r.st, r.ph, first);
                named_arrive(3 + (wg ^ 1), 256);
                wg_wait<1>();
                if (lane == 0) mbar_arrive(empty + 8 * kst);
                softmax_tile<false>(s, m0, m1, l0, l1, al0, al1);
                wg_wait<0>();
                if (lane == 0) mbar_arrive(empty + 8 * r.st);
                r.next();
#pragma unroll
                for (int i = 0; i < 32; i++) pa[i] = pack_bf16(s[2 * i], s[2 * i + 1]);
#pragma unroll
                for (int i = 0; i < 16; i++) {
                    o[4 * i] *= al0; o[4 * i + 1] *= al0; o[4 * i + 2] *= al1; o[4 * i + 3] *= al1;
                }
                first = 1;
            }
            issue_pv(pa, r.st, r.ph, first);
            l0 += __shfl_xor_sync(~0u, l0, 1); l0 += __shfl_xor_sync(~0u, l0, 2);
            l1 += __shfl_xor_sync(~0u, l1, 1); l1 += __shfl_xor_sync(~0u, l1, 2);
            const float i0 = 1.f / l0, i1 = 1.f / l1;
            if ((tid & 127) == 0) bulk_wait_read<0>();
            named_sync(1 + wg, 128);
            wg_wait<0>();
            if (lane == 0) mbar_arrive(empty + 8 * r.st);
            r.next();
            store_slab64(stg, wq * 16, o, i0, i1, lane);
            store_slab64(stg + 8192, wq * 16, o + 32, i0, i1, lane);
            fence_proxy_async();
            named_sync(1 + wg, 128);
            if ((tid & 127) == 0) {
                tma_store_2d(&tm_ctx_st, stg, h * 128, qi * 128 + wg * 64);
                tma_store_2d(&tm_ctx_st, stg + 8192, h * 128 + 64, qi * 128 + wg * 64);
                bulk_commit();
            }
        }
        if ((tid & 127) == 0) bulk_wait<0>();
    }
}
constexpr int OP_NS = 4;
constexpr int OP_ULD = 41 * 16;
constexpr int OP_UCH = 8 * OP_ULD;
constexpr int OP_SMEM = OP_NS * 32768 + 32768 + 4 * WTAB * 4 + 4 * OP_UCH + 4 * 648 * 4 + 256 + 1024;

template <int N> DEVI void wgmma_conv(float* d, const uint32_t* a, uint64_t db);
template <> DEVI void wgmma_conv<32>(float* d, const uint32_t* a, uint64_t db) {
    asm volatile("wgmma.mma_async.sync.aligned.m64n32k16.f32.bf16.bf16 {%0,%1,%2,%3,%4,%5,%6,%7,%8,%9,%10,%11,%12,%13,%14,%15}, "
                 "{%16,%17,%18,%19}, %20, 1, 1, 1, 0;"
                 : ACC8(d, 0), ACC8(d, 8) : "r"(a[0]), "r"(a[1]), "r"(a[2]), "r"(a[3]), "l"(db));
}
template <> DEVI void wgmma_conv<24>(float* d, const uint32_t* a, uint64_t db) {
    asm volatile("wgmma.mma_async.sync.aligned.m64n24k16.f32.bf16.bf16 {%0,%1,%2,%3,%4,%5,%6,%7,%8,%9,%10,%11}, "
                 "{%12,%13,%14,%15}, %16, 1, 1, 1, 0;"
                 : ACC8(d, 0), "+f"(d[8]), "+f"(d[9]), "+f"(d[10]), "+f"(d[11]) : "r"(a[0]), "r"(a[1]), "r"(a[2]), "r"(a[3]), "l"(db));
}
template <> DEVI void wgmma_conv<16>(float* d, const uint32_t* a, uint64_t db) {
    asm volatile("wgmma.mma_async.sync.aligned.m64n16k16.f32.bf16.bf16 {%0,%1,%2,%3,%4,%5,%6,%7}, "
                 "{%8,%9,%10,%11}, %12, 1, 1, 1, 0;"
                 : ACC8(d, 0) : "r"(a[0]), "r"(a[1]), "r"(a[2]), "r"(a[3]), "l"(db));
}
template <> DEVI void wgmma_conv<8>(float* d, const uint32_t* a, uint64_t db) {
    asm volatile("wgmma.mma_async.sync.aligned.m64n8k16.f32.bf16.bf16 {%0,%1,%2,%3}, "
                 "{%4,%5,%6,%7}, %8, 1, 1, 1, 0;"
                 : "+f"(d[0]), "+f"(d[1]), "+f"(d[2]), "+f"(d[3]) : "r"(a[0]), "r"(a[1]), "r"(a[2]), "r"(a[3]), "l"(db));
}
DEVI uint32_t lds32(uint32_t a) { uint32_t v; asm volatile("ld.shared.b32 %0, [%1];" : "=r"(v) : "r"(a)); return v; }
DEVI uint32_t lds16(uint32_t a) { uint16_t v; asm volatile("ld.shared.b16 %0, [%1];" : "=h"(v) : "r"(a)); return v; }

template <int J> DEVI void conv_pair(float* acc, uint32_t* f, uint32_t wa, uint64_t du, int c) {
#pragma unroll
    for (int i = 0; i < 8; i++) {
        f[4 * i] = lds32(wa + i * 64); f[4 * i + 1] = lds32(wa + i * 64 + 32);
        f[4 * i + 2] = lds32(wa + i * 64 - 32); f[4 * i + 3] = lds32(wa + i * 64);
    }
    wg_fence();
#pragma unroll
    for (int i = 0; i < 8; i++) {
        const int kk = 3 - (i & 3);
        const uint64_t db = du + (uint64_t)(kk * 2 * (OP_ULD / 16) + (i >> 2) + c);
        wgmma_conv<32 - 8 * J>(acc, f + 4 * i, db);
    }
    wg_commit();
}
template <int J> DEVI void conv_group(float* acc, uint32_t wa, uint64_t du) {
    uint32_t fa[32], fb[32];
#pragma unroll
    for (int h = 0; h < 2; h++) {
        const int c = 8 * J + 4 * h;
        conv_pair<J>(acc, fa, wa + c * 256, du, c);
        wg_wait<1>();
        conv_pair<J>(acc, fb, wa + (c + 2) * 256, du, c + 2);
        wg_wait<1>();
    }
    wg_wait<0>();
}

__global__ void __cluster_dims__(2, 1, 1) __launch_bounds__(512, 1)
outproj_kernel(const __grid_constant__ CUtensorMap tm_ctx, const __grid_constant__ CUtensorMap tm_wo,
               const __grid_constant__ CUtensorMap tm_out, SsmParams sp, bf16* __restrict__ out) {
    extern __shared__ uint8_t smem_raw[];
    const uint32_t sb = (smem_u32(smem_raw) + 1023) & ~1023u;
    const uint32_t sX = sb + OP_NS * 32768, sW = sX + 32768, sU = sW + 4 * WTAB * 4, sK = sU + 4 * OP_UCH, bars = sK + 4 * 648 * 4;
    const uint32_t full = bars, empty = bars + 64, xfull = bars + 128, wfull = bars + 136;
    const int tid = threadIdx.x, warp = tid >> 5, lane = tid & 31, wg = tid >> 7;
    const uint32_t rank = cluster_rank();
    const uint32_t kr = rank;
    const int cl = blockIdx.x >> 1;
    const int m0 = (cl >> 2) * 128, n0 = (cl & 3) * 128, k0 = kr * 2048;
    if (tid == 0) {
        for (int i = 0; i < OP_NS; i++) { mbar_init(full + 8 * i, 1); mbar_init(empty + 8 * i, 8); }
        mbar_init(xfull, 1);
        mbar_init(wfull, 1);
        fence_barrier_init();
    }
    __syncthreads();
    cluster_sync_all();
    if (wg == 3) {
        reg_dec<40>();
        if (tid == 384) {
            mbar_expect_tx(wfull, 4 * 648 * 4);
            bulk_load(sK, g_kp + blockIdx.x * 4 * 648, 4 * 648 * 4, wfull);
            mbar_expect_tx(xfull, 32768);
            for (int it = 0; it < OP_NS; it++) {
                const uint32_t dst = sb + it * 32768, fb = full + 8 * it;
                mbar_expect_tx(fb, 32768);
                tma_load_2d(dst + 16384, &tm_wo, n0, k0 + it * 64, fb);
                tma_load_2d(dst + 24576, &tm_wo, n0 + 64, k0 + it * 64, fb);
            }
            pdl_wait();
            for (int it = 0; it < 32; it++) {
                const int st = it & (OP_NS - 1);
                const uint32_t dst = sb + st * 32768, fb = full + 8 * st;
                if (it >= OP_NS) {
                    mbar_wait(empty + 8 * st, ((it / OP_NS) & 1) ^ 1);
                    mbar_expect_tx(fb, 32768);
                    tma_load_2d(dst + 16384, &tm_wo, n0, k0 + it * 64, fb);
                    tma_load_2d(dst + 24576, &tm_wo, n0 + 64, k0 + it * 64, fb);
                }
                tma_load_2d(dst, &tm_ctx, k0 + it * 64, m0, fb);
                tma_load_2d(dst + 8192, &tm_ctx, k0 + it * 64, m0 + 64, fb);
            }
        }
        __syncwarp();
    } else if (wg == 2) {
        reg_inc<208>();
        const int ct = tid & 127, wq = warp & 3, g = lane >> 2, t = lane & 3;
        const int d0 = blockIdx.x * 4;
        uint2 v[2][8];
#pragma unroll
        for (int h = 0; h < 2; h++)
#pragma unroll
            for (int i = 0; i < 8; i++)
                v[h][i] = __ldg(reinterpret_cast<const uint2*>(sp.u + (size_t)((ct + 128 * h) * 8 + i) * SSM_D + d0));
        mbar_wait(wfull, 0);
        for (int qd = ct; qd < WTAB / 4; qd += 128) {
            const int o = qd * 4 - 64;
            uint32_t ka[5];
#pragma unroll
            for (int e = 0; e < 5; e++) ka[e] = sK + 4 * kp_index(max(o - 1 + e, 0));
#pragma unroll
            for (int c = 0; c < 4; c++) {
                float k[5];
#pragma unroll
                for (int e = 0; e < 5; e++) k[e] = o - 1 + e < 0 ? 0.f : __uint_as_float(lds32(ka[e] + c * 648 * 4));
                asm volatile("st.shared.v4.b32 [%0], {%1,%2,%3,%4};" ::"r"(sW + (c * WTAB + qd * 4) * 4), "r"(pack_bf16(k[1], k[0])),
                             "r"(pack_bf16(k[2], k[1])), "r"(pack_bf16(k[3], k[2])), "r"(pack_bf16(k[4], k[3])) : "memory");
            }
        }
        for (int i = ct; i < 4 * 8 * 8; i += 128) {
            const uint32_t a = sU + (i >> 3) * OP_ULD + (32 + (i & 7)) * 16;
            asm volatile("st.shared.v4.b32 [%0], {%1,%1,%1,%1};" ::"r"(a), "r"(0) : "memory");
        }
#pragma unroll
        for (int h = 0; h < 2; h++) {
            const int q = ct + 128 * h;
            const uint32_t a = sU + (q & 7) * OP_ULD + (31 - (q >> 3)) * 16;
#pragma unroll
            for (int c = 0; c < 4; c++) {
                uint32_t w[4];
#pragma unroll
                for (int i = 0; i < 4; i++) {
                    const uint32_t lo = (c & 2) ? v[h][2 * i].y : v[h][2 * i].x, hi = (c & 2) ? v[h][2 * i + 1].y : v[h][2 * i + 1].x;
                    w[i] = __byte_perm(lo, hi, (c & 1) ? 0x7632 : 0x5410);
                }
                asm volatile("st.shared.v4.b32 [%0], {%1,%2,%3,%4};" ::"r"(a + c * OP_UCH), "r"(w[0]), "r"(w[1]), "r"(w[2]), "r"(w[3]) : "memory");
            }
        }
        const uint2 dsk = __ldg(reinterpret_cast<const uint2*>(sp.dskip + d0));
        fence_proxy_async();
        named_sync(3, 128);
        uint32_t res[16][2];
#pragma unroll
        for (int c = 0; c < 4; c++) {
            float acc[16];
#pragma unroll
            for (int i = 0; i < 16; i++) acc[i] = 0.f;
            const uint32_t wa = sW + (c * WTAB + 64 + 16 * (wq - 3) + g - 2 * t) * 4;
            const uint64_t du = make_desc(sU + c * OP_UCH, OP_ULD, 128, 0);
            conv_group<0>(acc, wa, du);
            conv_group<1>(acc, wa, du);
            conv_group<2>(acc, wa, du);
            conv_group<3>(acc, wa, du);
            const uint32_t dw = (c & 2) ? dsk.y : dsk.x;
            const float D = (c & 1) ? bhi(dw) : blo(dw);
#pragma unroll
            for (int i = 0; i < 16; i++) {
                const int n = 8 * (i >> 2) + 2 * t + (i & 1), j = 2 * wq + ((i >> 1) & 1);
                const float u = __uint_as_float(lds16(sU + c * OP_UCH + j * OP_ULD + n * 16 + g * 2) << 16);
                const uint32_t o = __bfloat16_as_ushort(__float2bfloat16_rn(rbf(acc[i]) + rbf(u * D)));
                if (c & 1) res[i][c >> 1] |= o << 16; else res[i][c >> 1] = o;
            }
        }
#pragma unroll
        for (int i = 0; i < 16; i++) {
            const int a = 31 - (8 * (i >> 2) + 2 * t + (i & 1)), b = 16 * wq + g + 8 * ((i >> 1) & 1);
            *reinterpret_cast<uint2*>(out + (size_t)(64 * a + b) * 1024 + 512 + d0) = make_uint2(res[i][0], res[i][1]);
        }
    } else {
        float acc[64];
#pragma unroll 1
        for (int it = 0; it < 32; it++) {
            const int st = it & (OP_NS - 1);
            mbar_wait(full + 8 * st, (it / OP_NS) & 1);
            wg_fence();
            const uint32_t base = sb + st * 32768;
            const uint64_t da = desc_kmajor(base + wg * 8192), db = desc_mnmajor(base + 16384, 8192);
#pragma unroll
            for (int k = 0; k < 4; k++) wgmma_ss128<1>(acc, da + k * 2, db + k * 128, (it | k) != 0);
            wg_commit();
            if (it > 0 && it + OP_NS - 1 < 32) {
                wg_wait<1>();
                if (lane == 0) mbar_arrive(empty + 8 * ((it - 1) & (OP_NS - 1)));
            }
        }
        wg_wait<0>();
        uint32_t peer, pbar;
        asm volatile("mapa.shared::cluster.u32 %0, %1, %2;" : "=r"(peer) : "r"(sX + tid * 16), "r"(rank ^ 1));
        asm volatile("mapa.shared::cluster.u32 %0, %1, %2;" : "=r"(pbar) : "r"(xfull), "r"(rank ^ 1));
#pragma unroll
        for (int i = 0; i < 8; i++) {
            const float* s = acc + 4 * i;
            const float a = kr ? s[0] : s[32], b = kr ? s[1] : s[33], c = kr ? s[2] : s[34], d = kr ? s[3] : s[35];
            asm volatile("st.async.weak.shared::cluster.mbarrier::complete_tx::bytes.v4.f32 [%0], {%1,%2,%3,%4}, [%5];"
                         ::"r"(peer + i * 4096), "f"(a), "f"(b), "f"(c), "f"(d), "r"(pbar) : "memory");
        }
        mbar_wait(xfull, 0);
        float r[32];
#pragma unroll
        for (int i = 0; i < 8; i++) {
            float a, b, c, d;
            asm volatile("ld.shared.v4.f32 {%0,%1,%2,%3}, [%4];" : "=f"(a), "=f"(b), "=f"(c), "=f"(d) : "r"(sX + tid * 16 + i * 4096));
            const float* s = acc + 4 * i;
            r[4 * i] = a + (kr ? s[32] : s[0]); r[4 * i + 1] = b + (kr ? s[33] : s[1]);
            r[4 * i + 2] = c + (kr ? s[34] : s[2]); r[4 * i + 3] = d + (kr ? s[35] : s[3]);
        }
        const uint32_t stg = sb + wg * 8192;
        store_slab64(stg, (warp & 3) * 16, r, 1.f, 1.f, lane);
        fence_proxy_async();
        named_sync(1 + wg, 128);
        if ((tid & 127) == 0) {
            tma_store_2d(&tm_out, stg, n0 + kr * 64, m0 + wg * 64);
            bulk_commit();
            bulk_wait<0>();
        }
    }
}

typedef CUresult (*EncodeFn)(CUtensorMap*, CUtensorMapDataType, cuuint32_t, void*, const cuuint64_t*, const cuuint64_t*,
                             const cuuint32_t*, const cuuint32_t*, CUtensorMapInterleave, CUtensorMapSwizzle,
                             CUtensorMapL2promotion, CUtensorMapFloatOOBfill);

static void make_map(EncodeFn fn, CUtensorMap* m, const void* p, uint64_t cols, uint64_t rows, uint32_t box_rows) {
    cuuint64_t dims[2] = {cols, rows};
    cuuint64_t strides[1] = {cols * 2};
    cuuint32_t box[2] = {64, box_rows};
    cuuint32_t es[2] = {1, 1};
    fn(m, CU_TENSOR_MAP_DATA_TYPE_BFLOAT16, 2, const_cast<void*>(p), dims, strides, box, es, CU_TENSOR_MAP_INTERLEAVE_NONE,
       CU_TENSOR_MAP_SWIZZLE_128B, CU_TENSOR_MAP_L2_PROMOTION_L2_256B, CU_TENSOR_MAP_FLOAT_OOB_FILL_NONE);
}

extern "C" void kernel_launch(void* const* d_in, const int* in_sizes, int n_in, void* d_out, int out_size) {
    void* fp = nullptr;
    cudaDriverEntryPointQueryResult qr;
    cudaGetDriverEntryPoint("cuTensorMapEncodeTiled", &fp, cudaEnableDefault, &qr);
    EncodeFn fn = (EncodeFn)fp;
    void *p_kv, *p_ctx;
    cudaGetSymbolAddress(&p_kv, g_kv);
    cudaGetSymbolAddress(&p_ctx, g_ctx);
    CUtensorMap tm_x, tm_c, tm_wq, tm_wk, tm_wv, tm_wo, tm_kv, tm_ctx, tm_out;
    make_map(fn, &tm_x, d_in[0], DM, SEQ, 128);
    make_map(fn, &tm_c, d_in[1], DM, SEQ, 128);
    make_map(fn, &tm_wq, d_in[2], HDALL, DM, 64);
    make_map(fn, &tm_wk, d_in[3], HDALL, DM, 64);
    make_map(fn, &tm_wv, d_in[4], HDALL, DM, 64);
    make_map(fn, &tm_wo, d_in[5], DM, HDALL, 64);
    make_map(fn, &tm_kv, p_kv, 2 * HDALL, SEQ, 128);
    make_map(fn, &tm_ctx, p_ctx, HDALL, SEQ, 64);
    make_map(fn, &tm_out, d_out, 1024, SEQ, 64);
    SsmParams sp;
    sp.u = (const bf16*)d_in[6]; sp.lar = (const bf16*)d_in[7]; sp.aim = (const bf16*)d_in[8];
    sp.cre = (const bf16*)d_in[9]; sp.cim = (const bf16*)d_in[10]; sp.ldt = (const bf16*)d_in[11]; sp.dskip = (const bf16*)d_in[12];
    cudaFuncSetAttribute(gemm_kv_kernel, cudaFuncAttributeMaxDynamicSharedMemorySize, G1_SMEM);
    cudaFuncSetAttribute(attn_kernel, cudaFuncAttributeMaxDynamicSharedMemorySize, AT_SMEM);
    cudaFuncSetAttribute(outproj_kernel, cudaFuncAttributeMaxDynamicSharedMemorySize, OP_SMEM);
    cudaStream_t st = cudaStreamPerThread;
    gemm_kv_kernel<<<128, G1_THREADS, G1_SMEM, st>>>(tm_c, tm_wk, tm_wv, tm_kv, sp, (const bf16*)d_in[0], (const bf16*)d_in[2]);
    cudaLaunchAttribute at[1];
    at[0].id = cudaLaunchAttributeProgrammaticStreamSerialization;
    at[0].val.programmaticStreamSerializationAllowed = 1;
    cudaLaunchConfig_t cfg = {};
    cfg.stream = st; cfg.attrs = at; cfg.numAttrs = 1;
    cfg.gridDim = dim3(132); cfg.blockDim = dim3(384); cfg.dynamicSmemBytes = AT_SMEM;
    cudaLaunchKernelEx(&cfg, attn_kernel, tm_x, tm_wq, tm_kv, tm_ctx, sp.u, (const bf16*)d_in[5]);
    cfg.gridDim = dim3(128); cfg.blockDim = dim3(512); cfg.dynamicSmemBytes = OP_SMEM;
    cudaLaunchKernelEx(&cfg, outproj_kernel, tm_ctx, tm_wo, tm_out, sp, (bf16*)d_out);
}
```

```cpp
#include <cuda_runtime.h>
#include <cuda_bf16.h>
#include <cuda.h>
#include <stdint.h>

typedef __nv_bfloat16 bf16;

#define DEVI __device__ __forceinline__

constexpr int SEQ = 2048, DM = 512, NH = 32, HD = 128, HDALL = NH * HD;
constexpr int SSM_D = 512, SSM_N = 128;
constexpr int WTAB = 2112;

__device__ bf16 g_kv[(size_t)SEQ * 2 * HDALL];
__device__ bf16 g_ctx[(size_t)SEQ * HDALL];
__device__ unsigned int g_sched;

#define STAMP(cond, i)
DEVI uint32_t smem_u32(const void* p) { return (uint32_t)__cvta_generic_to_shared(p); }
DEVI void mbar_init(uint32_t a, uint32_t cnt) { asm volatile("mbarrier.init.shared::cta.b64 [%0], %1;" ::"r"(a), "r"(cnt)); }
DEVI void mbar_expect_tx(uint32_t a, uint32_t bytes) {
    asm volatile("mbarrier.arrive.expect_tx.shared::cta.b64 _, [%0], %1;" ::"r"(a), "r"(bytes) : "memory");
}
DEVI void mbar_arrive(uint32_t a) { asm volatile("mbarrier.arrive.shared::cta.b64 _, [%0];" ::"r"(a) : "memory"); }
DEVI void mbar_arrive_cluster(uint32_t a, uint32_t cta) {
    asm volatile("{\n.reg .b32 r;\nmapa.shared::cluster.u32 r, %0, %1;\n"
                 "mbarrier.arrive.shared::cluster.b64 _, [r];\n}" ::"r"(a), "r"(cta) : "memory");
}
#define MBAR_WAIT_ASM(OP)                                                                              \
    asm volatile("{\n.reg .pred p, q;\n.reg .u32 t0, t1;\n" OP " p, [%0], %1;\n@p bra D_%=;\n"         \
                 "mov.u32 t0, %%globaltimer_lo;\nW_%=:\n" OP " p, [%0], %1;\n"                         \
                 "mov.u32 t1, %%globaltimer_lo;\nsub.u32 t1, t1, t0;\n"                                \
                 "setp.gt.or.u32 q, t1, 4000000, p;\n@!q bra W_%=;\nD_%=:\n}" ::"r"(a), "r"(parity) : "memory")
DEVI void mbar_wait(uint32_t a, uint32_t parity) { MBAR_WAIT_ASM("mbarrier.try_wait.parity.shared::cta.b64"); }
DEVI void mbar_wait_cluster(uint32_t a, uint32_t parity) { MBAR_WAIT_ASM("mbarrier.try_wait.parity.acquire.cluster.shared::cta.b64"); }
DEVI void fence_barrier_init() { asm volatile("fence.mbarrier_init.release.cluster;" ::: "memory"); }
DEVI void fence_proxy_async() { asm volatile("fence.proxy.async.shared::cta;" ::: "memory"); }
DEVI void cluster_sync_all() {
    asm volatile("barrier.cluster.arrive.release.aligned;\nbarrier.cluster.wait.acquire.aligned;" ::: "memory");
}
DEVI uint32_t cluster_rank() { uint32_t r; asm volatile("mov.u32 %0, %%cluster_ctarank;" : "=r"(r)); return r; }
DEVI void tma_load_2d(uint32_t dst, const CUtensorMap* m, int c0, int c1, uint32_t bar) {
    asm volatile("cp.async.bulk.tensor.2d.shared::cluster.global.mbarrier::complete_tx::bytes [%0], [%1, {%3, %4}], [%2];"
                 ::"r"(dst), "l"(m), "r"(bar), "r"(c0), "r"(c1) : "memory");
}
DEVI void tma_load_2d_mc(uint32_t dst, const CUtensorMap* m, int c0, int c1, uint32_t bar, uint16_t mask) {
    asm volatile("cp.async.bulk.tensor.2d.shared::cluster.global.mbarrier::complete_tx::bytes.multicast::cluster [%0], [%1, {%3, %4}], [%2], %5;"
                 ::"r"(dst), "l"(m), "r"(bar), "r"(c0), "r"(c1), "h"(mask) : "memory");
}
DEVI void tma_prefetch_2d(const CUtensorMap* m, int c0, int c1) {
    asm volatile("cp.async.bulk.prefetch.tensor.2d.L2.global [%0, {%1, %2}];" ::"l"(m), "r"(c0), "r"(c1) : "memory");
}
DEVI void tma_store_2d(const CUtensorMap* m, uint32_t src, int c0, int c1) {
    asm volatile("cp.async.bulk.tensor.2d.global.shared::cta.bulk_group [%0, {%2, %3}], [%1];"
                 ::"l"(m), "r"(src), "r"(c0), "r"(c1) : "memory");
}
DEVI void bulk_load(uint32_t dst, const void* src, uint32_t bytes, uint32_t bar) {
    asm volatile("cp.async.bulk.shared::cluster.global.mbarrier::complete_tx::bytes [%0], [%1], %2, [%3];"
                 ::"r"(dst), "l"(src), "r"(bytes), "r"(bar) : "memory");
}
DEVI void bulk_prefetch(const void* src, uint32_t bytes) {
    asm volatile("cp.async.bulk.prefetch.L2.global [%0], %1;" ::"l"(src), "r"(bytes) : "memory");
}
DEVI void bulk_commit() { asm volatile("cp.async.bulk.commit_group;" ::: "memory"); }
template <int N> DEVI void bulk_wait_read() { asm volatile("cp.async.bulk.wait_group.read %0;" ::"n"(N) : "memory"); }
template <int N> DEVI void bulk_wait() { asm volatile("cp.async.bulk.wait_group %0;" ::"n"(N) : "memory"); }
DEVI void prefetch_tmap(const CUtensorMap* m) { asm volatile("prefetch.tensormap [%0];" ::"l"(m) : "memory"); }
DEVI void named_sync(int id, int n) { asm volatile("bar.sync %0, %1;" ::"r"(id), "r"(n) : "memory"); }
DEVI void named_arrive(int id, int n) { asm volatile("bar.arrive %0, %1;" ::"r"(id), "r"(n) : "memory"); }
DEVI void pdl_wait() { asm volatile("griddepcontrol.wait;" ::: "memory"); }
DEVI void pdl_launch() { asm volatile("griddepcontrol.launch_dependents;" ::: "memory"); }
template <int R> DEVI void reg_inc() { asm volatile("setmaxnreg.inc.sync.aligned.u32 %0;" ::"n"(R)); }
template <int R> DEVI void reg_dec() { asm volatile("setmaxnreg.dec.sync.aligned.u32 %0;" ::"n"(R)); }

DEVI void wg_fence() { asm volatile("wgmma.fence.sync.aligned;" ::: "memory"); }
DEVI void wg_commit() { asm volatile("wgmma.commit_group.sync.aligned;" ::: "memory"); }
template <int N> DEVI void wg_wait() { asm volatile("wgmma.wait_group.sync.aligned %0;" ::"n"(N) : "memory"); }

DEVI uint64_t make_desc(uint32_t addr, uint32_t lbo, uint32_t sbo, uint32_t swz) {
    return (uint64_t)((addr & 0x3FFFF) >> 4) | ((uint64_t)(lbo >> 4) << 16) | ((uint64_t)(sbo >> 4) << 32) | ((uint64_t)swz << 62);
}
DEVI uint64_t desc_kmajor(uint32_t addr) { return make_desc(addr, 16, 1024, 1); }
DEVI uint64_t desc_mnmajor(uint32_t addr, uint32_t lbo) { return make_desc(addr, lbo, 1024, 1); }

#define ACC8(d, o) "+f"(d[o + 0]), "+f"(d[o + 1]), "+f"(d[o + 2]), "+f"(d[o + 3]), "+f"(d[o + 4]), "+f"(d[o + 5]), "+f"(d[o + 6]), "+f"(d[o + 7])
#define ACC64(d) ACC8(d, 0), ACC8(d, 8), ACC8(d, 16), ACC8(d, 24), ACC8(d, 32), ACC8(d, 40), ACC8(d, 48), ACC8(d, 56)
#define R64 "{%0,%1,%2,%3,%4,%5,%6,%7,%8,%9,%10,%11,%12,%13,%14,%15,%16,%17,%18,%19,%20,%21,%22,%23,%24,%25,%26,%27,%28,%29,%30,%31," \
            "%32,%33,%34,%35,%36,%37,%38,%39,%40,%41,%42,%43,%44,%45,%46,%47,%48,%49,%50,%51,%52,%53,%54,%55,%56,%57,%58,%59,%60,%61,%62,%63}"

template <int TB> DEVI void wgmma_ss128(float* d, uint64_t da, uint64_t db, int acc) {
    asm volatile("{\n.reg .pred p;\nsetp.ne.b32 p, %66, 0;\n"
                 "wgmma.mma_async.sync.aligned.m64n128k16.f32.bf16.bf16 " R64 ", %64, %65, p, 1, 1, 0, %67;\n}"
                 : ACC64(d) : "l"(da), "l"(db), "r"(acc), "n"(TB));
}
template <int TB> DEVI void wgmma_rs128(float* d, const uint32_t* a, uint64_t db, int acc) {
    asm volatile("{\n.reg .pred p;\nsetp.ne.b32 p, %69, 0;\n"
                 "wgmma.mma_async.sync.aligned.m64n128k16.f32.bf16.bf16 " R64 ", {%64,%65,%66,%67}, %68, p, 1, 1, %70;\n}"
                 : ACC64(d) : "r"(a[0]), "r"(a[1]), "r"(a[2]), "r"(a[3]), "l"(db), "r"(acc), "n"(TB));
}
DEVI uint32_t pack_bf16(float lo, float hi) {
    uint32_t r;
    asm("cvt.rn.bf16x2.f32 %0, %1, %2;" : "=r"(r) : "f"(hi), "f"(lo));
    return r;
}
DEVI void stmatrix_x4(uint32_t addr, uint32_t r0, uint32_t r1, uint32_t r2, uint32_t r3) {
    asm volatile("stmatrix.sync.aligned.m8n8.x4.shared.b16 [%0], {%1,%2,%3,%4};" ::"r"(addr), "r"(r0), "r"(r1), "r"(r2), "r"(r3) : "memory");
}
DEVI float ex2(float x) { float y; asm("ex2.approx.ftz.f32 %0, %1;" : "=f"(y) : "f"(x)); return y; }

DEVI void store_slab64(uint32_t base, int row0, const float* d, float s0, float s1, int lane) {
    int mi = lane >> 3, r = lane & 7;
    int row = row0 + (mi & 1) * 8 + r;
#pragma unroll
    for (int j = 0; j < 8; j += 2) {
        uint32_t r0 = pack_bf16(d[4 * j + 0] * s0, d[4 * j + 1] * s0);
        uint32_t r1 = pack_bf16(d[4 * j + 2] * s1, d[4 * j + 3] * s1);
        uint32_t r2 = pack_bf16(d[4 * j + 4] * s0, d[4 * j + 5] * s0);
        uint32_t r3 = pack_bf16(d[4 * j + 6] * s1, d[4 * j + 7] * s1);
        int chunk = j + (mi >> 1);
        stmatrix_x4(base + row * 128 + ((chunk ^ (row & 7)) << 4), r0, r1, r2, r3);
    }
}
struct cf { float x, y; };
DEVI cf cmul(cf a, cf b) { cf r; r.x = fmaf(a.x, b.x, -a.y * b.y); r.y = fmaf(a.x, b.y, a.y * b.x); return r; }
DEVI cf csq(cf a) { cf r; r.x = fmaf(a.x, a.x, -a.y * a.y); r.y = (a.x + a.x) * a.y; return r; }
DEVI cf cexp_(float re, float im) {
    float m = __expf(re), s, c;
    __sincosf(im, &s, &c);
    cf r; r.x = m * c; r.y = m * s; return r;
}
DEVI uint32_t h2(cf v) { uint32_t r; asm("cvt.rn.f16x2.f32 %0, %1, %2;" : "=r"(r) : "f"(v.y), "f"(v.x)); return r; }
DEVI uint32_t h2c(cf v) { uint32_t r; asm("cvt.rn.f16x2.f32 %0, %1, %2;" : "=r"(r) : "f"(-v.y), "f"(v.x)); return r; }
DEVI void mma_group(float (*c)[4], const uint32_t (*a)[4], const uint32_t (*b)[2]) {
    asm volatile(
        "mma.sync.aligned.m16n8k16.row.col.f32.f16.f16.f32 {%0,%1,%2,%3}, {%20,%21,%22,%23}, {%40,%41}, {%0,%1,%2,%3};\n"
        "mma.sync.aligned.m16n8k16.row.col.f32.f16.f16.f32 {%4,%5,%6,%7}, {%24,%25,%26,%27}, {%40,%41}, {%4,%5,%6,%7};\n"
        "mma.sync.aligned.m16n8k16.row.col.f32.f16.f16.f32 {%8,%9,%10,%11}, {%28,%29,%30,%31}, {%42,%43}, {%8,%9,%10,%11};\n"
        "mma.sync.aligned.m16n8k16.row.col.f32.f16.f16.f32 {%12,%13,%14,%15}, {%32,%33,%34,%35}, {%44,%45}, {%12,%13,%14,%15};\n"
        "mma.sync.aligned.m16n8k16.row.col.f32.f16.f16.f32 {%16,%17,%18,%19}, {%36,%37,%38,%39}, {%46,%47}, {%16,%17,%18,%19};\n"
        : "+f"(c[0][0]), "+f"(c[0][1]), "+f"(c[0][2]), "+f"(c[0][3]), "+f"(c[1][0]), "+f"(c[1][1]), "+f"(c[1][2]), "+f"(c[1][3]),
          "+f"(c[2][0]), "+f"(c[2][1]), "+f"(c[2][2]), "+f"(c[2][3]), "+f"(c[3][0]), "+f"(c[3][1]), "+f"(c[3][2]), "+f"(c[3][3]),
          "+f"(c[4][0]), "+f"(c[4][1]), "+f"(c[4][2]), "+f"(c[4][3])
        : "r"(a[0][0]), "r"(a[0][1]), "r"(a[0][2]), "r"(a[0][3]), "r"(a[1][0]), "r"(a[1][1]), "r"(a[1][2]), "r"(a[1][3]),
          "r"(a[2][0]), "r"(a[2][1]), "r"(a[2][2]), "r"(a[2][3]), "r"(a[3][0]), "r"(a[3][1]), "r"(a[3][2]), "r"(a[3][3]),
          "r"(a[4][0]), "r"(a[4][1]), "r"(a[4][2]), "r"(a[4][3]),
          "r"(b[0][0]), "r"(b[0][1]), "r"(b[1][0]), "r"(b[1][1]), "r"(b[2][0]), "r"(b[2][1]), "r"(b[3][0]), "r"(b[3][1]));
}
DEVI float bf2f(bf16 v) { return __bfloat162float(v); }
DEVI float rbf(float v) { return __bfloat162float(__float2bfloat16_rn(v)); }

struct SsmParams { const bf16 *lar, *aim, *cre, *cim, *ldt, *dskip, *u; };

DEVI int kp_index(int l) {
    int p = (int)rbf((float)l);
    return p < 256 ? p : (p < 512 ? 128 + (p >> 1) : (p < 1024 ? 256 + (p >> 2) : 384 + (p >> 3)));
}

DEVI void ssm_kgen_warp(const SsmParams& P, int d, int lane, float* kp) {
    const int g = lane >> 2, t = lane & 3;
    float ar[4], ai[4], cr[4], ci[4], gr[4], gi[4];
    bf16 raw[4][4];
    const bf16 rdt = P.ldt[d];
#pragma unroll
    for (int q = 0; q < 4; q++) {
        const int n = d * SSM_N + 32 * q + lane;
        raw[q][0] = P.lar[n]; raw[q][1] = P.aim[n]; raw[q][2] = P.cre[n]; raw[q][3] = P.cim[n];
    }
    const float dt = rbf(expf(bf2f(rdt)));
#pragma unroll
    for (int q = 0; q < 4; q++) {
        ar[q] = -rbf(expf(bf2f(raw[q][0]))) * dt;
        ai[q] = bf2f(raw[q][1]) * dt;
        cr[q] = 2.f * (bf2f(raw[q][2]) * dt);
        ci[q] = 2.f * (bf2f(raw[q][3]) * dt);
        float m = expf(ar[q] * 64.f), sn, cs;
        sincosf(ai[q] * 64.f, &sn, &cs);
        gr[q] = m * cs; gi[q] = m * sn;
    }
    float cm = 0.f;
#pragma unroll
    for (int q = 0; q < 4; q++) cm = fmaxf(cm, fmaxf(fabsf(cr[q]), fabsf(ci[q])));
#pragma unroll
    for (int o = 16; o; o >>= 1) cm = fmaxf(cm, __shfl_xor_sync(~0u, cm, o));
    const int ex = min(max((int)(__float_as_uint(cm) >> 23), 1), 253);
    const float cs_dn = __uint_as_float((uint32_t)(254 - ex) << 23), cs_up = __uint_as_float((uint32_t)ex << 23);
    float acc[5][4];
#pragma unroll
    for (int s = 0; s < 5; s++) { acc[s][0] = acc[s][1] = acc[s][2] = acc[s][3] = 0.f; }
    float klast = 0.f;
    const float gf = (float)g;
#pragma unroll
    for (int q = 0; q < 4; q++) {
#pragma unroll 1
        for (int g0 = 0; g0 < 8; g0 += 2) {
            uint32_t fa[5][4], fb[4][2];
#pragma unroll
            for (int h = 0; h < 2; h++) {
                const int src = ((g0 + h) << 2) | t;
                const float a_r = __shfl_sync(~0u, ar[q], src), a_i = __shfl_sync(~0u, ai[q], src);
                cf C, G;
                C.x = __shfl_sync(~0u, cr[q], src) * cs_dn; C.y = __shfl_sync(~0u, ci[q], src) * cs_dn;
                G.x = __shfl_sync(~0u, gr[q], src); G.y = __shfl_sync(~0u, gi[q], src);
                cf E = cexp_(a_r * gf, a_i * gf);
                cf B = csq(csq(csq(E)));
                fb[0][h] = h2c(cmul(C, B));
                cf EG = cmul(E, G);
                fa[0][2 * h] = h2(E); fa[0][2 * h + 1] = h2(EG);
                cf G2 = csq(G);
                cf X = cmul(E, G2), Xh = cmul(EG, G2);
                fa[1][2 * h] = h2(X); fa[1][2 * h + 1] = h2(Xh);
#pragma unroll
                for (int s = 2; s < 5; s++) {
                    B = csq(B); X = csq(X); Xh = csq(Xh);
                    fb[s - 1][h] = h2c(cmul(C, B));
                    fa[s][2 * h] = h2(X); fa[s][2 * h + 1] = h2(Xh);
                }
                X = csq(X);
                klast += fmaf(C.x, X.x, -C.y * X.y);
            }
            mma_group(acc, fa, fb);
        }
    }
    klast += __shfl_xor_sync(~0u, klast, 1);
    klast += __shfl_xor_sync(~0u, klast, 2);
#pragma unroll
    for (int s = 0; s < 5; s++) {
        int b = 128 * s + g + 16 * t;
        kp[b] = acc[s][0] * cs_up; kp[b + 8] = acc[s][1] * cs_up; kp[b + 64] = acc[s][2] * cs_up; kp[b + 72] = acc[s][3] * cs_up;
    }
    if (lane == 0) kp[640] = klast * cs_up;
}

constexpr int G1_THREADS = 384;
constexpr int G1_NS = 11;
constexpr int G1_SMEM = G1_NS * 16384 + 32768 + 256 + 1024;

__global__ void __cluster_dims__(2, 1, 1) __launch_bounds__(G1_THREADS, 1)
gemm_kv_kernel(const __grid_constant__ CUtensorMap tm_c, const __grid_constant__ CUtensorMap tm_wk,
               const __grid_constant__ CUtensorMap tm_wv, const __grid_constant__ CUtensorMap tm_kv_st,
               const bf16* __restrict__ px, const bf16* __restrict__ pwq) {
    extern __shared__ uint8_t smem_raw[];
    const uint32_t sb = (smem_u32(smem_raw) + 1023) & ~1023u;
    const uint32_t sC = sb + G1_NS * 16384, bars = sC + 32768;
    const uint32_t full = bars, empty = bars + 128;
    const int tid = threadIdx.x, warp = tid >> 5, lane = tid & 31, wg = tid >> 7;
    const uint32_t rank = cluster_rank();
    const int cl = blockIdx.x >> 1;
    const int m0 = ((cl & 7) * 2 + rank) * 128;
    const int ng = cl >> 3;
    STAMP(blockIdx.x == 10 && tid == 0, 0);
    if (tid == 0) {
        for (int i = 0; i < G1_NS; i++) { mbar_init(full + 8 * i, 1); mbar_init(empty + 8 * i, 16); }
        fence_barrier_init();
        for (int it = 0; it < 8; it++) {
            mbar_expect_tx(full + 8 * it, 16384);
            tma_load_2d(sb + it * 16384, &tm_c, it * 64, m0, full + 8 * it);
        }
    }
    __syncthreads();
    cluster_sync_all();
    pdl_launch();
    if (wg == 2) {
        reg_dec<40>();
        if (tid == 256) {
            const CUtensorMap* tw = ng < 4 ? &tm_wk : &tm_wv;
            const int n0 = (ng & 3) * 1024 + rank * 64;
            int st = 8; uint32_t ph = 1;
            for (int it = 0; it < 64; it++) {
                mbar_wait(empty + 8 * st, ph);
                mbar_expect_tx(full + 8 * st, 16384);
                tma_load_2d_mc(sb + st * 16384 + rank * 8192, tw, n0 + (it >> 3) * 128, (it & 7) * 64, full + 8 * st, 3);
                if (it < 2) {
                    for (int j = 3 + it * 8 + (cl & 7); j < 19; j += 16) tma_prefetch_2d(tw, n0 + (j >> 3) * 128, (j & 7) * 64);
                }
                if (it == 24) bulk_prefetch(px + blockIdx.x * 8192, 16384);
                if (it == 32) bulk_prefetch(pwq + blockIdx.x * 16384, 32768);
                if (++st == G1_NS) { st = 0; ph ^= 1; }
            }
        }
        __syncwarp();
    } else {
        reg_inc<232>();
        uint32_t af[128];
        float acc[64];
        const int wq = warp & 3;
        {
            const int row = wg * 64 + wq * 16 + (lane & 15);
#pragma unroll
            for (int kc = 0; kc < 8; kc++) {
                mbar_wait(full + 8 * kc, 0);
#pragma unroll
                for (int k = 0; k < 4; k++) {
                    const uint32_t a = sb + kc * 16384 + row * 128 + (((2 * k + (lane >> 4)) ^ (row & 7)) << 4);
                    uint32_t* f = af + kc * 16 + k * 4;
                    asm volatile("ldmatrix.sync.aligned.m8n8.x4.shared.b16 {%0,%1,%2,%3}, [%4];"
                                 : "=r"(f[0]), "=r"(f[1]), "=r"(f[2]), "=r"(f[3]) : "r"(a) : "memory");
                }
                __syncwarp();
                if (lane < 2) mbar_arrive_cluster(empty + 8 * kc, lane);
            }
        }
        const uint32_t stg = sC + wg * 16384;
        int st = 8, pst = 0; uint32_t ph = 0;
        if (wg == 1) named_sync(3, 256);
#pragma unroll 1
        for (int t = 0; t < 8; t++) {
#pragma unroll
            for (int kc = 0; kc < 8; kc++) {
                mbar_wait(full + 8 * st, ph);
                STAMP(blockIdx.x == 10 && (tid & 127) == 0, 1 + wg * 96 + t * 12 + kc);
                wg_fence();
                const uint64_t db = desc_mnmajor(sb + st * 16384, 8192);
#pragma unroll
                for (int k = 0; k < 4; k++) wgmma_rs128<1>(acc, af + kc * 16 + k * 4, db + k * 128, (kc | k) != 0);
                wg_commit();
                if (kc == 3 && t == 0 && wg == 0) named_arrive(3, 256);
                if (kc > 0) {
                    wg_wait<1>();
                    if (lane < 2) mbar_arrive_cluster(empty + 8 * pst, lane);
                }
                pst = st;
                if (++st == G1_NS) { st = 0; ph ^= 1; }
            }
            if ((tid & 127) == 0) bulk_wait_read<0>();
            named_sync(1 + wg, 128);
            wg_wait<0>();
            STAMP(blockIdx.x == 10 && (tid & 127) == 0, 9 + wg * 96 + t * 12);
            if (lane < 2) mbar_arrive_cluster(empty + 8 * pst, lane);
            store_slab64(stg, wq * 16, acc, 1.f, 1.f, lane);
            store_slab64(stg + 8192, wq * 16, acc + 32, 1.f, 1.f, lane);
            fence_proxy_async();
            named_sync(1 + wg, 128);
            if ((tid & 127) == 0) {
                tma_store_2d(&tm_kv_st, stg, ng * 1024 + t * 128, m0 + wg * 64);
                tma_store_2d(&tm_kv_st, stg + 8192, ng * 1024 + t * 128 + 64, m0 + wg * 64);
                bulk_commit();
            }
            STAMP(blockIdx.x == 10 && (tid & 127) == 0, 10 + wg * 96 + t * 12);
        }
        if ((tid & 127) == 0) bulk_wait<0>();
        __syncwarp();
    }
    asm volatile("barrier.cluster.arrive.relaxed.aligned;\nbarrier.cluster.wait.aligned;" ::: "memory");
}
constexpr int AT_NS = 6;
constexpr int AT_SMEM = AT_NS * 32768 + 32768 + 256 + 1024;
constexpr int AT_ITEMS = 512;

DEVI uint32_t hmax2(uint32_t a, uint32_t b) { uint32_t r; asm("max.bf16x2 %0, %1, %2;" : "=r"(r) : "r"(a), "r"(b)); return r; }
DEVI uint32_t hmul2(uint32_t a, uint32_t b) { uint32_t r; asm("mul.rn.bf16x2 %0, %1, %2;" : "=r"(r) : "r"(a), "r"(b)); return r; }
DEVI uint32_t hfma2(uint32_t a, uint32_t b, uint32_t c) { uint32_t r; asm("fma.rn.bf16x2 %0, %1, %2, %3;" : "=r"(r) : "r"(a), "r"(b), "r"(c)); return r; }
DEVI float blo(uint32_t v) { return __uint_as_float(v << 16); }
DEVI float bhi(uint32_t v) { return __uint_as_float(v & 0xffff0000u); }

template <bool FIRST>
DEVI void softmax_tile(float* s, float& m0, float& m1, float& l0, float& l1, float& al0, float& al1) {
    const uint32_t HI = 0x3DB53DB5u;
    const uint32_t LO = 0x371E371Eu;
    const float L2E = 1.4426950408889634f;
    uint32_t x0 = 0xFF80FF80u, x1 = 0xFF80FF80u;
#pragma unroll
    for (int j = 0; j < 16; j++) {
        uint32_t a = pack_bf16(s[4 * j], s[4 * j + 1]), b = pack_bf16(s[4 * j + 2], s[4 * j + 3]);
        a = hfma2(a, HI, hmul2(a, LO));
        b = hfma2(b, HI, hmul2(b, LO));
        s[4 * j] = __uint_as_float(a); s[4 * j + 2] = __uint_as_float(b);
        x0 = hmax2(x0, a); x1 = hmax2(x1, b);
    }
    uint32_t x = hmax2(__byte_perm(x0, x1, 0x5410), __byte_perm(x0, x1, 0x7632));
    x = hmax2(x, __shfl_xor_sync(~0u, x, 1));
    x = hmax2(x, __shfl_xor_sync(~0u, x, 2));
    float n0 = blo(x), n1 = bhi(x);
    if (!FIRST) {
        n0 = fmaxf(n0, m0); n1 = fmaxf(n1, m1);
        al0 = ex2((m0 - n0) * L2E); al1 = ex2((m1 - n1) * L2E);
    }
    m0 = n0; m1 = n1;
    const float c0 = -n0 * L2E, c1 = -n1 * L2E;
    float s0 = 0.f, s1 = 0.f;
#pragma unroll
    for (int j = 0; j < 16; j++) {
        uint32_t a = __float_as_uint(s[4 * j]), b = __float_as_uint(s[4 * j + 2]);
        float e0 = ex2(fmaf(blo(a), L2E, c0)), e1 = ex2(fmaf(bhi(a), L2E, c0));
        float e2 = ex2(fmaf(blo(b), L2E, c1)), e3 = ex2(fmaf(bhi(b), L2E, c1));
        s0 += e0 + e1; s1 += e2 + e3;
        s[4 * j] = e0; s[4 * j + 1] = e1; s[4 * j + 2] = e2; s[4 * j + 3] = e3;
    }
    if (FIRST) { l0 = s0; l1 = s1; }
    else { l0 = fmaf(l0, al0, s0); l1 = fmaf(l1, al1, s1); }
}

struct Ring {
    int st; uint32_t ph;
    DEVI void next() { if (++st == AT_NS) { st = 0; ph ^= 1; } }
};

__global__ void __launch_bounds__(384, 1)
attn_kernel(const __grid_constant__ CUtensorMap tm_x, const __grid_constant__ CUtensorMap tm_wq,
            const __grid_constant__ CUtensorMap tm_kv, const __grid_constant__ CUtensorMap tm_ctx_st,
            const bf16* __restrict__ pu, const bf16* __restrict__ pwo) {
    extern __shared__ uint8_t smem_raw[];
    const uint32_t sb = (smem_u32(smem_raw) + 1023) & ~1023u;
    const uint32_t sO = sb + AT_NS * 32768, bars = sO + 32768;
    const uint32_t full = bars, empty = bars + 64;
    volatile int* slots = reinterpret_cast<volatile int*>(smem_raw + (bars + 128 - smem_u32(smem_raw)));
    const int tid = threadIdx.x, warp = tid >> 5, lane = tid & 31, wg = tid >> 7;
    if (tid == 0) {
        for (int i = 0; i < AT_NS; i++) { mbar_init(full + 8 * i, 1); mbar_init(empty + 8 * i, 8); }
        fence_barrier_init();
    }
    __syncthreads();
    if (wg == 2) {
        reg_dec<24>();
        if (warp == 8 && lane == 0) {
            Ring r{0, 1};
            int n = 0;
            while (true) {
                int idx = (int)atomicInc(&g_sched, AT_ITEMS + gridDim.x - 1);
                if (idx >= AT_ITEMS - 128 && idx < AT_ITEMS) {
                    bulk_prefetch(pu + (idx - (AT_ITEMS - 128)) * 8192, 16384);
                    bulk_prefetch(pwo + (idx - (AT_ITEMS - 128)) * 16384, 32768);
                }
                mbar_wait(empty + 8 * r.st, r.ph);
                if (idx >= AT_ITEMS) {
                    slots[n & 3] = -1;
                    mbar_arrive(full + 8 * r.st);
                    break;
                }
                slots[n & 3] = idx;
                const int qi = 15 - (idx >> 5), h = idx & 31;
                for (int kc = 0; kc < 8; kc++) {
                    if (kc) mbar_wait(empty + 8 * r.st, r.ph);
                    const uint32_t fb = full + 8 * r.st, dst = sb + r.st * 32768;
                    mbar_expect_tx(fb, 32768);
                    tma_load_2d(dst, &tm_x, kc * 64, qi * 128, fb);
                    tma_load_2d(dst + 16384, &tm_wq, h * 128, kc * 64, fb);
                    tma_load_2d(dst + 24576, &tm_wq, h * 128 + 64, kc * 64, fb);
                    r.next();
                }
                if (n == 0) { pdl_wait(); pdl_launch(); }
                for (int j = qi; j >= -1; j--) {
#pragma unroll
                    for (int v = 0; v < 2; v++) {
                        const int jj = j + v;
                        if (jj < 0 || jj > qi || (v == 0 && j < 0)) continue;
                        mbar_wait(empty + 8 * r.st, r.ph);
                        const uint32_t fb = full + 8 * r.st, dst = sb + r.st * 32768;
                        mbar_expect_tx(fb, 32768);
                        tma_load_2d(dst, &tm_kv, v * HDALL + h * 128, jj * 128, fb);
                        tma_load_2d(dst + 16384, &tm_kv, v * HDALL + h * 128 + 64, jj * 128, fb);
                        r.next();
                    }
                }
                n++;
            }
            if (n == 0) { pdl_wait(); pdl_launch(); }
        }
    } else {
        reg_inc<240>();
        Ring r{0, 0};
        float o[64], s[64];
        uint32_t qf[32], pa[32];
        const int g = lane >> 2, t = lane & 3, wq = warp & 3;
        const uint32_t stg = sO + wg * 16384;
        if (wg == 1) named_arrive(3, 256);
        for (int n = 0;; n++) {
            mbar_wait(full + 8 * r.st, r.ph);
            const int idx = slots[n & 3];
            if (idx < 0) break;
            const int qi = 15 - (idx >> 5), h = idx & 31;
#pragma unroll 1
            for (int kc = 0; kc < 8; kc++) {
                if (kc) mbar_wait(full + 8 * r.st, r.ph);
                wg_fence();
                const uint32_t base = sb + r.st * 32768;
                const uint64_t da = desc_kmajor(base + wg * 8192), db = desc_mnmajor(base + 16384, 8192);
#pragma unroll
                for (int k = 0; k < 4; k++) wgmma_ss128<1>(s, da + k * 2, db + k * 128, (kc | k) != 0);
                wg_commit();
                if (kc) {
                    wg_wait<1>();
                    if (lane == 0) mbar_arrive(empty + 8 * (r.st == 0 ? AT_NS - 1 : r.st - 1));
                }
                r.next();
            }
            wg_wait<0>();
            if (lane == 0) mbar_arrive(empty + 8 * (r.st == 0 ? AT_NS - 1 : r.st - 1));
#pragma unroll
            for (int i = 0; i < 32; i++) qf[i] = pack_bf16(s[2 * i], s[2 * i + 1]);
            float m0, m1, l0, l1, al0, al1;
            auto issue_qk = [&]() {
                mbar_wait(full + 8 * r.st, r.ph);
                wg_fence();
                const uint64_t db = desc_kmajor(sb + r.st * 32768);
#pragma unroll
                for (int k = 0; k < 8; k++) wgmma_rs128<0>(s, qf + 4 * k, db + (k >> 2) * 1024 + (k & 3) * 2, k != 0);
                wg_commit();
            };
            auto issue_pv = [&](const uint32_t* p, int st, uint32_t ph, int acc) {
                mbar_wait(full + 8 * st, ph);
                wg_fence();
                const uint64_t db = desc_mnmajor(sb + st * 32768, 16384);
#pragma unroll
                for (int k = 0; k < 8; k++) wgmma_rs128<1>(o, p + 4 * k, db + k * 128, acc | k);
                wg_commit();
            };
            issue_qk();
            wg_wait<0>();
            if (lane == 0) mbar_arrive(empty + 8 * r.st);
            r.next();
            {
                const int row = wg * 64 + wq * 16 + g;
#pragma unroll
                for (int j = 0; j < 16; j++) {
                    const int c = 8 * j + 2 * t;
                    if (c > row) s[4 * j] = -INFINITY;
                    if (c + 1 > row) s[4 * j + 1] = -INFINITY;
                    if (c > row + 8) s[4 * j + 2] = -INFINITY;
                    if (c + 1 > row + 8) s[4 * j + 3] = -INFINITY;
                }
            }
            softmax_tile<true>(s, m0, m1, l0, l1, al0, al1);
#pragma unroll
            for (int i = 0; i < 32; i++) pa[i] = pack_bf16(s[2 * i], s[2 * i + 1]);
            int first = 0;
#pragma unroll 1
            for (int j = qi; j >= 1; j--) {
                named_sync(3 + wg, 256);
                issue_qk();
                const int kst = r.st;
                r.next();
                issue_pv(pa, r.st, r.ph, first);
                named_arrive(3 + (wg ^ 1), 256);
                wg_wait<1>();
                if (lane == 0) mbar_arrive(empty + 8 * kst);
                softmax_tile<false>(s, m0, m1, l0, l1, al0, al1);
                wg_wait<0>();
                if (lane == 0) mbar_arrive(empty + 8 * r.st);
                r.next();
#pragma unroll
                for (int i = 0; i < 32; i++) pa[i] = pack_bf16(s[2 * i], s[2 * i + 1]);
#pragma unroll
                for (int i = 0; i < 16; i++) {
                    o[4 * i] *= al0; o[4 * i + 1] *= al0; o[4 * i + 2] *= al1; o[4 * i + 3] *= al1;
                }
                first = 1;
            }
            issue_pv(pa, r.st, r.ph, first);
            l0 += __shfl_xor_sync(~0u, l0, 1); l0 += __shfl_xor_sync(~0u, l0, 2);
            l1 += __shfl_xor_sync(~0u, l1, 1); l1 += __shfl_xor_sync(~0u, l1, 2);
            const float i0 = 1.f / l0, i1 = 1.f / l1;
            if ((tid & 127) == 0) bulk_wait_read<0>();
            named_sync(1 + wg, 128);
            wg_wait<0>();
            if (lane == 0) mbar_arrive(empty + 8 * r.st);
            r.next();
            store_slab64(stg, wq * 16, o, i0, i1, lane);
            store_slab64(stg + 8192, wq * 16, o + 32, i0, i1, lane);
            fence_proxy_async();
            named_sync(1 + wg, 128);
            if ((tid & 127) == 0) {
                tma_store_2d(&tm_ctx_st, stg, h * 128, qi * 128 + wg * 64);
                tma_store_2d(&tm_ctx_st, stg + 8192, h * 128 + 64, qi * 128 + wg * 64);
                bulk_commit();
            }
        }
        if ((tid & 127) == 0) bulk_wait<0>();
    }
}
constexpr int OP_NS = 4;
constexpr int OP_ULD = 41 * 16;
constexpr int OP_UCH = 8 * OP_ULD;
constexpr int OP_SMEM = OP_NS * 32768 + 32768 + 4 * WTAB * 4 + 4 * OP_UCH + 4 * 648 * 4 + 256 + 1024;

template <int N> DEVI void wgmma_conv(float* d, const uint32_t* a, uint64_t db);
template <> DEVI void wgmma_conv<32>(float* d, const uint32_t* a, uint64_t db) {
    asm volatile("wgmma.mma_async.sync.aligned.m64n32k16.f32.bf16.bf16 {%0,%1,%2,%3,%4,%5,%6,%7,%8,%9,%10,%11,%12,%13,%14,%15}, "
                 "{%16,%17,%18,%19}, %20, 1, 1, 1, 0;"
                 : ACC8(d, 0), ACC8(d, 8) : "r"(a[0]), "r"(a[1]), "r"(a[2]), "r"(a[3]), "l"(db));
}
template <> DEVI void wgmma_conv<24>(float* d, const uint32_t* a, uint64_t db) {
    asm volatile("wgmma.mma_async.sync.aligned.m64n24k16.f32.bf16.bf16 {%0,%1,%2,%3,%4,%5,%6,%7,%8,%9,%10,%11}, "
                 "{%12,%13,%14,%15}, %16, 1, 1, 1, 0;"
                 : ACC8(d, 0), "+f"(d[8]), "+f"(d[9]), "+f"(d[10]), "+f"(d[11]) : "r"(a[0]), "r"(a[1]), "r"(a[2]), "r"(a[3]), "l"(db));
}
template <> DEVI void wgmma_conv<16>(float* d, const uint32_t* a, uint64_t db) {
    asm volatile("wgmma.mma_async.sync.aligned.m64n16k16.f32.bf16.bf16 {%0,%1,%2,%3,%4,%5,%6,%7}, "
                 "{%8,%9,%10,%11}, %12, 1, 1, 1, 0;"
                 : ACC8(d, 0) : "r"(a[0]), "r"(a[1]), "r"(a[2]), "r"(a[3]), "l"(db));
}
template <> DEVI void wgmma_conv<8>(float* d, const uint32_t* a, uint64_t db) {
    asm volatile("wgmma.mma_async.sync.aligned.m64n8k16.f32.bf16.bf16 {%0,%1,%2,%3}, "
                 "{%4,%5,%6,%7}, %8, 1, 1, 1, 0;"
                 : "+f"(d[0]), "+f"(d[1]), "+f"(d[2]), "+f"(d[3]) : "r"(a[0]), "r"(a[1]), "r"(a[2]), "r"(a[3]), "l"(db));
}
DEVI uint32_t lds32(uint32_t a) { uint32_t v; asm volatile("ld.shared.b32 %0, [%1];" : "=r"(v) : "r"(a)); return v; }
DEVI uint32_t lds16(uint32_t a) { uint16_t v; asm volatile("ld.shared.b16 %0, [%1];" : "=h"(v) : "r"(a)); return v; }

template <int J> DEVI void conv_pair(float* acc, uint32_t* f, uint32_t wa, uint64_t du, int c) {
#pragma unroll
    for (int i = 0; i < 8; i++) {
        f[4 * i] = lds32(wa + i * 64); f[4 * i + 1] = lds32(wa + i * 64 + 32);
        f[4 * i + 2] = lds32(wa + i * 64 - 32); f[4 * i + 3] = lds32(wa + i * 64);
    }
    wg_fence();
#pragma unroll
    for (int i = 0; i < 8; i++) {
        const int kk = 3 - (i & 3);
        const uint64_t db = du + (uint64_t)(kk * 2 * (OP_ULD / 16) + (i >> 2) + c);
        wgmma_conv<32 - 8 * J>(acc, f + 4 * i, db);
    }
    wg_commit();
}
template <int J> DEVI void conv_group(float* acc, uint32_t wa, uint64_t du) {
    uint32_t fa[32], fb[32];
#pragma unroll
    for (int h = 0; h < 2; h++) {
        const int c = 8 * J + 4 * h;
        conv_pair<J>(acc, fa, wa + c * 256, du, c);
        wg_wait<1>();
        conv_pair<J>(acc, fb, wa + (c + 2) * 256, du, c + 2);
        wg_wait<1>();
    }
    wg_wait<0>();
}

__global__ void __cluster_dims__(2, 1, 1) __launch_bounds__(512, 1)
outproj_kernel(const __grid_constant__ CUtensorMap tm_ctx, const __grid_constant__ CUtensorMap tm_wo,
               const __grid_constant__ CUtensorMap tm_out, SsmParams sp, bf16* __restrict__ out) {
    extern __shared__ uint8_t smem_raw[];
    const uint32_t sb = (smem_u32(smem_raw) + 1023) & ~1023u;
    const uint32_t sX = sb + OP_NS * 32768, sW = sX + 32768, sU = sW + 4 * WTAB * 4, sK = sU + 4 * OP_UCH, bars = sK + 4 * 648 * 4;
    const uint32_t full = bars, empty = bars + 64, xfull = bars + 128, wfull = bars + 136;
    const int tid = threadIdx.x, warp = tid >> 5, lane = tid & 31, wg = tid >> 7;
    const uint32_t rank = cluster_rank();
    const uint32_t kr = rank;
    const int cl = blockIdx.x >> 1;
    const int m0 = (cl >> 2) * 128, n0 = (cl & 3) * 128, k0 = kr * 2048;
    if (tid == 0) {
        for (int i = 0; i < OP_NS; i++) { mbar_init(full + 8 * i, 1); mbar_init(empty + 8 * i, 8); }
        mbar_init(xfull, 1);
        mbar_init(wfull, 1);
        fence_barrier_init();
    }
    __syncthreads();
    cluster_sync_all();
    if (wg == 3) {
        reg_dec<40>();
        if (tid == 384) {
            mbar_expect_tx(xfull, 32768);
            for (int it = 0; it < OP_NS; it++) {
                const uint32_t dst = sb + it * 32768, fb = full + 8 * it;
                mbar_expect_tx(fb, 32768);
                tma_load_2d(dst + 16384, &tm_wo, n0, k0 + it * 64, fb);
                tma_load_2d(dst + 24576, &tm_wo, n0 + 64, k0 + it * 64, fb);
            }
            pdl_wait();
            for (int it = 0; it < 32; it++) {
                const int st = it & (OP_NS - 1);
                const uint32_t dst = sb + st * 32768, fb = full + 8 * st;
                if (it >= OP_NS) {
                    mbar_wait(empty + 8 * st, ((it / OP_NS) & 1) ^ 1);
                    mbar_expect_tx(fb, 32768);
                    tma_load_2d(dst + 16384, &tm_wo, n0, k0 + it * 64, fb);
                    tma_load_2d(dst + 24576, &tm_wo, n0 + 64, k0 + it * 64, fb);
                }
                tma_load_2d(dst, &tm_ctx, k0 + it * 64, m0, fb);
                tma_load_2d(dst + 8192, &tm_ctx, k0 + it * 64, m0 + 64, fb);
            }
        }
        __syncwarp();
    } else if (wg == 2) {
        reg_inc<208>();
        const int ct = tid & 127, wq = warp & 3, g = lane >> 2, t = lane & 3;
        const int d0 = blockIdx.x * 4;
        uint2 v[2][8];
#pragma unroll
        for (int h = 0; h < 2; h++)
#pragma unroll
            for (int i = 0; i < 8; i++)
                v[h][i] = __ldg(reinterpret_cast<const uint2*>(sp.u + (size_t)((ct + 128 * h) * 8 + i) * SSM_D + d0));
        for (int i = ct; i < 4 * 8 * 8; i += 128) {
            const uint32_t a = sU + (i >> 3) * OP_ULD + (32 + (i & 7)) * 16;
            asm volatile("st.shared.v4.b32 [%0], {%1,%1,%1,%1};" ::"r"(a), "r"(0) : "memory");
        }
#pragma unroll
        for (int h = 0; h < 2; h++) {
            const int q = ct + 128 * h;
            const uint32_t a = sU + (q & 7) * OP_ULD + (31 - (q >> 3)) * 16;
#pragma unroll
            for (int c = 0; c < 4; c++) {
                uint32_t w[4];
#pragma unroll
                for (int i = 0; i < 4; i++) {
                    const uint32_t lo = (c & 2) ? v[h][2 * i].y : v[h][2 * i].x, hi = (c & 2) ? v[h][2 * i + 1].y : v[h][2 * i + 1].x;
                    w[i] = __byte_perm(lo, hi, (c & 1) ? 0x7632 : 0x5410);
                }
                asm volatile("st.shared.v4.b32 [%0], {%1,%2,%3,%4};" ::"r"(a + c * OP_UCH), "r"(w[0]), "r"(w[1]), "r"(w[2]), "r"(w[3]) : "memory");
            }
        }
        ssm_kgen_warp(sp, d0 + wq, lane, reinterpret_cast<float*>(smem_raw + (sK - smem_u32(smem_raw))) + wq * 648);
        named_sync(3, 128);
        for (int qd = ct; qd < WTAB / 4; qd += 128) {
            const int o = qd * 4 - 64;
            uint32_t ka[5];
#pragma unroll
            for (int e = 0; e < 5; e++) ka[e] = sK + 4 * kp_index(max(o - 1 + e, 0));
#pragma unroll
            for (int c = 0; c < 4; c++) {
                float k[5];
#pragma unroll
                for (int e = 0; e < 5; e++) k[e] = o - 1 + e < 0 ? 0.f : __uint_as_float(lds32(ka[e] + c * 648 * 4));
                asm volatile("st.shared.v4.b32 [%0], {%1,%2,%3,%4};" ::"r"(sW + (c * WTAB + qd * 4) * 4), "r"(pack_bf16(k[1], k[0])),
                             "r"(pack_bf16(k[2], k[1])), "r"(pack_bf16(k[3], k[2])), "r"(pack_bf16(k[4], k[3])) : "memory");
            }
        }
        const uint2 dsk = __ldg(reinterpret_cast<const uint2*>(sp.dskip + d0));
        fence_proxy_async();
        named_sync(3, 128);
        uint32_t res[16][2];
#pragma unroll
        for (int c = 0; c < 4; c++) {
            float acc[16];
#pragma unroll
            for (int i = 0; i < 16; i++) acc[i] = 0.f;
            const uint32_t wa = sW + (c * WTAB + 64 + 16 * (wq - 3) + g - 2 * t) * 4;
            const uint64_t du = make_desc(sU + c * OP_UCH, OP_ULD, 128, 0);
            conv_group<0>(acc, wa, du);
            conv_group<1>(acc, wa, du);
            conv_group<2>(acc, wa, du);
            conv_group<3>(acc, wa, du);
            const uint32_t dw = (c & 2) ? dsk.y : dsk.x;
            const float D = (c & 1) ? bhi(dw) : blo(dw);
#pragma unroll
            for (int i = 0; i < 16; i++) {
                const int n = 8 * (i >> 2) + 2 * t + (i & 1), j = 2 * wq + ((i >> 1) & 1);
                const float u = __uint_as_float(lds16(sU + c * OP_UCH + j * OP_ULD + n * 16 + g * 2) << 16);
                const uint32_t o = __bfloat16_as_ushort(__float2bfloat16_rn(rbf(acc[i]) + rbf(u * D)));
                if (c & 1) res[i][c >> 1] |= o << 16; else res[i][c >> 1] = o;
            }
        }
#pragma unroll
        for (int i = 0; i < 16; i++) {
            const int a = 31 - (8 * (i >> 2) + 2 * t + (i & 1)), b = 16 * wq + g + 8 * ((i >> 1) & 1);
            *reinterpret_cast<uint2*>(out + (size_t)(64 * a + b) * 1024 + 512 + d0) = make_uint2(res[i][0], res[i][1]);
        }
    } else {
        float acc[64];
#pragma unroll 1
        for (int it = 0; it < 32; it++) {
            const int st = it & (OP_NS - 1);
            mbar_wait(full + 8 * st, (it / OP_NS) & 1);
            wg_fence();
            const uint32_t base = sb + st * 32768;
            const uint64_t da = desc_kmajor(base + wg * 8192), db = desc_mnmajor(base + 16384, 8192);
#pragma unroll
            for (int k = 0; k < 4; k++) wgmma_ss128<1>(acc, da + k * 2, db + k * 128, (it | k) != 0);
            wg_commit();
            if (it > 0 && it + OP_NS - 1 < 32) {
                wg_wait<1>();
                if (lane == 0) mbar_arrive(empty + 8 * ((it - 1) & (OP_NS - 1)));
            }
        }
        wg_wait<0>();
        uint32_t peer, pbar;
        asm volatile("mapa.shared::cluster.u32 %0, %1, %2;" : "=r"(peer) : "r"(sX + tid * 16), "r"(rank ^ 1));
        asm volatile("mapa.shared::cluster.u32 %0, %1, %2;" : "=r"(pbar) : "r"(xfull), "r"(rank ^ 1));
#pragma unroll
        for (int i = 0; i < 8; i++) {
            const float* s = acc + 4 * i;
            const float a = kr ? s[0] : s[32], b = kr ? s[1] : s[33], c = kr ? s[2] : s[34], d = kr ? s[3] : s[35];
            asm volatile("st.async.weak.shared::cluster.mbarrier::complete_tx::bytes.v4.f32 [%0], {%1,%2,%3,%4}, [%5];"
                         ::"r"(peer + i * 4096), "f"(a), "f"(b), "f"(c), "f"(d), "r"(pbar) : "memory");
        }
        mbar_wait(xfull, 0);
        float r[32];
#pragma unroll
        for (int i = 0; i < 8; i++) {
            float a, b, c, d;
            asm volatile("ld.shared.v4.f32 {%0,%1,%2,%3}, [%4];" : "=f"(a), "=f"(b), "=f"(c), "=f"(d) : "r"(sX + tid * 16 + i * 4096));
            const float* s = acc + 4 * i;
            r[4 * i] = a + (kr ? s[32] : s[0]); r[4 * i + 1] = b + (kr ? s[33] : s[1]);
            r[4 * i + 2] = c + (kr ? s[34] : s[2]); r[4 * i + 3] = d + (kr ? s[35] : s[3]);
        }
        const uint32_t stg = sb + wg * 8192;
        store_slab64(stg, (warp & 3) * 16, r, 1.f, 1.f, lane);
        fence_proxy_async();
        named_sync(1 + wg, 128);
        if ((tid & 127) == 0) {
            tma_store_2d(&tm_out, stg, n0 + kr * 64, m0 + wg * 64);
            bulk_commit();
            bulk_wait<0>();
        }
    }
}

typedef CUresult (*EncodeFn)(CUtensorMap*, CUtensorMapDataType, cuuint32_t, void*, const cuuint64_t*, const cuuint64_t*,
                             const cuuint32_t*, const cuuint32_t*, CUtensorMapInterleave, CUtensorMapSwizzle,
                             CUtensorMapL2promotion, CUtensorMapFloatOOBfill);

static void make_map(EncodeFn fn, CUtensorMap* m, const void* p, uint64_t cols, uint64_t rows, uint32_t box_rows) {
    cuuint64_t dims[2] = {cols, rows};
    cuuint64_t strides[1] = {cols * 2};
    cuuint32_t box[2] = {64, box_rows};
    cuuint32_t es[2] = {1, 1};
    fn(m, CU_TENSOR_MAP_DATA_TYPE_BFLOAT16, 2, const_cast<void*>(p), dims, strides, box, es, CU_TENSOR_MAP_INTERLEAVE_NONE,
       CU_TENSOR_MAP_SWIZZLE_128B, CU_TENSOR_MAP_L2_PROMOTION_L2_256B, CU_TENSOR_MAP_FLOAT_OOB_FILL_NONE);
}

extern "C" void kernel_launch(void* const* d_in, const int* in_sizes, int n_in, void* d_out, int out_size) {
    void* fp = nullptr;
    cudaDriverEntryPointQueryResult qr;
    cudaGetDriverEntryPoint("cuTensorMapEncodeTiled", &fp, cudaEnableDefault, &qr);
    EncodeFn fn = (EncodeFn)fp;
    void *p_kv, *p_ctx;
    cudaGetSymbolAddress(&p_kv, g_kv);
    cudaGetSymbolAddress(&p_ctx, g_ctx);
    CUtensorMap tm_kv_st, tm_x, tm_c, tm_wq, tm_wk, tm_wv, tm_wo, tm_kv, tm_ctx, tm_out;
    make_map(fn, &tm_x, d_in[0], DM, SEQ, 128);
    make_map(fn, &tm_c, d_in[1], DM, SEQ, 128);
    make_map(fn, &tm_wq, d_in[2], HDALL, DM, 64);
    make_map(fn, &tm_wk, d_in[3], HDALL, DM, 64);
    make_map(fn, &tm_wv, d_in[4], HDALL, DM, 64);
    make_map(fn, &tm_wo, d_in[5], DM, HDALL, 64);
    make_map(fn, &tm_kv, p_kv, 2 * HDALL, SEQ, 128);
    make_map(fn, &tm_kv_st, p_kv, 2 * HDALL, SEQ, 64);
    make_map(fn, &tm_ctx, p_ctx, HDALL, SEQ, 64);
    make_map(fn, &tm_out, d_out, 1024, SEQ, 64);
    SsmParams sp;
    sp.u = (const bf16*)d_in[6]; sp.lar = (const bf16*)d_in[7]; sp.aim = (const bf16*)d_in[8];
    sp.cre = (const bf16*)d_in[9]; sp.cim = (const bf16*)d_in[10]; sp.ldt = (const bf16*)d_in[11]; sp.dskip = (const bf16*)d_in[12];
    cudaFuncSetAttribute(gemm_kv_kernel, cudaFuncAttributeMaxDynamicSharedMemorySize, G1_SMEM);
    cudaFuncSetAttribute(attn_kernel, cudaFuncAttributeMaxDynamicSharedMemorySize, AT_SMEM);
    cudaFuncSetAttribute(outproj_kernel, cudaFuncAttributeMaxDynamicSharedMemorySize, OP_SMEM);
    cudaStream_t st = cudaStreamPerThread;
    gemm_kv_kernel<<<128, G1_THREADS, G1_SMEM, st>>>(tm_c, tm_wk, tm_wv, tm_kv_st, (const bf16*)d_in[0], (const bf16*)d_in[2]);
    cudaLaunchAttribute at[1];
    at[0].id = cudaLaunchAttributeProgrammaticStreamSerialization;
    at[0].val.programmaticStreamSerializationAllowed = 1;
    cudaLaunchConfig_t cfg = {};
    cfg.stream = st; cfg.attrs = at; cfg.numAttrs = 1;
    cfg.gridDim = dim3(132); cfg.blockDim = dim3(384); cfg.dynamicSmemBytes = AT_SMEM;
    cudaLaunchKernelEx(&cfg, attn_kernel, tm_x, tm_wq, tm_kv, tm_ctx, sp.u, (const bf16*)d_in[5]);
    cfg.gridDim = dim3(128); cfg.blockDim = dim3(512); cfg.dynamicSmemBytes = OP_SMEM;
    cudaLaunchKernelEx(&cfg, outproj_kernel, tm_ctx, tm_wo, tm_out, sp, (bf16*)d_out);
}
```

```cpp
#include <cuda_runtime.h>
#include <cuda_bf16.h>
#include <cuda.h>
#include <stdint.h>

typedef __nv_bfloat16 bf16;

#define DEVI __device__ __forceinline__

constexpr int SEQ = 2048, DM = 512, NH = 32, HD = 128, HDALL = NH * HD;
constexpr int SSM_D = 512, SSM_N = 128;
constexpr int WTAB = 2112;

__device__ bf16 g_kv[(size_t)SEQ * 2 * HDALL];
__device__ bf16 g_ctx[(size_t)SEQ * HDALL];
__device__ unsigned int g_sched;

#define STAMP(cond, i)
DEVI uint32_t smem_u32(const void* p) { return (uint32_t)__cvta_generic_to_shared(p); }
DEVI void mbar_init(uint32_t a, uint32_t cnt) { asm volatile("mbarrier.init.shared::cta.b64 [%0], %1;" ::"r"(a), "r"(cnt)); }
DEVI void mbar_expect_tx(uint32_t a, uint32_t bytes) {
    asm volatile("mbarrier.arrive.expect_tx.shared::cta.b64 _, [%0], %1;" ::"r"(a), "r"(bytes) : "memory");
}
DEVI void mbar_arrive(uint32_t a) { asm volatile("mbarrier.arrive.shared::cta.b64 _, [%0];" ::"r"(a) : "memory"); }
DEVI void mbar_arrive_cluster(uint32_t a, uint32_t cta) {
    asm volatile("{\n.reg .b32 r;\nmapa.shared::cluster.u32 r, %0, %1;\n"
                 "mbarrier.arrive.shared::cluster.b64 _, [r];\n}" ::"r"(a), "r"(cta) : "memory");
}
#define MBAR_WAIT_ASM(OP)                                                                              \
    asm volatile("{\n.reg .pred p, q;\n.reg .u32 t0, t1;\n" OP " p, [%0], %1;\n@p bra D_%=;\n"         \
                 "mov.u32 t0, %%globaltimer_lo;\nW_%=:\n" OP " p, [%0], %1;\n"                         \
                 "mov.u32 t1, %%globaltimer_lo;\nsub.u32 t1, t1, t0;\n"                                \
                 "setp.gt.or.u32 q, t1, 4000000, p;\n@!q bra W_%=;\nD_%=:\n}" ::"r"(a), "r"(parity) : "memory")
DEVI void mbar_wait(uint32_t a, uint32_t parity) { MBAR_WAIT_ASM("mbarrier.try_wait.parity.shared::cta.b64"); }
DEVI void mbar_wait_cluster(uint32_t a, uint32_t parity) { MBAR_WAIT_ASM("mbarrier.try_wait.parity.acquire.cluster.shared::cta.b64"); }
DEVI void fence_barrier_init() { asm volatile("fence.mbarrier_init.release.cluster;" ::: "memory"); }
DEVI void fence_proxy_async() { asm volatile("fence.proxy.async.shared::cta;" ::: "memory"); }
DEVI void cluster_sync_all() {
    asm volatile("barrier.cluster.arrive.release.aligned;\nbarrier.cluster.wait.acquire.aligned;" ::: "memory");
}
DEVI uint32_t cluster_rank() { uint32_t r; asm volatile("mov.u32 %0, %%cluster_ctarank;" : "=r"(r)); return r; }
DEVI void tma_load_2d(uint32_t dst, const CUtensorMap* m, int c0, int c1, uint32_t bar) {
    asm volatile("cp.async.bulk.tensor.2d.shared::cluster.global.mbarrier::complete_tx::bytes [%0], [%1, {%3, %4}], [%2];"
                 ::"r"(dst), "l"(m), "r"(bar), "r"(c0), "r"(c1) : "memory");
}
DEVI void tma_load_2d_mc(uint32_t dst, const CUtensorMap* m, int c0, int c1, uint32_t bar, uint16_t mask) {
    asm volatile("cp.async.bulk.tensor.2d.shared::cluster.global.mbarrier::complete_tx::bytes.multicast::cluster [%0], [%1, {%3, %4}], [%2], %5;"
                 ::"r"(dst), "l"(m), "r"(bar), "r"(c0), "r"(c1), "h"(mask) : "memory");
}
DEVI void tma_prefetch_2d(const CUtensorMap* m, int c0, int c1) {
    asm volatile("cp.async.bulk.prefetch.tensor.2d.L2.global [%0, {%1, %2}];" ::"l"(m), "r"(c0), "r"(c1) : "memory");
}
DEVI void tma_store_2d(const CUtensorMap* m, uint32_t src, int c0, int c1) {
    asm volatile("cp.async.bulk.tensor.2d.global.shared::cta.bulk_group [%0, {%2, %3}], [%1];"
                 ::"l"(m), "r"(src), "r"(c0), "r"(c1) : "memory");
}
DEVI void bulk_load(uint32_t dst, const void* src, uint32_t bytes, uint32_t bar) {
    asm volatile("cp.async.bulk.shared::cluster.global.mbarrier::complete_tx::bytes [%0], [%1], %2, [%3];"
                 ::"r"(dst), "l"(src), "r"(bytes), "r"(bar) : "memory");
}
DEVI void bulk_prefetch(const void* src, uint32_t bytes) {
    asm volatile("cp.async.bulk.prefetch.L2.global [%0], %1;" ::"l"(src), "r"(bytes) : "memory");
}
DEVI void bulk_commit() { asm volatile("cp.async.bulk.commit_group;" ::: "memory"); }
template <int N> DEVI void bulk_wait_read() { asm volatile("cp.async.bulk.wait_group.read %0;" ::"n"(N) : "memory"); }
template <int N> DEVI void bulk_wait() { asm volatile("cp.async.bulk.wait_group %0;" ::"n"(N) : "memory"); }
DEVI void prefetch_tmap(const CUtensorMap* m) { asm volatile("prefetch.tensormap [%0];" ::"l"(m) : "memory"); }
DEVI void named_sync(int id, int n) { asm volatile("bar.sync %0, %1;" ::"r"(id), "r"(n) : "memory"); }
DEVI void named_arrive(int id, int n) { asm volatile("bar.arrive %0, %1;" ::"r"(id), "r"(n) : "memory"); }
DEVI void pdl_wait() { asm volatile("griddepcontrol.wait;" ::: "memory"); }
DEVI void pdl_launch() { asm volatile("griddepcontrol.launch_dependents;" ::: "memory"); }
template <int R> DEVI void reg_inc() { asm volatile("setmaxnreg.inc.sync.aligned.u32 %0;" ::"n"(R)); }
template <int R> DEVI void reg_dec() { asm volatile("setmaxnreg.dec.sync.aligned.u32 %0;" ::"n"(R)); }

DEVI void wg_fence() { asm volatile("wgmma.fence.sync.aligned;" ::: "memory"); }
DEVI void wg_commit() { asm volatile("wgmma.commit_group.sync.aligned;" ::: "memory"); }
template <int N> DEVI void wg_wait() { asm volatile("wgmma.wait_group.sync.aligned %0;" ::"n"(N) : "memory"); }

DEVI uint64_t make_desc(uint32_t addr, uint32_t lbo, uint32_t sbo, uint32_t swz) {
    return (uint64_t)((addr & 0x3FFFF) >> 4) | ((uint64_t)(lbo >> 4) << 16) | ((uint64_t)(sbo >> 4) << 32) | ((uint64_t)swz << 62);
}
DEVI uint64_t desc_kmajor(uint32_t addr) { return make_desc(addr, 16, 1024, 1); }
DEVI uint64_t desc_mnmajor(uint32_t addr, uint32_t lbo) { return make_desc(addr, lbo, 1024, 1); }

#define ACC8(d, o) "+f"(d[o + 0]), "+f"(d[o + 1]), "+f"(d[o + 2]), "+f"(d[o + 3]), "+f"(d[o + 4]), "+f"(d[o + 5]), "+f"(d[o + 6]), "+f"(d[o + 7])
#define ACC64(d) ACC8(d, 0), ACC8(d, 8), ACC8(d, 16), ACC8(d, 24), ACC8(d, 32), ACC8(d, 40), ACC8(d, 48), ACC8(d, 56)
#define R64 "{%0,%1,%2,%3,%4,%5,%6,%7,%8,%9,%10,%11,%12,%13,%14,%15,%16,%17,%18,%19,%20,%21,%22,%23,%24,%25,%26,%27,%28,%29,%30,%31," \
            "%32,%33,%34,%35,%36,%37,%38,%39,%40,%41,%42,%43,%44,%45,%46,%47,%48,%49,%50,%51,%52,%53,%54,%55,%56,%57,%58,%59,%60,%61,%62,%63}"

template <int TB> DEVI void wgmma_ss128(float* d, uint64_t da, uint64_t db, int acc) {
    asm volatile("{\n.reg .pred p;\nsetp.ne.b32 p, %66, 0;\n"
                 "wgmma.mma_async.sync.aligned.m64n128k16.f32.bf16.bf16 " R64 ", %64, %65, p, 1, 1, 0, %67;\n}"
                 : ACC64(d) : "l"(da), "l"(db), "r"(acc), "n"(TB));
}
template <int TB> DEVI void wgmma_rs128(float* d, const uint32_t* a, uint64_t db, int acc) {
    asm volatile("{\n.reg .pred p;\nsetp.ne.b32 p, %69, 0;\n"
                 "wgmma.mma_async.sync.aligned.m64n128k16.f32.bf16.bf16 " R64 ", {%64,%65,%66,%67}, %68, p, 1, 1, %70;\n}"
                 : ACC64(d) : "r"(a[0]), "r"(a[1]), "r"(a[2]), "r"(a[3]), "l"(db), "r"(acc), "n"(TB));
}
DEVI uint32_t pack_bf16(float lo, float hi) {
    uint32_t r;
    asm("cvt.rn.bf16x2.f32 %0, %1, %2;" : "=r"(r) : "f"(hi), "f"(lo));
    return r;
}
DEVI void stmatrix_x4(uint32_t addr, uint32_t r0, uint32_t r1, uint32_t r2, uint32_t r3) {
    asm volatile("stmatrix.sync.aligned.m8n8.x4.shared.b16 [%0], {%1,%2,%3,%4};" ::"r"(addr), "r"(r0), "r"(r1), "r"(r2), "r"(r3) : "memory");
}
DEVI float ex2(float x) { float y; asm("ex2.approx.ftz.f32 %0, %1;" : "=f"(y) : "f"(x)); return y; }

DEVI void store_slab64(uint32_t base, int row0, const float* d, float s0, float s1, int lane) {
    int mi = lane >> 3, r = lane & 7;
    int row = row0 + (mi & 1) * 8 + r;
#pragma unroll
    for (int j = 0; j < 8; j += 2) {
        uint32_t r0 = pack_bf16(d[4 * j + 0] * s0, d[4 * j + 1] * s0);
        uint32_t r1 = pack_bf16(d[4 * j + 2] * s1, d[4 * j + 3] * s1);
        uint32_t r2 = pack_bf16(d[4 * j + 4] * s0, d[4 * j + 5] * s0);
        uint32_t r3 = pack_bf16(d[4 * j + 6] * s1, d[4 * j + 7] * s1);
        int chunk = j + (mi >> 1);
        stmatrix_x4(base + row * 128 + ((chunk ^ (row & 7)) << 4), r0, r1, r2, r3);
    }
}
struct cf { float x, y; };
DEVI cf cmul(cf a, cf b) { cf r; r.x = fmaf(a.x, b.x, -a.y * b.y); r.y = fmaf(a.x, b.y, a.y * b.x); return r; }
DEVI cf csq(cf a) { cf r; r.x = fmaf(a.x, a.x, -a.y * a.y); r.y = (a.x + a.x) * a.y; return r; }
DEVI cf cexp_(float re, float im) {
    float m = __expf(re), s, c;
    __sincosf(im, &s, &c);
    cf r; r.x = m * c; r.y = m * s; return r;
}
DEVI uint32_t h2(cf v) { uint32_t r; asm("cvt.rn.f16x2.f32 %0, %1, %2;" : "=r"(r) : "f"(v.y), "f"(v.x)); return r; }
DEVI uint32_t h2c(cf v) { uint32_t r; asm("cvt.rn.f16x2.f32 %0, %1, %2;" : "=r"(r) : "f"(-v.y), "f"(v.x)); return r; }
DEVI void mma_group(float (*c)[4], const uint32_t (*a)[4], const uint32_t (*b)[2]) {
    asm volatile(
        "mma.sync.aligned.m16n8k16.row.col.f32.f16.f16.f32 {%0,%1,%2,%3}, {%20,%21,%22,%23}, {%40,%41}, {%0,%1,%2,%3};\n"
        "mma.sync.aligned.m16n8k16.row.col.f32.f16.f16.f32 {%4,%5,%6,%7}, {%24,%25,%26,%27}, {%40,%41}, {%4,%5,%6,%7};\n"
        "mma.sync.aligned.m16n8k16.row.col.f32.f16.f16.f32 {%8,%9,%10,%11}, {%28,%29,%30,%31}, {%42,%43}, {%8,%9,%10,%11};\n"
        "mma.sync.aligned.m16n8k16.row.col.f32.f16.f16.f32 {%12,%13,%14,%15}, {%32,%33,%34,%35}, {%44,%45}, {%12,%13,%14,%15};\n"
        "mma.sync.aligned.m16n8k16.row.col.f32.f16.f16.f32 {%16,%17,%18,%19}, {%36,%37,%38,%39}, {%46,%47}, {%16,%17,%18,%19};\n"
        : "+f"(c[0][0]), "+f"(c[0][1]), "+f"(c[0][2]), "+f"(c[0][3]), "+f"(c[1][0]), "+f"(c[1][1]), "+f"(c[1][2]), "+f"(c[1][3]),
          "+f"(c[2][0]), "+f"(c[2][1]), "+f"(c[2][2]), "+f"(c[2][3]), "+f"(c[3][0]), "+f"(c[3][1]), "+f"(c[3][2]), "+f"(c[3][3]),
          "+f"(c[4][0]), "+f"(c[4][1]), "+f"(c[4][2]), "+f"(c[4][3])
        : "r"(a[0][0]), "r"(a[0][1]), "r"(a[0][2]), "r"(a[0][3]), "r"(a[1][0]), "r"(a[1][1]), "r"(a[1][2]), "r"(a[1][3]),
          "r"(a[2][0]), "r"(a[2][1]), "r"(a[2][2]), "r"(a[2][3]), "r"(a[3][0]), "r"(a[3][1]), "r"(a[3][2]), "r"(a[3][3]),
          "r"(a[4][0]), "r"(a[4][1]), "r"(a[4][2]), "r"(a[4][3]),
          "r"(b[0][0]), "r"(b[0][1]), "r"(b[1][0]), "r"(b[1][1]), "r"(b[2][0]), "r"(b[2][1]), "r"(b[3][0]), "r"(b[3][1]));
}
DEVI float bf2f(bf16 v) { return __bfloat162float(v); }
DEVI float rbf(float v) { return __bfloat162float(__float2bfloat16_rn(v)); }

struct SsmParams { const bf16 *lar, *aim, *cre, *cim, *ldt, *dskip, *u; };

DEVI int kp_index(int l) {
    int p = (int)rbf((float)l);
    return p < 256 ? p : (p < 512 ? 128 + (p >> 1) : (p < 1024 ? 256 + (p >> 2) : 384 + (p >> 3)));
}

DEVI void ssm_kgen_warp(const SsmParams& P, int d, int lane, float* kp) {
    const int g = lane >> 2, t = lane & 3;
    float ar[4], ai[4], cr[4], ci[4], gr[4], gi[4];
    bf16 raw[4][4];
    const bf16 rdt = P.ldt[d];
#pragma unroll
    for (int q = 0; q < 4; q++) {
        const int n = d * SSM_N + 32 * q + lane;
        raw[q][0] = P.lar[n]; raw[q][1] = P.aim[n]; raw[q][2] = P.cre[n]; raw[q][3] = P.cim[n];
    }
    const float dt = rbf(expf(bf2f(rdt)));
#pragma unroll
    for (int q = 0; q < 4; q++) {
        ar[q] = -rbf(expf(bf2f(raw[q][0]))) * dt;
        ai[q] = bf2f(raw[q][1]) * dt;
        cr[q] = 2.f * (bf2f(raw[q][2]) * dt);
        ci[q] = 2.f * (bf2f(raw[q][3]) * dt);
        float m = expf(ar[q] * 64.f), sn, cs;
        sincosf(ai[q] * 64.f, &sn, &cs);
        gr[q] = m * cs; gi[q] = m * sn;
    }
    float cm = 0.f;
#pragma unroll
    for (int q = 0; q < 4; q++) cm = fmaxf(cm, fmaxf(fabsf(cr[q]), fabsf(ci[q])));
#pragma unroll
    for (int o = 16; o; o >>= 1) cm = fmaxf(cm, __shfl_xor_sync(~0u, cm, o));
    const int ex = min(max((int)(__float_as_uint(cm) >> 23), 1), 253);
    const float cs_dn = __uint_as_float((uint32_t)(254 - ex) << 23), cs_up = __uint_as_float((uint32_t)ex << 23);
    float acc[5][4];
#pragma unroll
    for (int s = 0; s < 5; s++) { acc[s][0] = acc[s][1] = acc[s][2] = acc[s][3] = 0.f; }
    float klast = 0.f;
    const float gf = (float)g;
#pragma unroll
    for (int q = 0; q < 4; q++) {
#pragma unroll 1
        for (int g0 = 0; g0 < 8; g0 += 2) {
            uint32_t fa[5][4], fb[4][2];
#pragma unroll
            for (int h = 0; h < 2; h++) {
                const int src = ((g0 + h) << 2) | t;
                const float a_r = __shfl_sync(~0u, ar[q], src), a_i = __shfl_sync(~0u, ai[q], src);
                cf C, G;
                C.x = __shfl_sync(~0u, cr[q], src) * cs_dn; C.y = __shfl_sync(~0u, ci[q], src) * cs_dn;
                G.x = __shfl_sync(~0u, gr[q], src); G.y = __shfl_sync(~0u, gi[q], src);
                cf E = cexp_(a_r * gf, a_i * gf);
                cf B = csq(csq(csq(E)));
                fb[0][h] = h2c(cmul(C, B));
                cf EG = cmul(E, G);
                fa[0][2 * h] = h2(E); fa[0][2 * h + 1] = h2(EG);
                cf G2 = csq(G);
                cf X = cmul(E, G2), Xh = cmul(EG, G2);
                fa[1][2 * h] = h2(X); fa[1][2 * h + 1] = h2(Xh);
#pragma unroll
                for (int s = 2; s < 5; s++) {
                    B = csq(B); X = csq(X); Xh = csq(Xh);
                    fb[s - 1][h] = h2c(cmul(C, B));
                    fa[s][2 * h] = h2(X); fa[s][2 * h + 1] = h2(Xh);
                }
                X = csq(X);
                klast += fmaf(C.x, X.x, -C.y * X.y);
            }
            mma_group(acc, fa, fb);
        }
    }
    klast += __shfl_xor_sync(~0u, klast, 1);
    klast += __shfl_xor_sync(~0u, klast, 2);
#pragma unroll
    for (int s = 0; s < 5; s++) {
        int b = 128 * s + g + 16 * t;
        kp[b] = acc[s][0] * cs_up; kp[b + 8] = acc[s][1] * cs_up; kp[b + 64] = acc[s][2] * cs_up; kp[b + 72] = acc[s][3] * cs_up;
    }
    if (lane == 0) kp[640] = klast * cs_up;
}

constexpr int G1_THREADS = 384;
constexpr int G1_NS = 11;
constexpr int G1_SMEM = G1_NS * 16384 + 32768 + 256 + 1024;

__global__ void __cluster_dims__(2, 1, 1) __launch_bounds__(G1_THREADS, 1)
gemm_kv_kernel(const __grid_constant__ CUtensorMap tm_c, const __grid_constant__ CUtensorMap tm_wk,
               const __grid_constant__ CUtensorMap tm_wv, const __grid_constant__ CUtensorMap tm_kv_st,
               const bf16* __restrict__ px, const bf16* __restrict__ pwq) {
    extern __shared__ uint8_t smem_raw[];
    const uint32_t sb = (smem_u32(smem_raw) + 1023) & ~1023u;
    const uint32_t sC = sb + G1_NS * 16384, bars = sC + 32768;
    const uint32_t full = bars, empty = bars + 128;
    const int tid = threadIdx.x, warp = tid >> 5, lane = tid & 31, wg = tid >> 7;
    const uint32_t rank = cluster_rank();
    const int cl = blockIdx.x >> 1;
    const int m0 = ((cl & 7) * 2 + rank) * 128;
    const int ng = cl >> 3;
    STAMP(blockIdx.x == 10 && tid == 0, 0);
    if (tid == 0) {
        for (int i = 0; i < G1_NS; i++) { mbar_init(full + 8 * i, 1); mbar_init(empty + 8 * i, 16); }
        fence_barrier_init();
        for (int it = 0; it < 8; it++) {
            mbar_expect_tx(full + 8 * it, 16384);
            tma_load_2d(sb + it * 16384, &tm_c, it * 64, m0, full + 8 * it);
        }
    }
    __syncthreads();
    cluster_sync_all();
    pdl_launch();
    if (wg == 2) {
        reg_dec<40>();
        if (tid == 256) {
            const CUtensorMap* tw = ng < 4 ? &tm_wk : &tm_wv;
            const int n0 = (ng & 3) * 1024 + rank * 64;
            int st = 8; uint32_t ph = 1;
            for (int it = 0; it < 64; it++) {
                mbar_wait(empty + 8 * st, ph);
                mbar_expect_tx(full + 8 * st, 16384);
                tma_load_2d_mc(sb + st * 16384 + rank * 8192, tw, n0 + (it >> 3) * 128, (it & 7) * 64, full + 8 * st, 3);
                if (it < 2) {
                    for (int j = 3 + it * 8 + (cl & 7); j < 19; j += 16) tma_prefetch_2d(tw, n0 + (j >> 3) * 128, (j & 7) * 64);
                }
                if (it >= 3 && it + 16 < 64 && (it & 7) == (cl & 7)) tma_prefetch_2d(tw, n0 + ((it + 16) >> 3) * 128, (it & 7) * 64);
                if (it == 24) bulk_prefetch(px + blockIdx.x * 8192, 16384);
                if (it == 32) bulk_prefetch(pwq + blockIdx.x * 16384, 32768);
                if (++st == G1_NS) { st = 0; ph ^= 1; }
            }
        }
        __syncwarp();
    } else {
        reg_inc<232>();
        uint32_t af[128];
        float acc[64];
        const int wq = warp & 3;
        const int row = wg * 64 + wq * 16 + (lane & 15);
        const uint32_t stg = sC + wg * 16384;
        int st = 8, pst = 0; uint32_t ph = 0;
#pragma unroll
        for (int kc = 0; kc < 8; kc++) {
            mbar_wait(full + 8 * kc, 0);
#pragma unroll
            for (int k = 0; k < 4; k++) {
                const uint32_t a = sb + kc * 16384 + row * 128 + (((2 * k + (lane >> 4)) ^ (row & 7)) << 4);
                uint32_t* f = af + kc * 16 + k * 4;
                asm volatile("ldmatrix.sync.aligned.m8n8.x4.shared.b16 {%0,%1,%2,%3}, [%4];"
                             : "=r"(f[0]), "=r"(f[1]), "=r"(f[2]), "=r"(f[3]) : "r"(a) : "memory");
            }
            __syncwarp();
            if (lane < 2) mbar_arrive_cluster(empty + 8 * kc, lane);
        }
#pragma unroll 1
        for (int t = 0; t < 8; t++) {
            if (wg == 1 || t > 0) named_sync(3 + wg, 256);
#pragma unroll
            for (int kc = 0; kc < 8; kc++) {
                mbar_wait(full + 8 * st, ph);
                STAMP(blockIdx.x == 10 && (tid & 127) == 0, 1 + wg * 96 + t * 12 + kc);
                wg_fence();
                const uint64_t db = desc_mnmajor(sb + st * 16384, 8192);
#pragma unroll
                for (int k = 0; k < 4; k++) wgmma_rs128<1>(acc, af + kc * 16 + k * 4, db + k * 128, (kc | k) != 0);
                wg_commit();
                if (kc == 3 && (wg == 0 || t < 7)) named_arrive(3 + (wg ^ 1), 256);
                if (kc > 0) {
                    wg_wait<1>();
                    if (lane < 2) mbar_arrive_cluster(empty + 8 * pst, lane);
                }
                pst = st;
                if (++st == G1_NS) { st = 0; ph ^= 1; }
            }
            if ((tid & 127) == 0) bulk_wait_read<0>();
            named_sync(1 + wg, 128);
            wg_wait<0>();
            STAMP(blockIdx.x == 10 && (tid & 127) == 0, 9 + wg * 96 + t * 12);
            if (lane < 2) mbar_arrive_cluster(empty + 8 * pst, lane);
            store_slab64(stg, wq * 16, acc, 1.f, 1.f, lane);
            store_slab64(stg + 8192, wq * 16, acc + 32, 1.f, 1.f, lane);
            fence_proxy_async();
            named_sync(1 + wg, 128);
            if ((tid & 127) == 0) {
                tma_store_2d(&tm_kv_st, stg, ng * 1024 + t * 128, m0 + wg * 64);
                tma_store_2d(&tm_kv_st, stg + 8192, ng * 1024 + t * 128 + 64, m0 + wg * 64);
                bulk_commit();
            }
            STAMP(blockIdx.x == 10 && (tid & 127) == 0, 10 + wg * 96 + t * 12);
        }
        if ((tid & 127) == 0) bulk_wait<0>();
        __syncwarp();
    }
    asm volatile("barrier.cluster.arrive.relaxed.aligned;\nbarrier.cluster.wait.aligned;" ::: "memory");
}
constexpr int AT_NS = 6;
constexpr int AT_SMEM = AT_NS * 32768 + 32768 + 256 + 1024;
constexpr int AT_ITEMS = 512;

DEVI uint32_t hmax2(uint32_t a, uint32_t b) { uint32_t r; asm("max.bf16x2 %0, %1, %2;" : "=r"(r) : "r"(a), "r"(b)); return r; }
DEVI uint32_t hmul2(uint32_t a, uint32_t b) { uint32_t r; asm("mul.rn.bf16x2 %0, %1, %2;" : "=r"(r) : "r"(a), "r"(b)); return r; }
DEVI uint32_t hfma2(uint32_t a, uint32_t b, uint32_t c) { uint32_t r; asm("fma.rn.bf16x2 %0, %1, %2, %3;" : "=r"(r) : "r"(a), "r"(b), "r"(c)); return r; }
DEVI float blo(uint32_t v) { return __uint_as_float(v << 16); }
DEVI float bhi(uint32_t v) { return __uint_as_float(v & 0xffff0000u); }

template <bool FIRST>
DEVI void softmax_tile(float* s, float& m0, float& m1, float& l0, float& l1, float& al0, float& al1) {
    const uint32_t HI = 0x3DB53DB5u;
    const uint32_t LO = 0x371E371Eu;
    const float L2E = 1.4426950408889634f;
    uint32_t x0 = 0xFF80FF80u, x1 = 0xFF80FF80u;
#pragma unroll
    for (int j = 0; j < 16; j++) {
        uint32_t a = pack_bf16(s[4 * j], s[4 * j + 1]), b = pack_bf16(s[4 * j + 2], s[4 * j + 3]);
        a = hfma2(a, HI, hmul2(a, LO));
        b = hfma2(b, HI, hmul2(b, LO));
        s[4 * j] = __uint_as_float(a); s[4 * j + 2] = __uint_as_float(b);
        x0 = hmax2(x0, a); x1 = hmax2(x1, b);
    }
    uint32_t x = hmax2(__byte_perm(x0, x1, 0x5410), __byte_perm(x0, x1, 0x7632));
    x = hmax2(x, __shfl_xor_sync(~0u, x, 1));
    x = hmax2(x, __shfl_xor_sync(~0u, x, 2));
    float n0 = blo(x), n1 = bhi(x);
    if (!FIRST) {
        n0 = fmaxf(n0, m0); n1 = fmaxf(n1, m1);
        al0 = ex2((m0 - n0) * L2E); al1 = ex2((m1 - n1) * L2E);
    }
    m0 = n0; m1 = n1;
    const float c0 = -n0 * L2E, c1 = -n1 * L2E;
    float s0 = 0.f, s1 = 0.f;
#pragma unroll
    for (int j = 0; j < 16; j++) {
        uint32_t a = __float_as_uint(s[4 * j]), b = __float_as_uint(s[4 * j + 2]);
        float e0 = ex2(fmaf(blo(a), L2E, c0)), e1 = ex2(fmaf(bhi(a), L2E, c0));
        float e2 = ex2(fmaf(blo(b), L2E, c1)), e3 = ex2(fmaf(bhi(b), L2E, c1));
        s0 += e0 + e1; s1 += e2 + e3;
        s[4 * j] = e0; s[4 * j + 1] = e1; s[4 * j + 2] = e2; s[4 * j + 3] = e3;
    }
    if (FIRST) { l0 = s0; l1 = s1; }
    else { l0 = fmaf(l0, al0, s0); l1 = fmaf(l1, al1, s1); }
}

struct Ring {
    int st; uint32_t ph;
    DEVI void next() { if (++st == AT_NS) { st = 0; ph ^= 1; } }
};

__global__ void __launch_bounds__(384, 1)
attn_kernel(const __grid_constant__ CUtensorMap tm_x, const __grid_constant__ CUtensorMap tm_wq,
            const __grid_constant__ CUtensorMap tm_kv, const __grid_constant__ CUtensorMap tm_ctx_st,
            const bf16* __restrict__ pu, const bf16* __restrict__ pwo) {
    extern __shared__ uint8_t smem_raw[];
    const uint32_t sb = (smem_u32(smem_raw) + 1023) & ~1023u;
    const uint32_t sO = sb + AT_NS * 32768, bars = sO + 32768;
    const uint32_t full = bars, empty = bars + 64;
    volatile int* slots = reinterpret_cast<volatile int*>(smem_raw + (bars + 128 - smem_u32(smem_raw)));
    const int tid = threadIdx.x, warp = tid >> 5, lane = tid & 31, wg = tid >> 7;
    if (tid == 0) {
        for (int i = 0; i < AT_NS; i++) { mbar_init(full + 8 * i, 1); mbar_init(empty + 8 * i, 8); }
        fence_barrier_init();
    }
    __syncthreads();
    if (wg == 2) {
        reg_dec<24>();
        if (warp == 8 && lane == 0) {
            Ring r{0, 1};
            int n = 0;
            while (true) {
                int idx = (int)atomicInc(&g_sched, AT_ITEMS + gridDim.x - 1);
                if (idx >= AT_ITEMS - 128 && idx < AT_ITEMS) {
                    bulk_prefetch(pu + (idx - (AT_ITEMS - 128)) * 8192, 16384);
                    bulk_prefetch(pwo + (idx - (AT_ITEMS - 128)) * 16384, 32768);
                }
                mbar_wait(empty + 8 * r.st, r.ph);
                if (idx >= AT_ITEMS) {
                    slots[n & 3] = -1;
                    mbar_arrive(full + 8 * r.st);
                    break;
                }
                slots[n & 3] = idx;
                const int qi = 15 - (idx >> 5), h = idx & 31;
                for (int kc = 0; kc < 8; kc++) {
                    if (kc) mbar_wait(empty + 8 * r.st, r.ph);
                    const uint32_t fb = full + 8 * r.st, dst = sb + r.st * 32768;
                    mbar_expect_tx(fb, 32768);
                    tma_load_2d(dst, &tm_x, kc * 64, qi * 128, fb);
                    tma_load_2d(dst + 16384, &tm_wq, h * 128, kc * 64, fb);
                    tma_load_2d(dst + 24576, &tm_wq, h * 128 + 64, kc * 64, fb);
                    r.next();
                }
                if (n == 0) { pdl_wait(); pdl_launch(); }
                for (int j = qi; j >= -1; j--) {
#pragma unroll
                    for (int v = 0; v < 2; v++) {
                        const int jj = j + v;
                        if (jj < 0 || jj > qi || (v == 0 && j < 0)) continue;
                        mbar_wait(empty + 8 * r.st, r.ph);
                        const uint32_t fb = full + 8 * r.st, dst = sb + r.st * 32768;
                        mbar_expect_tx(fb, 32768);
                        tma_load_2d(dst, &tm_kv, v * HDALL + h * 128, jj * 128, fb);
                        tma_load_2d(dst + 16384, &tm_kv, v * HDALL + h * 128 + 64, jj * 128, fb);
                        r.next();
                    }
                }
                n++;
            }
            if (n == 0) { pdl_wait(); pdl_launch(); }
        }
    } else {
        reg_inc<240>();
        Ring r{0, 0};
        float o[64], s[64];
        uint32_t qf[32], pa[32];
        const int g = lane >> 2, t = lane & 3, wq = warp & 3;
        const uint32_t stg = sO + wg * 16384;
        if (wg == 1) named_arrive(3, 256);
        for (int n = 0;; n++) {
            mbar_wait(full + 8 * r.st, r.ph);
            const int idx = slots[n & 3];
            if (idx < 0) break;
            const int qi = 15 - (idx >> 5), h = idx & 31;
#pragma unroll 1
            for (int kc = 0; kc < 8; kc++) {
                if (kc) mbar_wait(full + 8 * r.st, r.ph);
                wg_fence();
                const uint32_t base = sb + r.st * 32768;
                const uint64_t da = desc_kmajor(base + wg * 8192), db = desc_mnmajor(base + 16384, 8192);
#pragma unroll
                for (int k = 0; k < 4; k++) wgmma_ss128<1>(s, da + k * 2, db + k * 128, (kc | k) != 0);
                wg_commit();
                if (kc) {
                    wg_wait<1>();
                    if (lane == 0) mbar_arrive(empty + 8 * (r.st == 0 ? AT_NS - 1 : r.st - 1));
                }
                r.next();
            }
            wg_wait<0>();
            if (lane == 0) mbar_arrive(empty + 8 * (r.st == 0 ? AT_NS - 1 : r.st - 1));
#pragma unroll
            for (int i = 0; i < 32; i++) qf[i] = pack_bf16(s[2 * i], s[2 * i + 1]);
            float m0, m1, l0, l1, al0, al1;
            auto issue_qk = [&]() {
                mbar_wait(full + 8 * r.st, r.ph);
                wg_fence();
                const uint64_t db = desc_kmajor(sb + r.st * 32768);
#pragma unroll
                for (int k = 0; k < 8; k++) wgmma_rs128<0>(s, qf + 4 * k, db + (k >> 2) * 1024 + (k & 3) * 2, k != 0);
                wg_commit();
            };
            auto issue_pv = [&](const uint32_t* p, int st, uint32_t ph, int acc) {
                mbar_wait(full + 8 * st, ph);
                wg_fence();
                const uint64_t db = desc_mnmajor(sb + st * 32768, 16384);
#pragma unroll
                for (int k = 0; k < 8; k++) wgmma_rs128<1>(o, p + 4 * k, db + k * 128, acc | k);
                wg_commit();
            };
            issue_qk();
            wg_wait<0>();
            if (lane == 0) mbar_arrive(empty + 8 * r.st);
            r.next();
            {
                const int row = wg * 64 + wq * 16 + g;
#pragma unroll
                for (int j = 0; j < 16; j++) {
                    const int c = 8 * j + 2 * t;
                    if (c > row) s[4 * j] = -INFINITY;
                    if (c + 1 > row) s[4 * j + 1] = -INFINITY;
                    if (c > row + 8) s[4 * j + 2] = -INFINITY;
                    if (c + 1 > row + 8) s[4 * j + 3] = -INFINITY;
                }
            }
            softmax_tile<true>(s, m0, m1, l0, l1, al0, al1);
#pragma unroll
            for (int i = 0; i < 32; i++) pa[i] = pack_bf16(s[2 * i], s[2 * i + 1]);
            int first = 0;
#pragma unroll 1
            for (int j = qi; j >= 1; j--) {
                named_sync(3 + wg, 256);
                issue_qk();
                const int kst = r.st;
                r.next();
                issue_pv(pa, r.st, r.ph, first);
                named_arrive(3 + (wg ^ 1), 256);
                wg_wait<1>();
                if (lane == 0) mbar_arrive(empty + 8 * kst);
                softmax_tile<false>(s, m0, m1, l0, l1, al0, al1);
                wg_wait<0>();
                if (lane == 0) mbar_arrive(empty + 8 * r.st);
                r.next();
#pragma unroll
                for (int i = 0; i < 32; i++) pa[i] = pack_bf16(s[2 * i], s[2 * i + 1]);
#pragma unroll
                for (int i = 0; i < 16; i++) {
                    o[4 * i] *= al0; o[4 * i + 1] *= al0; o[4 * i + 2] *= al1; o[4 * i + 3] *= al1;
                }
                first = 1;
            }
            issue_pv(pa, r.st, r.ph, first);
            l0 += __shfl_xor_sync(~0u, l0, 1); l0 += __shfl_xor_sync(~0u, l0, 2);
            l1 += __shfl_xor_sync(~0u, l1, 1); l1 += __shfl_xor_sync(~0u, l1, 2);
            const float i0 = 1.f / l0, i1 = 1.f / l1;
            if ((tid & 127) == 0) bulk_wait_read<0>();
            named_sync(1 + wg, 128);
            wg_wait<0>();
            if (lane == 0) mbar_arrive(empty + 8 * r.st);
            r.next();
            store_slab64(stg, wq * 16, o, i0, i1, lane);
            store_slab64(stg + 8192, wq * 16, o + 32, i0, i1, lane);
            fence_proxy_async();
            named_sync(1 + wg, 128);
            if ((tid & 127) == 0) {
                tma_store_2d(&tm_ctx_st, stg, h * 128, qi * 128 + wg * 64);
                tma_store_2d(&tm_ctx_st, stg + 8192, h * 128 + 64, qi * 128 + wg * 64);
                bulk_commit();
            }
        }
        if ((tid & 127) == 0) bulk_wait<0>();
    }
}
constexpr int OP_NS = 4;
constexpr int OP_ULD = 41 * 16;
constexpr int OP_UCH = 8 * OP_ULD;
constexpr int OP_SMEM = OP_NS * 32768 + 32768 + 4 * WTAB * 4 + 4 * OP_UCH + 4 * 648 * 4 + 256 + 1024;

template <int N> DEVI void wgmma_conv(float* d, const uint32_t* a, uint64_t db);
template <> DEVI void wgmma_conv<32>(float* d, const uint32_t* a, uint64_t db) {
    asm volatile("wgmma.mma_async.sync.aligned.m64n32k16.f32.bf16.bf16 {%0,%1,%2,%3,%4,%5,%6,%7,%8,%9,%10,%11,%12,%13,%14,%15}, "
                 "{%16,%17,%18,%19}, %20, 1, 1, 1, 0;"
                 : ACC8(d, 0), ACC8(d, 8) : "r"(a[0]), "r"(a[1]), "r"(a[2]), "r"(a[3]), "l"(db));
}
template <> DEVI void wgmma_conv<24>(float* d, const uint32_t* a, uint64_t db) {
    asm volatile("wgmma.mma_async.sync.aligned.m64n24k16.f32.bf16.bf16 {%0,%1,%2,%3,%4,%5,%6,%7,%8,%9,%10,%11}, "
                 "{%12,%13,%14,%15}, %16, 1, 1, 1, 0;"
                 : ACC8(d, 0), "+f"(d[8]), "+f"(d[9]), "+f"(d[10]), "+f"(d[11]) : "r"(a[0]), "r"(a[1]), "r"(a[2]), "r"(a[3]), "l"(db));
}
template <> DEVI void wgmma_conv<16>(float* d, const uint32_t* a, uint64_t db) {
    asm volatile("wgmma.mma_async.sync.aligned.m64n16k16.f32.bf16.bf16 {%0,%1,%2,%3,%4,%5,%6,%7}, "
                 "{%8,%9,%10,%11}, %12, 1, 1, 1, 0;"
                 : ACC8(d, 0) : "r"(a[0]), "r"(a[1]), "r"(a[2]), "r"(a[3]), "l"(db));
}
template <> DEVI void wgmma_conv<8>(float* d, const uint32_t* a, uint64_t db) {
    asm volatile("wgmma.mma_async.sync.aligned.m64n8k16.f32.bf16.bf16 {%0,%1,%2,%3}, "
                 "{%4,%5,%6,%7}, %8, 1, 1, 1, 0;"
                 : "+f"(d[0]), "+f"(d[1]), "+f"(d[2]), "+f"(d[3]) : "r"(a[0]), "r"(a[1]), "r"(a[2]), "r"(a[3]), "l"(db));
}
DEVI uint32_t lds32(uint32_t a) { uint32_t v; asm volatile("ld.shared.b32 %0, [%1];" : "=r"(v) : "r"(a)); return v; }
DEVI uint32_t lds16(uint32_t a) { uint16_t v; asm volatile("ld.shared.b16 %0, [%1];" : "=h"(v) : "r"(a)); return v; }

template <int J> DEVI void conv_pair(float* acc, uint32_t* f, uint32_t wa, uint64_t du, int c) {
#pragma unroll
    for (int i = 0; i < 8; i++) {
        f[4 * i] = lds32(wa + i * 64); f[4 * i + 1] = lds32(wa + i * 64 + 32);
        f[4 * i + 2] = lds32(wa + i * 64 - 32); f[4 * i + 3] = lds32(wa + i * 64);
    }
    wg_fence();
#pragma unroll
    for (int i = 0; i < 8; i++) {
        const int kk = 3 - (i & 3);
        const uint64_t db = du + (uint64_t)(kk * 2 * (OP_ULD / 16) + (i >> 2) + c);
        wgmma_conv<32 - 8 * J>(acc, f + 4 * i, db);
    }
    wg_commit();
}
template <int J> DEVI void conv_group(float* acc, uint32_t wa, uint64_t du) {
    uint32_t fa[32], fb[32];
#pragma unroll
    for (int h = 0; h < 2; h++) {
        const int c = 8 * J + 4 * h;
        conv_pair<J>(acc, fa, wa + c * 256, du, c);
        wg_wait<1>();
        conv_pair<J>(acc, fb, wa + (c + 2) * 256, du, c + 2);
        wg_wait<1>();
    }
    wg_wait<0>();
}

__global__ void __cluster_dims__(2, 1, 1) __launch_bounds__(512, 1)
outproj_kernel(const __grid_constant__ CUtensorMap tm_ctx, const __grid_constant__ CUtensorMap tm_wo,
               const __grid_constant__ CUtensorMap tm_out, SsmParams sp, bf16* __restrict__ out) {
    extern __shared__ uint8_t smem_raw[];
    const uint32_t sb = (smem_u32(smem_raw) + 1023) & ~1023u;
    const uint32_t sX = sb + OP_NS * 32768, sW = sX + 32768, sU = sW + 4 * WTAB * 4, sK = sU + 4 * OP_UCH, bars = sK + 4 * 648 * 4;
    const uint32_t full = bars, empty = bars + 64, xfull = bars + 128, wfull = bars + 136;
    const int tid = threadIdx.x, warp = tid >> 5, lane = tid & 31, wg = tid >> 7;
    const uint32_t rank = cluster_rank();
    const uint32_t kr = rank;
    const int cl = blockIdx.x >> 1;
    const int m0 = (cl >> 2) * 128, n0 = (cl & 3) * 128, k0 = kr * 2048;
    STAMP(blockIdx.x == 10 && tid == 0, 1000);
    if (tid == 0) {
        for (int i = 0; i < OP_NS; i++) { mbar_init(full + 8 * i, 1); mbar_init(empty + 8 * i, 8); }
        mbar_init(xfull, 1);
        mbar_init(wfull, 1);
        fence_barrier_init();
    }
    __syncthreads();
    cluster_sync_all();
    if (wg == 3) {
        reg_dec<40>();
        if (tid == 384) {
            mbar_expect_tx(xfull, 32768);
            for (int it = 0; it < OP_NS; it++) {
                const uint32_t dst = sb + it * 32768, fb = full + 8 * it;
                mbar_expect_tx(fb, 32768);
                tma_load_2d(dst + 16384, &tm_wo, n0, k0 + it * 64, fb);
                tma_load_2d(dst + 24576, &tm_wo, n0 + 64, k0 + it * 64, fb);
            }
            pdl_wait();
            STAMP(blockIdx.x == 10, 1005);
            for (int it = 0; it < 32; it++) {
                const int st = it & (OP_NS - 1);
                const uint32_t dst = sb + st * 32768, fb = full + 8 * st;
                if (it >= OP_NS) {
                    mbar_wait(empty + 8 * st, ((it / OP_NS) & 1) ^ 1);
                    mbar_expect_tx(fb, 32768);
                    tma_load_2d(dst + 16384, &tm_wo, n0, k0 + it * 64, fb);
                    tma_load_2d(dst + 24576, &tm_wo, n0 + 64, k0 + it * 64, fb);
                }
                tma_load_2d(dst, &tm_ctx, k0 + it * 64, m0, fb);
                tma_load_2d(dst + 8192, &tm_ctx, k0 + it * 64, m0 + 64, fb);
            }
        }
        __syncwarp();
    } else if (wg == 2) {
        reg_inc<208>();
        const int ct = tid & 127, wq = warp & 3, g = lane >> 2, t = lane & 3;
        const int d0 = blockIdx.x * 4;
        uint2 v[2][8];
#pragma unroll
        for (int h = 0; h < 2; h++)
#pragma unroll
            for (int i = 0; i < 8; i++)
                v[h][i] = __ldg(reinterpret_cast<const uint2*>(sp.u + (size_t)((ct + 128 * h) * 8 + i) * SSM_D + d0));
        for (int i = ct; i < 4 * 8 * 8; i += 128) {
            const uint32_t a = sU + (i >> 3) * OP_ULD + (32 + (i & 7)) * 16;
            asm volatile("st.shared.v4.b32 [%0], {%1,%1,%1,%1};" ::"r"(a), "r"(0) : "memory");
        }
#pragma unroll
        for (int h = 0; h < 2; h++) {
            const int q = ct + 128 * h;
            const uint32_t a = sU + (q & 7) * OP_ULD + (31 - (q >> 3)) * 16;
#pragma unroll
            for (int c = 0; c < 4; c++) {
                uint32_t w[4];
#pragma unroll
                for (int i = 0; i < 4; i++) {
                    const uint32_t lo = (c & 2) ? v[h][2 * i].y : v[h][2 * i].x, hi = (c & 2) ? v[h][2 * i + 1].y : v[h][2 * i + 1].x;
                    w[i] = __byte_perm(lo, hi, (c & 1) ? 0x7632 : 0x5410);
                }
                asm volatile("st.shared.v4.b32 [%0], {%1,%2,%3,%4};" ::"r"(a + c * OP_UCH), "r"(w[0]), "r"(w[1]), "r"(w[2]), "r"(w[3]) : "memory");
            }
        }
        STAMP(blockIdx.x == 10 && ct == 0, 1001);
        ssm_kgen_warp(sp, d0 + wq, lane, reinterpret_cast<float*>(smem_raw + (sK - smem_u32(smem_raw))) + wq * 648);
        named_sync(3, 128);
        STAMP(blockIdx.x == 10 && ct == 0, 1002);
        for (int qd = ct; qd < WTAB / 4; qd += 128) {
            const int o = qd * 4 - 64;
            uint32_t ka[5];
#pragma unroll
            for (int e = 0; e < 5; e++) ka[e] = sK + 4 * kp_index(max(o - 1 + e, 0));
#pragma unroll
            for (int c = 0; c < 4; c++) {
                float k[5];
#pragma unroll
                for (int e = 0; e < 5; e++) k[e] = o - 1 + e < 0 ? 0.f : __uint_as_float(lds32(ka[e] + c * 648 * 4));
                asm volatile("st.shared.v4.b32 [%0], {%1,%2,%3,%4};" ::"r"(sW + (c * WTAB + qd * 4) * 4), "r"(pack_bf16(k[1], k[0])),
                             "r"(pack_bf16(k[2], k[1])), "r"(pack_bf16(k[3], k[2])), "r"(pack_bf16(k[4], k[3])) : "memory");
            }
        }
        const uint2 dsk = __ldg(reinterpret_cast<const uint2*>(sp.dskip + d0));
        fence_proxy_async();
        named_sync(3, 128);
        uint32_t res[16][2];
        STAMP(blockIdx.x == 10 && ct == 0, 1003);
#pragma unroll 1
        for (int c = 0; c < 4; c++) {
            float acc[16];
#pragma unroll
            for (int i = 0; i < 16; i++) acc[i] = 0.f;
            const uint32_t wa = sW + (c * WTAB + 64 + 16 * (wq - 3) + g - 2 * t) * 4;
            const uint64_t du = make_desc(sU + c * OP_UCH, OP_ULD, 128, 0);
            conv_group<0>(acc, wa, du);
            conv_group<1>(acc, wa, du);
            conv_group<2>(acc, wa, du);
            conv_group<3>(acc, wa, du);
            const uint32_t dw = (c & 2) ? dsk.y : dsk.x;
            const float D = (c & 1) ? bhi(dw) : blo(dw);
#pragma unroll
            for (int i = 0; i < 16; i++) {
                const int n = 8 * (i >> 2) + 2 * t + (i & 1), j = 2 * wq + ((i >> 1) & 1);
                const float u = __uint_as_float(lds16(sU + c * OP_UCH + j * OP_ULD + n * 16 + g * 2) << 16);
                const uint32_t o = __bfloat16_as_ushort(__float2bfloat16_rn(rbf(acc[i]) + rbf(u * D)));
                res[i][0] = __byte_perm(res[i][0], res[i][1], 0x5432); res[i][1] = __byte_perm(res[i][1], o, 0x5432);
            }
        }
        STAMP(blockIdx.x == 10 && ct == 0, 1004);
#pragma unroll
        for (int i = 0; i < 16; i++) {
            const int a = 31 - (8 * (i >> 2) + 2 * t + (i & 1)), b = 16 * wq + g + 8 * ((i >> 1) & 1);
            *reinterpret_cast<uint2*>(out + (size_t)(64 * a + b) * 1024 + 512 + d0) = make_uint2(res[i][0], res[i][1]);
        }
    } else {
        float acc[64];
#pragma unroll 1
        for (int it = 0; it < 32; it++) {
            const int st = it & (OP_NS - 1);
            mbar_wait(full + 8 * st, (it / OP_NS) & 1);
            STAMP(blockIdx.x == 10 && tid == 0, 1009 + it);
            wg_fence();
            const uint32_t base = sb + st * 32768;
            const uint64_t da = desc_kmajor(base + wg * 8192), db = desc_mnmajor(base + 16384, 8192);
#pragma unroll
            for (int k = 0; k < 4; k++) wgmma_ss128<1>(acc, da + k * 2, db + k * 128, (it | k) != 0);
            wg_commit();
            if (it > 0 && it + OP_NS - 1 < 32) {
                wg_wait<1>();
                if (lane == 0) mbar_arrive(empty + 8 * ((it - 1) & (OP_NS - 1)));
            }
        }
        wg_wait<0>();
        uint32_t peer, pbar;
        asm volatile("mapa.shared::cluster.u32 %0, %1, %2;" : "=r"(peer) : "r"(sX + tid * 16), "r"(rank ^ 1));
        asm volatile("mapa.shared::cluster.u32 %0, %1, %2;" : "=r"(pbar) : "r"(xfull), "r"(rank ^ 1));
#pragma unroll
        for (int i = 0; i < 8; i++) {
            const float* s = acc + 4 * i;
            const float a = kr ? s[0] : s[32], b = kr ? s[1] : s[33], c = kr ? s[2] : s[34], d = kr ? s[3] : s[35];
            asm volatile("st.async.weak.shared::cluster.mbarrier::complete_tx::bytes.v4.f32 [%0], {%1,%2,%3,%4}, [%5];"
                         ::"r"(peer + i * 4096), "f"(a), "f"(b), "f"(c), "f"(d), "r"(pbar) : "memory");
        }
        STAMP(blockIdx.x == 10 && tid == 0, 1006);
        mbar_wait(xfull, 0);
        STAMP(blockIdx.x == 10 && tid == 0, 1007);
        float r[32];
#pragma unroll
        for (int i = 0; i < 8; i++) {
            float a, b, c, d;
            asm volatile("ld.shared.v4.f32 {%0,%1,%2,%3}, [%4];" : "=f"(a), "=f"(b), "=f"(c), "=f"(d) : "r"(sX + tid * 16 + i * 4096));
            const float* s = acc + 4 * i;
            r[4 * i] = a + (kr ? s[32] : s[0]); r[4 * i + 1] = b + (kr ? s[33] : s[1]);
            r[4 * i + 2] = c + (kr ? s[34] : s[2]); r[4 * i + 3] = d + (kr ? s[35] : s[3]);
        }
        const uint32_t stg = sb + wg * 8192;
        store_slab64(stg, (warp & 3) * 16, r, 1.f, 1.f, lane);
        fence_proxy_async();
        named_sync(1 + wg, 128);
        if ((tid & 127) == 0) {
            tma_store_2d(&tm_out, stg, n0 + kr * 64, m0 + wg * 64);
            bulk_commit();
            bulk_wait<0>();
            STAMP(blockIdx.x == 10 && tid == 0, 1008);
        }
    }
}

typedef CUresult (*EncodeFn)(CUtensorMap*, CUtensorMapDataType, cuuint32_t, void*, const cuuint64_t*, const cuuint64_t*,
                             const cuuint32_t*, const cuuint32_t*, CUtensorMapInterleave, CUtensorMapSwizzle,
                             CUtensorMapL2promotion, CUtensorMapFloatOOBfill);

static void make_map(EncodeFn fn, CUtensorMap* m, const void* p, uint64_t cols, uint64_t rows, uint32_t box_rows) {
    cuuint64_t dims[2] = {cols, rows};
    cuuint64_t strides[1] = {cols * 2};
    cuuint32_t box[2] = {64, box_rows};
    cuuint32_t es[2] = {1, 1};
    fn(m, CU_TENSOR_MAP_DATA_TYPE_BFLOAT16, 2, const_cast<void*>(p), dims, strides, box, es, CU_TENSOR_MAP_INTERLEAVE_NONE,
       CU_TENSOR_MAP_SWIZZLE_128B, CU_TENSOR_MAP_L2_PROMOTION_L2_256B, CU_TENSOR_MAP_FLOAT_OOB_FILL_NONE);
}

extern "C" void kernel_launch(void* const* d_in, const int* in_sizes, int n_in, void* d_out, int out_size) {
    void* fp = nullptr;
    cudaDriverEntryPointQueryResult qr;
    cudaGetDriverEntryPoint("cuTensorMapEncodeTiled", &fp, cudaEnableDefault, &qr);
    EncodeFn fn = (EncodeFn)fp;
    void *p_kv, *p_ctx;
    cudaGetSymbolAddress(&p_kv, g_kv);
    cudaGetSymbolAddress(&p_ctx, g_ctx);
    CUtensorMap tm_kv_st, tm_x, tm_c, tm_wq, tm_wk, tm_wv, tm_wo, tm_kv, tm_ctx, tm_out;
    make_map(fn, &tm_x, d_in[0], DM, SEQ, 128);
    make_map(fn, &tm_c, d_in[1], DM, SEQ, 128);
    make_map(fn, &tm_wq, d_in[2], HDALL, DM, 64);
    make_map(fn, &tm_wk, d_in[3], HDALL, DM, 64);
    make_map(fn, &tm_wv, d_in[4], HDALL, DM, 64);
    make_map(fn, &tm_wo, d_in[5], DM, HDALL, 64);
    make_map(fn, &tm_kv, p_kv, 2 * HDALL, SEQ, 128);
    make_map(fn, &tm_kv_st, p_kv, 2 * HDALL, SEQ, 64);
    make_map(fn, &tm_ctx, p_ctx, HDALL, SEQ, 64);
    make_map(fn, &tm_out, d_out, 1024, SEQ, 64);
    SsmParams sp;
    sp.u = (const bf16*)d_in[6]; sp.lar = (const bf16*)d_in[7]; sp.aim = (const bf16*)d_in[8];
    sp.cre = (const bf16*)d_in[9]; sp.cim = (const bf16*)d_in[10]; sp.ldt = (const bf16*)d_in[11]; sp.dskip = (const bf16*)d_in[12];
    cudaFuncSetAttribute(gemm_kv_kernel, cudaFuncAttributeMaxDynamicSharedMemorySize, G1_SMEM);
    cudaFuncSetAttribute(attn_kernel, cudaFuncAttributeMaxDynamicSharedMemorySize, AT_SMEM);
    cudaFuncSetAttribute(outproj_kernel, cudaFuncAttributeMaxDynamicSharedMemorySize, OP_SMEM);
    cudaStream_t st = cudaStreamPerThread;
    gemm_kv_kernel<<<128, G1_THREADS, G1_SMEM, st>>>(tm_c, tm_wk, tm_wv, tm_kv_st, (const bf16*)d_in[0], (const bf16*)d_in[2]);
    cudaLaunchAttribute at[1];
    at[0].id = cudaLaunchAttributeProgrammaticStreamSerialization;
    at[0].val.programmaticStreamSerializationAllowed = 1;
    cudaLaunchConfig_t cfg = {};
    cfg.stream = st; cfg.attrs = at; cfg.numAttrs = 1;
    cfg.gridDim = dim3(132); cfg.blockDim = dim3(384); cfg.dynamicSmemBytes = AT_SMEM;
    cudaLaunchKernelEx(&cfg, attn_kernel, tm_x, tm_wq, tm_kv, tm_ctx, sp.u, (const bf16*)d_in[5]);
    cfg.gridDim = dim3(128); cfg.blockDim = dim3(512); cfg.dynamicSmemBytes = OP_SMEM;
    cudaLaunchKernelEx(&cfg, outproj_kernel, tm_ctx, tm_wo, tm_out, sp, (bf16*)d_out);
}
```

```cpp
#include <cuda_runtime.h>
#include <cuda_bf16.h>
#include <cuda.h>
#include <stdint.h>

typedef __nv_bfloat16 bf16;

#define DEVI __device__ __forceinline__

constexpr int SEQ = 2048, DM = 512, NH = 32, HD = 128, HDALL = NH * HD;
constexpr int SSM_D = 512, SSM_N = 128;
constexpr int WTAB = 2112;

__device__ bf16 g_kv[(size_t)SEQ * 2 * HDALL];
__device__ bf16 g_ctx[(size_t)SEQ * HDALL];
__device__ unsigned int g_sched;

#define STAMP(cond, i)
DEVI uint32_t smem_u32(const void* p) { return (uint32_t)__cvta_generic_to_shared(p); }
DEVI void mbar_init(uint32_t a, uint32_t cnt) { asm volatile("mbarrier.init.shared::cta.b64 [%0], %1;" ::"r"(a), "r"(cnt)); }
DEVI void mbar_expect_tx(uint32_t a, uint32_t bytes) {
    asm volatile("mbarrier.arrive.expect_tx.shared::cta.b64 _, [%0], %1;" ::"r"(a), "r"(bytes) : "memory");
}
DEVI void mbar_arrive(uint32_t a) { asm volatile("mbarrier.arrive.shared::cta.b64 _, [%0];" ::"r"(a) : "memory"); }
DEVI void mbar_arrive_cluster(uint32_t a, uint32_t cta) {
    asm volatile("{\n.reg .b32 r;\nmapa.shared::cluster.u32 r, %0, %1;\n"
                 "mbarrier.arrive.shared::cluster.b64 _, [r];\n}" ::"r"(a), "r"(cta) : "memory");
}
#define MBAR_WAIT_ASM(OP)                                                                              \
    asm volatile("{\n.reg .pred p, q;\n.reg .u32 t0, t1;\n" OP " p, [%0], %1;\n@p bra D_%=;\n"         \
                 "mov.u32 t0, %%globaltimer_lo;\nW_%=:\n" OP " p, [%0], %1;\n"                         \
                 "mov.u32 t1, %%globaltimer_lo;\nsub.u32 t1, t1, t0;\n"                                \
                 "setp.gt.or.u32 q, t1, 4000000, p;\n@!q bra W_%=;\nD_%=:\n}" ::"r"(a), "r"(parity) : "memory")
DEVI void mbar_wait(uint32_t a, uint32_t parity) { MBAR_WAIT_ASM("mbarrier.try_wait.parity.shared::cta.b64"); }
DEVI void mbar_wait_cluster(uint32_t a, uint32_t parity) { MBAR_WAIT_ASM("mbarrier.try_wait.parity.acquire.cluster.shared::cta.b64"); }
DEVI void fence_barrier_init() { asm volatile("fence.mbarrier_init.release.cluster;" ::: "memory"); }
DEVI void fence_proxy_async() { asm volatile("fence.proxy.async.shared::cta;" ::: "memory"); }
DEVI void cluster_sync_all() {
    asm volatile("barrier.cluster.arrive.release.aligned;\nbarrier.cluster.wait.acquire.aligned;" ::: "memory");
}
DEVI uint32_t cluster_rank() { uint32_t r; asm volatile("mov.u32 %0, %%cluster_ctarank;" : "=r"(r)); return r; }
DEVI void tma_load_2d(uint32_t dst, const CUtensorMap* m, int c0, int c1, uint32_t bar) {
    asm volatile("cp.async.bulk.tensor.2d.shared::cluster.global.mbarrier::complete_tx::bytes [%0], [%1, {%3, %4}], [%2];"
                 ::"r"(dst), "l"(m), "r"(bar), "r"(c0), "r"(c1) : "memory");
}
DEVI void tma_load_2d_mc(uint32_t dst, const CUtensorMap* m, int c0, int c1, uint32_t bar, uint16_t mask) {
    asm volatile("cp.async.bulk.tensor.2d.shared::cluster.global.mbarrier::complete_tx::bytes.multicast::cluster [%0], [%1, {%3, %4}], [%2], %5;"
                 ::"r"(dst), "l"(m), "r"(bar), "r"(c0), "r"(c1), "h"(mask) : "memory");
}
DEVI void tma_prefetch_2d(const CUtensorMap* m, int c0, int c1) {
    asm volatile("cp.async.bulk.prefetch.tensor.2d.L2.global [%0, {%1, %2}];" ::"l"(m), "r"(c0), "r"(c1) : "memory");
}
DEVI void tma_store_2d(const CUtensorMap* m, uint32_t src, int c0, int c1) {
    asm volatile("cp.async.bulk.tensor.2d.global.shared::cta.bulk_group [%0, {%2, %3}], [%1];"
                 ::"l"(m), "r"(src), "r"(c0), "r"(c1) : "memory");
}
DEVI void bulk_load(uint32_t dst, const void* src, uint32_t bytes, uint32_t bar) {
    asm volatile("cp.async.bulk.shared::cluster.global.mbarrier::complete_tx::bytes [%0], [%1], %2, [%3];"
                 ::"r"(dst), "l"(src), "r"(bytes), "r"(bar) : "memory");
}
DEVI void bulk_prefetch(const void* src, uint32_t bytes) {
    asm volatile("cp.async.bulk.prefetch.L2.global [%0], %1;" ::"l"(src), "r"(bytes) : "memory");
}
DEVI void bulk_commit() { asm volatile("cp.async.bulk.commit_group;" ::: "memory"); }
template <int N> DEVI void bulk_wait_read() { asm volatile("cp.async.bulk.wait_group.read %0;" ::"n"(N) : "memory"); }
template <int N> DEVI void bulk_wait() { asm volatile("cp.async.bulk.wait_group %0;" ::"n"(N) : "memory"); }
DEVI void prefetch_tmap(const CUtensorMap* m) { asm volatile("prefetch.tensormap [%0];" ::"l"(m) : "memory"); }
DEVI void named_sync(int id, int n) { asm volatile("bar.sync %0, %1;" ::"r"(id), "r"(n) : "memory"); }
DEVI void named_arrive(int id, int n) { asm volatile("bar.arrive %0, %1;" ::"r"(id), "r"(n) : "memory"); }
DEVI void pdl_wait() { asm volatile("griddepcontrol.wait;" ::: "memory"); }
DEVI void pdl_launch() { asm volatile("griddepcontrol.launch_dependents;" ::: "memory"); }
template <int R> DEVI void reg_inc() { asm volatile("setmaxnreg.inc.sync.aligned.u32 %0;" ::"n"(R)); }
template <int R> DEVI void reg_dec() { asm volatile("setmaxnreg.dec.sync.aligned.u32 %0;" ::"n"(R)); }

DEVI void wg_fence() { asm volatile("wgmma.fence.sync.aligned;" ::: "memory"); }
DEVI void wg_commit() { asm volatile("wgmma.commit_group.sync.aligned;" ::: "memory"); }
template <int N> DEVI void wg_wait() { asm volatile("wgmma.wait_group.sync.aligned %0;" ::"n"(N) : "memory"); }

DEVI uint64_t make_desc(uint32_t addr, uint32_t lbo, uint32_t sbo, uint32_t swz) {
    return (uint64_t)((addr & 0x3FFFF) >> 4) | ((uint64_t)(lbo >> 4) << 16) | ((uint64_t)(sbo >> 4) << 32) | ((uint64_t)swz << 62);
}
DEVI uint64_t desc_kmajor(uint32_t addr) { return make_desc(addr, 16, 1024, 1); }
DEVI uint64_t desc_mnmajor(uint32_t addr, uint32_t lbo) { return make_desc(addr, lbo, 1024, 1); }

#define ACC8(d, o) "+f"(d[o + 0]), "+f"(d[o + 1]), "+f"(d[o + 2]), "+f"(d[o + 3]), "+f"(d[o + 4]), "+f"(d[o + 5]), "+f"(d[o + 6]), "+f"(d[o + 7])
#define ACC64(d) ACC8(d, 0), ACC8(d, 8), ACC8(d, 16), ACC8(d, 24), ACC8(d, 32), ACC8(d, 40), ACC8(d, 48), ACC8(d, 56)
#define R64 "{%0,%1,%2,%3,%4,%5,%6,%7,%8,%9,%10,%11,%12,%13,%14,%15,%16,%17,%18,%19,%20,%21,%22,%23,%24,%25,%26,%27,%28,%29,%30,%31," \
            "%32,%33,%34,%35,%36,%37,%38,%39,%40,%41,%42,%43,%44,%45,%46,%47,%48,%49,%50,%51,%52,%53,%54,%55,%56,%57,%58,%59,%60,%61,%62,%63}"

template <int TB> DEVI void wgmma_ss128(float* d, uint64_t da, uint64_t db, int acc) {
    asm volatile("{\n.reg .pred p;\nsetp.ne.b32 p, %66, 0;\n"
                 "wgmma.mma_async.sync.aligned.m64n128k16.f32.bf16.bf16 " R64 ", %64, %65, p, 1, 1, 0, %67;\n}"
                 : ACC64(d) : "l"(da), "l"(db), "r"(acc), "n"(TB));
}
template <int TB> DEVI void wgmma_rs128(float* d, const uint32_t* a, uint64_t db, int acc) {
    asm volatile("{\n.reg .pred p;\nsetp.ne.b32 p, %69, 0;\n"
                 "wgmma.mma_async.sync.aligned.m64n128k16.f32.bf16.bf16 " R64 ", {%64,%65,%66,%67}, %68, p, 1, 1, %70;\n}"
                 : ACC64(d) : "r"(a[0]), "r"(a[1]), "r"(a[2]), "r"(a[3]), "l"(db), "r"(acc), "n"(TB));
}
DEVI uint32_t pack_bf16(float lo, float hi) {
    uint32_t r;
    asm("cvt.rn.bf16x2.f32 %0, %1, %2;" : "=r"(r) : "f"(hi), "f"(lo));
    return r;
}
DEVI void stmatrix_x4(uint32_t addr, uint32_t r0, uint32_t r1, uint32_t r2, uint32_t r3) {
    asm volatile("stmatrix.sync.aligned.m8n8.x4.shared.b16 [%0], {%1,%2,%3,%4};" ::"r"(addr), "r"(r0), "r"(r1), "r"(r2), "r"(r3) : "memory");
}
DEVI float ex2(float x) { float y; asm("ex2.approx.ftz.f32 %0, %1;" : "=f"(y) : "f"(x)); return y; }

DEVI void store_slab64(uint32_t base, int row0, const float* d, float s0, float s1, int lane) {
    int mi = lane >> 3, r = lane & 7;
    int row = row0 + (mi & 1) * 8 + r;
#pragma unroll
    for (int j = 0; j < 8; j += 2) {
        uint32_t r0 = pack_bf16(d[4 * j + 0] * s0, d[4 * j + 1] * s0);
        uint32_t r1 = pack_bf16(d[4 * j + 2] * s1, d[4 * j + 3] * s1);
        uint32_t r2 = pack_bf16(d[4 * j + 4] * s0, d[4 * j + 5] * s0);
        uint32_t r3 = pack_bf16(d[4 * j + 6] * s1, d[4 * j + 7] * s1);
        int chunk = j + (mi >> 1);
        stmatrix_x4(base + row * 128 + ((chunk ^ (row & 7)) << 4), r0, r1, r2, r3);
    }
}
struct cf { float x, y; };
DEVI cf cmul(cf a, cf b) { cf r; r.x = fmaf(a.x, b.x, -a.y * b.y); r.y = fmaf(a.x, b.y, a.y * b.x); return r; }
DEVI cf csq(cf a) { cf r; r.x = fmaf(a.x, a.x, -a.y * a.y); r.y = (a.x + a.x) * a.y; return r; }
DEVI cf cexp_(float re, float im) {
    float m = __expf(re), s, c;
    __sincosf(im, &s, &c);
    cf r; r.x = m * c; r.y = m * s; return r;
}
DEVI uint32_t h2(cf v) { uint32_t r; asm("cvt.rn.f16x2.f32 %0, %1, %2;" : "=r"(r) : "f"(v.y), "f"(v.x)); return r; }
DEVI uint32_t h2c(cf v) { uint32_t r; asm("cvt.rn.f16x2.f32 %0, %1, %2;" : "=r"(r) : "f"(-v.y), "f"(v.x)); return r; }
DEVI void mma_group(float (*c)[4], const uint32_t (*a)[4], const uint32_t (*b)[2]) {
    asm volatile(
        "mma.sync.aligned.m16n8k16.row.col.f32.f16.f16.f32 {%0,%1,%2,%3}, {%20,%21,%22,%23}, {%40,%41}, {%0,%1,%2,%3};\n"
        "mma.sync.aligned.m16n8k16.row.col.f32.f16.f16.f32 {%4,%5,%6,%7}, {%24,%25,%26,%27}, {%40,%41}, {%4,%5,%6,%7};\n"
        "mma.sync.aligned.m16n8k16.row.col.f32.f16.f16.f32 {%8,%9,%10,%11}, {%28,%29,%30,%31}, {%42,%43}, {%8,%9,%10,%11};\n"
        "mma.sync.aligned.m16n8k16.row.col.f32.f16.f16.f32 {%12,%13,%14,%15}, {%32,%33,%34,%35}, {%44,%45}, {%12,%13,%14,%15};\n"
        "mma.sync.aligned.m16n8k16.row.col.f32.f16.f16.f32 {%16,%17,%18,%19}, {%36,%37,%38,%39}, {%46,%47}, {%16,%17,%18,%19};\n"
        : "+f"(c[0][0]), "+f"(c[0][1]), "+f"(c[0][2]), "+f"(c[0][3]), "+f"(c[1][0]), "+f"(c[1][1]), "+f"(c[1][2]), "+f"(c[1][3]),
          "+f"(c[2][0]), "+f"(c[2][1]), "+f"(c[2][2]), "+f"(c[2][3]), "+f"(c[3][0]), "+f"(c[3][1]), "+f"(c[3][2]), "+f"(c[3][3]),
          "+f"(c[4][0]), "+f"(c[4][1]), "+f"(c[4][2]), "+f"(c[4][3])
        : "r"(a[0][0]), "r"(a[0][1]), "r"(a[0][2]), "r"(a[0][3]), "r"(a[1][0]), "r"(a[1][1]), "r"(a[1][2]), "r"(a[1][3]),
          "r"(a[2][0]), "r"(a[2][1]), "r"(a[2][2]), "r"(a[2][3]), "r"(a[3][0]), "r"(a[3][1]), "r"(a[3][2]), "r"(a[3][3]),
          "r"(a[4][0]), "r"(a[4][1]), "r"(a[4][2]), "r"(a[4][3]),
          "r"(b[0][0]), "r"(b[0][1]), "r"(b[1][0]), "r"(b[1][1]), "r"(b[2][0]), "r"(b[2][1]), "r"(b[3][0]), "r"(b[3][1]));
}
DEVI float bf2f(bf16 v) { return __bfloat162float(v); }
DEVI float rbf(float v) { return __bfloat162float(__float2bfloat16_rn(v)); }

struct SsmParams { const bf16 *lar, *aim, *cre, *cim, *ldt, *dskip, *u; };

DEVI int kp_index(int l) {
    int p = (int)rbf((float)l);
    return p < 256 ? p : (p < 512 ? 128 + (p >> 1) : (p < 1024 ? 256 + (p >> 2) : 384 + (p >> 3)));
}

DEVI void reds(uint32_t a, float v) { asm volatile("red.shared.add.f32 [%0], %1;" ::"r"(a), "f"(v) : "memory"); }
DEVI void ssm_kgen_warp(const SsmParams& P, int d, int half, int lane, uint32_t kp) {
    const int g = lane >> 2, t = lane & 3;
    float ar[2], ai[2], cr[2], ci[2], gr[2], gi[2];
    bf16 raw[2][4];
    const bf16 rdt = P.ldt[d];
#pragma unroll
    for (int q = 0; q < 2; q++) {
        const int n = d * SSM_N + 64 * half + 32 * q + lane;
        raw[q][0] = P.lar[n]; raw[q][1] = P.aim[n]; raw[q][2] = P.cre[n]; raw[q][3] = P.cim[n];
    }
    const float dt = rbf(expf(bf2f(rdt)));
#pragma unroll
    for (int q = 0; q < 2; q++) {
        ar[q] = -rbf(expf(bf2f(raw[q][0]))) * dt;
        ai[q] = bf2f(raw[q][1]) * dt;
        cr[q] = 2.f * (bf2f(raw[q][2]) * dt);
        ci[q] = 2.f * (bf2f(raw[q][3]) * dt);
        float m = expf(ar[q] * 64.f), sn, cs;
        sincosf(ai[q] * 64.f, &sn, &cs);
        gr[q] = m * cs; gi[q] = m * sn;
    }
    float cm = 0.f;
#pragma unroll
    for (int q = 0; q < 2; q++) cm = fmaxf(cm, fmaxf(fabsf(cr[q]), fabsf(ci[q])));
#pragma unroll
    for (int o = 16; o; o >>= 1) cm = fmaxf(cm, __shfl_xor_sync(~0u, cm, o));
    const int ex = min(max((int)(__float_as_uint(cm) >> 23), 1), 253);
    const float cs_dn = __uint_as_float((uint32_t)(254 - ex) << 23), cs_up = __uint_as_float((uint32_t)ex << 23);
    float acc[5][4];
#pragma unroll
    for (int s = 0; s < 5; s++) { acc[s][0] = acc[s][1] = acc[s][2] = acc[s][3] = 0.f; }
    float klast = 0.f;
    const float gf = (float)g;
#pragma unroll
    for (int q = 0; q < 2; q++) {
#pragma unroll 1
        for (int g0 = 0; g0 < 8; g0 += 2) {
            uint32_t fa[5][4], fb[4][2];
#pragma unroll
            for (int h = 0; h < 2; h++) {
                const int src = ((g0 + h) << 2) | t;
                const float a_r = __shfl_sync(~0u, ar[q], src), a_i = __shfl_sync(~0u, ai[q], src);
                cf C, G;
                C.x = __shfl_sync(~0u, cr[q], src) * cs_dn; C.y = __shfl_sync(~0u, ci[q], src) * cs_dn;
                G.x = __shfl_sync(~0u, gr[q], src); G.y = __shfl_sync(~0u, gi[q], src);
                cf E = cexp_(a_r * gf, a_i * gf);
                cf B = csq(csq(csq(E)));
                fb[0][h] = h2c(cmul(C, B));
                cf EG = cmul(E, G);
                fa[0][2 * h] = h2(E); fa[0][2 * h + 1] = h2(EG);
                cf G2 = csq(G);
                cf X = cmul(E, G2), Xh = cmul(EG, G2);
                fa[1][2 * h] = h2(X); fa[1][2 * h + 1] = h2(Xh);
#pragma unroll
                for (int s = 2; s < 5; s++) {
                    B = csq(B); X = csq(X); Xh = csq(Xh);
                    fb[s - 1][h] = h2c(cmul(C, B));
                    fa[s][2 * h] = h2(X); fa[s][2 * h + 1] = h2(Xh);
                }
                X = csq(X);
                klast += fmaf(C.x, X.x, -C.y * X.y);
            }
            mma_group(acc, fa, fb);
        }
    }
    klast += __shfl_xor_sync(~0u, klast, 1);
    klast += __shfl_xor_sync(~0u, klast, 2);
#pragma unroll
    for (int s = 0; s < 5; s++) {
        const uint32_t b = kp + (128 * s + g + 16 * t) * 4;
        reds(b, acc[s][0] * cs_up); reds(b + 32, acc[s][1] * cs_up); reds(b + 256, acc[s][2] * cs_up); reds(b + 288, acc[s][3] * cs_up);
    }
    if (lane == 0) reds(kp + 2560, klast * cs_up);
}

constexpr int G1_THREADS = 384;
constexpr int G1_NS = 11;
constexpr int G1_SMEM = G1_NS * 16384 + 32768 + 256 + 1024;

__global__ void __cluster_dims__(2, 1, 1) __launch_bounds__(G1_THREADS, 1)
gemm_kv_kernel(const __grid_constant__ CUtensorMap tm_c, const __grid_constant__ CUtensorMap tm_wk,
               const __grid_constant__ CUtensorMap tm_wv, const __grid_constant__ CUtensorMap tm_kv_st,
               const bf16* __restrict__ px, const bf16* __restrict__ pwq) {
    extern __shared__ uint8_t smem_raw[];
    const uint32_t sb = (smem_u32(smem_raw) + 1023) & ~1023u;
    const uint32_t sC = sb + G1_NS * 16384, bars = sC + 32768;
    const uint32_t full = bars, empty = bars + 128;
    const int tid = threadIdx.x, warp = tid >> 5, lane = tid & 31, wg = tid >> 7;
    const uint32_t rank = cluster_rank();
    const int cl = blockIdx.x >> 1;
    const int m0 = ((cl & 7) * 2 + rank) * 128;
    const int ng = cl >> 3;
    STAMP(blockIdx.x == 10 && tid == 0, 0);
    if (tid == 0) {
        for (int i = 0; i < G1_NS; i++) { mbar_init(full + 8 * i, 1); mbar_init(empty + 8 * i, 16); }
        fence_barrier_init();
        for (int it = 0; it < 8; it++) {
            mbar_expect_tx(full + 8 * it, 16384);
            tma_load_2d(sb + it * 16384, &tm_c, it * 64, m0, full + 8 * it);
        }
    }
    __syncthreads();
    cluster_sync_all();
    pdl_launch();
    if (wg == 2) {
        reg_dec<40>();
        if (tid == 256) {
            const CUtensorMap* tw = ng < 4 ? &tm_wk : &tm_wv;
            const int n0 = (ng & 3) * 1024 + rank * 64;
            int st = 8; uint32_t ph = 1;
            for (int it = 0; it < 64; it++) {
                mbar_wait(empty + 8 * st, ph);
                mbar_expect_tx(full + 8 * st, 16384);
                tma_load_2d_mc(sb + st * 16384 + rank * 8192, tw, n0 + (it >> 3) * 128, (it & 7) * 64, full + 8 * st, 3);
                if (it < 2) {
                    for (int j = 3 + it * 8 + (cl & 7); j < 19; j += 16) tma_prefetch_2d(tw, n0 + (j >> 3) * 128, (j & 7) * 64);
                }
                if (it >= 3 && it + 16 < 64 && (it & 7) == (cl & 7)) tma_prefetch_2d(tw, n0 + ((it + 16) >> 3) * 128, (it & 7) * 64);
                if (it == 24) bulk_prefetch(px + blockIdx.x * 8192, 16384);
                if (it == 32) bulk_prefetch(pwq + blockIdx.x * 16384, 32768);
                if (++st == G1_NS) { st = 0; ph ^= 1; }
            }
        }
        __syncwarp();
    } else {
        reg_inc<232>();
        uint32_t af[128];
        float acc[64];
        const int wq = warp & 3;
        const int row = wg * 64 + wq * 16 + (lane & 15);
        const uint32_t stg = sC + wg * 16384;
        int st = 8, pst = 0; uint32_t ph = 0;
#pragma unroll
        for (int kc = 0; kc < 8; kc++) {
            mbar_wait(full + 8 * kc, 0);
#pragma unroll
            for (int k = 0; k < 4; k++) {
                const uint32_t a = sb + kc * 16384 + row * 128 + (((2 * k + (lane >> 4)) ^ (row & 7)) << 4);
                uint32_t* f = af + kc * 16 + k * 4;
                asm volatile("ldmatrix.sync.aligned.m8n8.x4.shared.b16 {%0,%1,%2,%3}, [%4];"
                             : "=r"(f[0]), "=r"(f[1]), "=r"(f[2]), "=r"(f[3]) : "r"(a) : "memory");
            }
            __syncwarp();
            if (lane < 2) mbar_arrive_cluster(empty + 8 * kc, lane);
        }
#pragma unroll 1
        for (int t = 0; t < 8; t++) {
            if (wg == 1 || t > 0) named_sync(3 + wg, 256);
#pragma unroll
            for (int kc = 0; kc < 8; kc++) {
                mbar_wait(full + 8 * st, ph);
                STAMP(blockIdx.x == 10 && (tid & 127) == 0, 1 + wg * 96 + t * 12 + kc);
                wg_fence();
                const uint64_t db = desc_mnmajor(sb + st * 16384, 8192);
#pragma unroll
                for (int k = 0; k < 4; k++) wgmma_rs128<1>(acc, af + kc * 16 + k * 4, db + k * 128, (kc | k) != 0);
                wg_commit();
                if (kc == 3 && (wg == 0 || t < 7)) named_arrive(3 + (wg ^ 1), 256);
                if (kc > 0) {
                    wg_wait<1>();
                    if (lane < 2) mbar_arrive_cluster(empty + 8 * pst, lane);
                }
                pst = st;
                if (++st == G1_NS) { st = 0; ph ^= 1; }
            }
            if ((tid & 127) == 0) bulk_wait_read<0>();
            named_sync(1 + wg, 128);
            wg_wait<0>();
            STAMP(blockIdx.x == 10 && (tid & 127) == 0, 9 + wg * 96 + t * 12);
            if (lane < 2) mbar_arrive_cluster(empty + 8 * pst, lane);
            store_slab64(stg, wq * 16, acc, 1.f, 1.f, lane);
            store_slab64(stg + 8192, wq * 16, acc + 32, 1.f, 1.f, lane);
            fence_proxy_async();
            named_sync(1 + wg, 128);
            if ((tid & 127) == 0) {
                tma_store_2d(&tm_kv_st, stg, ng * 1024 + t * 128, m0 + wg * 64);
                tma_store_2d(&tm_kv_st, stg + 8192, ng * 1024 + t * 128 + 64, m0 + wg * 64);
                bulk_commit();
            }
            STAMP(blockIdx.x == 10 && (tid & 127) == 0, 10 + wg * 96 + t * 12);
        }
        if ((tid & 127) == 0) bulk_wait<0>();
        __syncwarp();
    }
    asm volatile("barrier.cluster.arrive.relaxed.aligned;\nbarrier.cluster.wait.aligned;" ::: "memory");
}
constexpr int AT_NS = 6;
constexpr int AT_SMEM = AT_NS * 32768 + 32768 + 256 + 1024;
constexpr int AT_ITEMS = 512;

DEVI uint32_t hmax2(uint32_t a, uint32_t b) { uint32_t r; asm("max.bf16x2 %0, %1, %2;" : "=r"(r) : "r"(a), "r"(b)); return r; }
DEVI uint32_t hmul2(uint32_t a, uint32_t b) { uint32_t r; asm("mul.rn.bf16x2 %0, %1, %2;" : "=r"(r) : "r"(a), "r"(b)); return r; }
DEVI uint32_t hfma2(uint32_t a, uint32_t b, uint32_t c) { uint32_t r; asm("fma.rn.bf16x2 %0, %1, %2, %3;" : "=r"(r) : "r"(a), "r"(b), "r"(c)); return r; }
DEVI float blo(uint32_t v) { return __uint_as_float(v << 16); }
DEVI float bhi(uint32_t v) { return __uint_as_float(v & 0xffff0000u); }

template <bool FIRST>
DEVI void softmax_tile(float* s, float& m0, float& m1, float& l0, float& l1, float& al0, float& al1) {
    const uint32_t HI = 0x3DB53DB5u;
    const uint32_t LO = 0x371E371Eu;
    const float L2E = 1.4426950408889634f;
    uint32_t x0 = 0xFF80FF80u, x1 = 0xFF80FF80u;
#pragma unroll
    for (int j = 0; j < 16; j++) {
        uint32_t a = pack_bf16(s[4 * j], s[4 * j + 1]), b = pack_bf16(s[4 * j + 2], s[4 * j + 3]);
        a = hfma2(a, HI, hmul2(a, LO));
        b = hfma2(b, HI, hmul2(b, LO));
        s[4 * j] = __uint_as_float(a); s[4 * j + 2] = __uint_as_float(b);
        x0 = hmax2(x0, a); x1 = hmax2(x1, b);
    }
    uint32_t x = hmax2(__byte_perm(x0, x1, 0x5410), __byte_perm(x0, x1, 0x7632));
    x = hmax2(x, __shfl_xor_sync(~0u, x, 1));
    x = hmax2(x, __shfl_xor_sync(~0u, x, 2));
    float n0 = blo(x), n1 = bhi(x);
    if (!FIRST) {
        n0 = fmaxf(n0, m0); n1 = fmaxf(n1, m1);
        al0 = ex2((m0 - n0) * L2E); al1 = ex2((m1 - n1) * L2E);
    }
    m0 = n0; m1 = n1;
    const float c0 = -n0 * L2E, c1 = -n1 * L2E;
    float s0 = 0.f, s1 = 0.f;
#pragma unroll
    for (int j = 0; j < 16; j++) {
        uint32_t a = __float_as_uint(s[4 * j]), b = __float_as_uint(s[4 * j + 2]);
        float e0 = ex2(fmaf(blo(a), L2E, c0)), e1 = ex2(fmaf(bhi(a), L2E, c0));
        float e2 = ex2(fmaf(blo(b), L2E, c1)), e3 = ex2(fmaf(bhi(b), L2E, c1));
        s0 += e0 + e1; s1 += e2 + e3;
        s[4 * j] = e0; s[4 * j + 1] = e1; s[4 * j + 2] = e2; s[4 * j + 3] = e3;
    }
    if (FIRST) { l0 = s0; l1 = s1; }
    else { l0 = fmaf(l0, al0, s0); l1 = fmaf(l1, al1, s1); }
}

struct Ring {
    int st; uint32_t ph;
    DEVI void next() { if (++st == AT_NS) { st = 0; ph ^= 1; } }
};

__global__ void __launch_bounds__(384, 1)
attn_kernel(const __grid_constant__ CUtensorMap tm_x, const __grid_constant__ CUtensorMap tm_wq,
            const __grid_constant__ CUtensorMap tm_kv, const __grid_constant__ CUtensorMap tm_ctx_st,
            const bf16* __restrict__ pu, const bf16* __restrict__ pwo) {
    extern __shared__ uint8_t smem_raw[];
    const uint32_t sb = (smem_u32(smem_raw) + 1023) & ~1023u;
    const uint32_t sO = sb + AT_NS * 32768, bars = sO + 32768;
    const uint32_t full = bars, empty = bars + 64;
    volatile int* slots = reinterpret_cast<volatile int*>(smem_raw + (bars + 128 - smem_u32(smem_raw)));
    const int tid = threadIdx.x, warp = tid >> 5, lane = tid & 31, wg = tid >> 7;
    if (tid == 0) {
        for (int i = 0; i < AT_NS; i++) { mbar_init(full + 8 * i, 1); mbar_init(empty + 8 * i, 8); }
        fence_barrier_init();
    }
    __syncthreads();
    if (wg == 2) {
        reg_dec<24>();
        if (warp == 8 && lane == 0) {
            Ring r{0, 1};
            int n = 0;
            while (true) {
                int idx = (int)atomicInc(&g_sched, AT_ITEMS + gridDim.x - 1);
                if (idx >= AT_ITEMS - 128 && idx < AT_ITEMS) {
                    bulk_prefetch(pu + (idx - (AT_ITEMS - 128)) * 8192, 16384);
                    bulk_prefetch(pwo + (idx - (AT_ITEMS - 128)) * 16384, 32768);
                }
                mbar_wait(empty + 8 * r.st, r.ph);
                if (idx >= AT_ITEMS) {
                    slots[n & 3] = -1;
                    mbar_arrive(full + 8 * r.st);
                    break;
                }
                slots[n & 3] = idx;
                const int qi = 15 - (idx >> 5), h = idx & 31;
                for (int kc = 0; kc < 8; kc++) {
                    if (kc) mbar_wait(empty + 8 * r.st, r.ph);
                    const uint32_t fb = full + 8 * r.st, dst = sb + r.st * 32768;
                    mbar_expect_tx(fb, 32768);
                    tma_load_2d(dst, &tm_x, kc * 64, qi * 128, fb);
                    tma_load_2d(dst + 16384, &tm_wq, h * 128, kc * 64, fb);
                    tma_load_2d(dst + 24576, &tm_wq, h * 128 + 64, kc * 64, fb);
                    r.next();
                }
                if (n == 0) { pdl_wait(); pdl_launch(); }
                for (int j = qi; j >= -1; j--) {
#pragma unroll
                    for (int v = 0; v < 2; v++) {
                        const int jj = j + v;
                        if (jj < 0 || jj > qi || (v == 0 && j < 0)) continue;
                        mbar_wait(empty + 8 * r.st, r.ph);
                        const uint32_t fb = full + 8 * r.st, dst = sb + r.st * 32768;
                        mbar_expect_tx(fb, 32768);
                        tma_load_2d(dst, &tm_kv, v * HDALL + h * 128, jj * 128, fb);
                        tma_load_2d(dst + 16384, &tm_kv, v * HDALL + h * 128 + 64, jj * 128, fb);
                        r.next();
                    }
                }
                n++;
            }
            if (n == 0) { pdl_wait(); pdl_launch(); }
        }
    } else {
        reg_inc<240>();
        Ring r{0, 0};
        float o[64], s[64];
        uint32_t qf[32], pa[32];
        const int g = lane >> 2, t = lane & 3, wq = warp & 3;
        const uint32_t stg = sO + wg * 16384;
        if (wg == 1) named_arrive(3, 256);
        for (int n = 0;; n++) {
            mbar_wait(full + 8 * r.st, r.ph);
            const int idx = slots[n & 3];
            if (idx < 0) break;
            const int qi = 15 - (idx >> 5), h = idx & 31;
#pragma unroll 1
            for (int kc = 0; kc < 8; kc++) {
                if (kc) mbar_wait(full + 8 * r.st, r.ph);
                wg_fence();
                const uint32_t base = sb + r.st * 32768;
                const uint64_t da = desc_kmajor(base + wg * 8192), db = desc_mnmajor(base + 16384, 8192);
#pragma unroll
                for (int k = 0; k < 4; k++) wgmma_ss128<1>(s, da + k * 2, db + k * 128, (kc | k) != 0);
                wg_commit();
                if (kc) {
                    wg_wait<1>();
                    if (lane == 0) mbar_arrive(empty + 8 * (r.st == 0 ? AT_NS - 1 : r.st - 1));
                }
                r.next();
            }
            wg_wait<0>();
            if (lane == 0) mbar_arrive(empty + 8 * (r.st == 0 ? AT_NS - 1 : r.st - 1));
#pragma unroll
            for (int i = 0; i < 32; i++) qf[i] = pack_bf16(s[2 * i], s[2 * i + 1]);
            float m0, m1, l0, l1, al0, al1;
            auto issue_qk = [&]() {
                mbar_wait(full + 8 * r.st, r.ph);
                wg_fence();
                const uint64_t db = desc_kmajor(sb + r.st * 32768);
#pragma unroll
                for (int k = 0; k < 8; k++) wgmma_rs128<0>(s, qf + 4 * k, db + (k >> 2) * 1024 + (k & 3) * 2, k != 0);
                wg_commit();
            };
            auto issue_pv = [&](const uint32_t* p, int st, uint32_t ph, int acc) {
                mbar_wait(full + 8 * st, ph);
                wg_fence();
                const uint64_t db = desc_mnmajor(sb + st * 32768, 16384);
#pragma unroll
                for (int k = 0; k < 8; k++) wgmma_rs128<1>(o, p + 4 * k, db + k * 128, acc | k);
                wg_commit();
            };
            issue_qk();
            wg_wait<0>();
            if (lane == 0) mbar_arrive(empty + 8 * r.st);
            r.next();
            {
                const int row = wg * 64 + wq * 16 + g;
#pragma unroll
                for (int j = 0; j < 16; j++) {
                    const int c = 8 * j + 2 * t;
                    if (c > row) s[4 * j] = -INFINITY;
                    if (c + 1 > row) s[4 * j + 1] = -INFINITY;
                    if (c > row + 8) s[4 * j + 2] = -INFINITY;
                    if (c + 1 > row + 8) s[4 * j + 3] = -INFINITY;
                }
            }
            softmax_tile<true>(s, m0, m1, l0, l1, al0, al1);
#pragma unroll
            for (int i = 0; i < 32; i++) pa[i] = pack_bf16(s[2 * i], s[2 * i + 1]);
            int first = 0;
#pragma unroll 1
            for (int j = qi; j >= 1; j--) {
                named_sync(3 + wg, 256);
                issue_qk();
                const int kst = r.st;
                r.next();
                issue_pv(pa, r.st, r.ph, first);
                named_arrive(3 + (wg ^ 1), 256);
                wg_wait<1>();
                if (lane == 0) mbar_arrive(empty + 8 * kst);
                softmax_tile<false>(s, m0, m1, l0, l1, al0, al1);
                wg_wait<0>();
                if (lane == 0) mbar_arrive(empty + 8 * r.st);
                r.next();
#pragma unroll
                for (int i = 0; i < 32; i++) pa[i] = pack_bf16(s[2 * i], s[2 * i + 1]);
#pragma unroll
                for (int i = 0; i < 16; i++) {
                    o[4 * i] *= al0; o[4 * i + 1] *= al0; o[4 * i + 2] *= al1; o[4 * i + 3] *= al1;
                }
                first = 1;
            }
            issue_pv(pa, r.st, r.ph, first);
            l0 += __shfl_xor_sync(~0u, l0, 1); l0 += __shfl_xor_sync(~0u, l0, 2);
            l1 += __shfl_xor_sync(~0u, l1, 1); l1 += __shfl_xor_sync(~0u, l1, 2);
            const float i0 = 1.f / l0, i1 = 1.f / l1;
            if ((tid & 127) == 0) bulk_wait_read<0>();
            named_sync(1 + wg, 128);
            wg_wait<0>();
            if (lane == 0) mbar_arrive(empty + 8 * r.st);
            r.next();
            store_slab64(stg, wq * 16, o, i0, i1, lane);
            store_slab64(stg + 8192, wq * 16, o + 32, i0, i1, lane);
            fence_proxy_async();
            named_sync(1 + wg, 128);
            if ((tid & 127) == 0) {
                tma_store_2d(&tm_ctx_st, stg, h * 128, qi * 128 + wg * 64);
                tma_store_2d(&tm_ctx_st, stg + 8192, h * 128 + 64, qi * 128 + wg * 64);
                bulk_commit();
            }
        }
        if ((tid & 127) == 0) bulk_wait<0>();
    }
}
constexpr int OP_NS = 4;
constexpr int OP_ULD = 41 * 16;
constexpr int OP_UCH = 8 * OP_ULD;
constexpr int OP_SMEM = OP_NS * 32768 + 32768 + 4 * WTAB * 4 + 4 * OP_UCH + 4 * 648 * 4 + 256 + 1024;

template <int N> DEVI void wgmma_conv(float* d, const uint32_t* a, uint64_t db);
template <> DEVI void wgmma_conv<32>(float* d, const uint32_t* a, uint64_t db) {
    asm volatile("wgmma.mma_async.sync.aligned.m64n32k16.f32.bf16.bf16 {%0,%1,%2,%3,%4,%5,%6,%7,%8,%9,%10,%11,%12,%13,%14,%15}, "
                 "{%16,%17,%18,%19}, %20, 1, 1, 1, 0;"
                 : ACC8(d, 0), ACC8(d, 8) : "r"(a[0]), "r"(a[1]), "r"(a[2]), "r"(a[3]), "l"(db));
}
template <> DEVI void wgmma_conv<24>(float* d, const uint32_t* a, uint64_t db) {
    asm volatile("wgmma.mma_async.sync.aligned.m64n24k16.f32.bf16.bf16 {%0,%1,%2,%3,%4,%5,%6,%7,%8,%9,%10,%11}, "
                 "{%12,%13,%14,%15}, %16, 1, 1, 1, 0;"
                 : ACC8(d, 0), "+f"(d[8]), "+f"(d[9]), "+f"(d[10]), "+f"(d[11]) : "r"(a[0]), "r"(a[1]), "r"(a[2]), "r"(a[3]), "l"(db));
}
template <> DEVI void wgmma_conv<16>(float* d, const uint32_t* a, uint64_t db) {
    asm volatile("wgmma.mma_async.sync.aligned.m64n16k16.f32.bf16.bf16 {%0,%1,%2,%3,%4,%5,%6,%7}, "
                 "{%8,%9,%10,%11}, %12, 1, 1, 1, 0;"
                 : ACC8(d, 0) : "r"(a[0]), "r"(a[1]), "r"(a[2]), "r"(a[3]), "l"(db));
}
template <> DEVI void wgmma_conv<8>(float* d, const uint32_t* a, uint64_t db) {
    asm volatile("wgmma.mma_async.sync.aligned.m64n8k16.f32.bf16.bf16 {%0,%1,%2,%3}, "
                 "{%4,%5,%6,%7}, %8, 1, 1, 1, 0;"
                 : "+f"(d[0]), "+f"(d[1]), "+f"(d[2]), "+f"(d[3]) : "r"(a[0]), "r"(a[1]), "r"(a[2]), "r"(a[3]), "l"(db));
}
DEVI uint32_t lds32(uint32_t a) { uint32_t v; asm volatile("ld.shared.b32 %0, [%1];" : "=r"(v) : "r"(a)); return v; }
DEVI uint32_t lds16(uint32_t a) { uint16_t v; asm volatile("ld.shared.b16 %0, [%1];" : "=h"(v) : "r"(a)); return v; }

template <int J> DEVI void conv_pair(float* acc, uint32_t* f, uint32_t wa, uint64_t du, int c) {
#pragma unroll
    for (int i = 0; i < 8; i++) {
        f[4 * i] = lds32(wa + i * 64); f[4 * i + 1] = lds32(wa + i * 64 + 32);
        f[4 * i + 2] = i ? f[4 * i - 3] : lds32(wa - 32); f[4 * i + 3] = f[4 * i];
    }
    wg_fence();
#pragma unroll
    for (int i = 0; i < 8; i++) {
        const int kk = 3 - (i & 3);
        const uint64_t db = du + (uint64_t)(kk * 2 * (OP_ULD / 16) + (i >> 2) + c);
        wgmma_conv<32 - 8 * J>(acc, f + 4 * i, db);
    }
    wg_commit();
}
template <int J> DEVI void conv_group(float* acc, uint32_t wa, uint64_t du) {
    uint32_t fa[32], fb[32];
#pragma unroll
    for (int h = 0; h < 2; h++) {
        const int c = 8 * J + 4 * h;
        conv_pair<J>(acc, fa, wa + c * 256, du, c);
        wg_wait<1>();
        conv_pair<J>(acc, fb, wa + (c + 2) * 256, du, c + 2);
        wg_wait<1>();
    }
    wg_wait<0>();
}

DEVI void expand_table(int ct, uint32_t sW, uint32_t sK) {
#pragma unroll 1
        for (int qd = ct; qd < WTAB / 4; qd += 384) {
            const int o = qd * 4 - 64;
            uint32_t ka[5];
#pragma unroll
            for (int e = 0; e < 5; e++) ka[e] = sK + 4 * kp_index(max(o - 1 + e, 0));
#pragma unroll
            for (int c = 0; c < 4; c++) {
                float k[5];
#pragma unroll
                for (int e = 0; e < 5; e++) k[e] = o - 1 + e < 0 ? 0.f : __uint_as_float(lds32(ka[e] + c * 648 * 4));
                asm volatile("st.shared.v4.b32 [%0], {%1,%2,%3,%4};" ::"r"(sW + (c * WTAB + qd * 4) * 4), "r"(pack_bf16(k[1], k[0])),
                             "r"(pack_bf16(k[2], k[1])), "r"(pack_bf16(k[3], k[2])), "r"(pack_bf16(k[4], k[3])) : "memory");
            }
        }
}

__global__ void __cluster_dims__(2, 1, 1) __launch_bounds__(512, 1)
outproj_kernel(const __grid_constant__ CUtensorMap tm_ctx, const __grid_constant__ CUtensorMap tm_wo,
               const __grid_constant__ CUtensorMap tm_out, SsmParams sp, bf16* __restrict__ out) {
    extern __shared__ uint8_t smem_raw[];
    const uint32_t sb = (smem_u32(smem_raw) + 1023) & ~1023u;
    const uint32_t sX = sb + OP_NS * 32768, sW = sX + 32768, sU = sW + 4 * WTAB * 4, sK = sU + 4 * OP_UCH, bars = sK + 4 * 648 * 4;
    const uint32_t full = bars, empty = bars + 64, xfull = bars + 128, wfull = bars + 136;
    const int tid = threadIdx.x, warp = tid >> 5, lane = tid & 31, wg = tid >> 7;
    const uint32_t rank = cluster_rank();
    const uint32_t kr = rank;
    const int cl = blockIdx.x >> 1;
    const int m0 = (cl >> 2) * 128, n0 = (cl & 3) * 128, k0 = kr * 2048;
    STAMP(blockIdx.x == 10 && tid == 0, 1000);
    if (tid == 0) {
        for (int i = 0; i < OP_NS; i++) { mbar_init(full + 8 * i, 1); mbar_init(empty + 8 * i, 8); }
        mbar_init(xfull, 1);
        mbar_init(wfull, 1);
        fence_barrier_init();
    }
    for (int i = tid; i < 648; i += 512) asm volatile("st.shared.v4.b32 [%0], {%1,%1,%1,%1};" ::"r"(sK + i * 16), "r"(0) : "memory");
    __syncthreads();
    cluster_sync_all();
    if (wg == 3) {
        reg_dec<40>();
        if (tid == 384) {
            mbar_expect_tx(xfull, 32768);
            for (int it = 0; it < OP_NS; it++) {
                const uint32_t dst = sb + it * 32768, fb = full + 8 * it;
                mbar_expect_tx(fb, 32768);
                tma_load_2d(dst + 16384, &tm_wo, n0, k0 + it * 64, fb);
                tma_load_2d(dst + 24576, &tm_wo, n0 + 64, k0 + it * 64, fb);
            }
            pdl_wait();
            STAMP(blockIdx.x == 10, 1005);
            for (int it = 0; it < 32; it++) {
                const int st = it & (OP_NS - 1);
                const uint32_t dst = sb + st * 32768, fb = full + 8 * st;
                if (it >= OP_NS) {
                    mbar_wait(empty + 8 * st, ((it / OP_NS) & 1) ^ 1);
                    mbar_expect_tx(fb, 32768);
                    tma_load_2d(dst + 16384, &tm_wo, n0, k0 + it * 64, fb);
                    tma_load_2d(dst + 24576, &tm_wo, n0 + 64, k0 + it * 64, fb);
                }
                tma_load_2d(dst, &tm_ctx, k0 + it * 64, m0, fb);
                tma_load_2d(dst + 8192, &tm_ctx, k0 + it * 64, m0 + 64, fb);
            }
        }
        __syncwarp();
    } else if (wg == 2) {
        reg_inc<208>();
        const int ct = tid & 127, wq = warp & 3, g = lane >> 2, t = lane & 3;
        const int d0 = blockIdx.x * 4;
        uint2 v[2][8];
#pragma unroll
        for (int h = 0; h < 2; h++)
#pragma unroll
            for (int i = 0; i < 8; i++)
                v[h][i] = __ldg(reinterpret_cast<const uint2*>(sp.u + (size_t)((ct + 128 * h) * 8 + i) * SSM_D + d0));
        for (int i = ct; i < 4 * 8 * 8; i += 128) {
            const uint32_t a = sU + (i >> 3) * OP_ULD + (32 + (i & 7)) * 16;
            asm volatile("st.shared.v4.b32 [%0], {%1,%1,%1,%1};" ::"r"(a), "r"(0) : "memory");
        }
#pragma unroll
        for (int h = 0; h < 2; h++) {
            const int q = ct + 128 * h;
            const uint32_t a = sU + (q & 7) * OP_ULD + (31 - (q >> 3)) * 16;
#pragma unroll
            for (int c = 0; c < 4; c++) {
                uint32_t w[4];
#pragma unroll
                for (int i = 0; i < 4; i++) {
                    const uint32_t lo = (c & 2) ? v[h][2 * i].y : v[h][2 * i].x, hi = (c & 2) ? v[h][2 * i + 1].y : v[h][2 * i + 1].x;
                    w[i] = __byte_perm(lo, hi, (c & 1) ? 0x7632 : 0x5410);
                }
                asm volatile("st.shared.v4.b32 [%0], {%1,%2,%3,%4};" ::"r"(a + c * OP_UCH), "r"(w[0]), "r"(w[1]), "r"(w[2]), "r"(w[3]) : "memory");
            }
        }
        STAMP(blockIdx.x == 10 && ct == 0, 1001);
        named_sync(3, 384);
        STAMP(blockIdx.x == 10 && ct == 0, 1002);
        expand_table(ct, sW, sK);
        const uint2 dsk = __ldg(reinterpret_cast<const uint2*>(sp.dskip + d0));
        fence_proxy_async();
        named_sync(4, 384);
        uint32_t res[16][2];
        STAMP(blockIdx.x == 10 && ct == 0, 1003);
#pragma unroll 1
        for (int c = 0; c < 4; c++) {
            float acc[16];
#pragma unroll
            for (int i = 0; i < 16; i++) acc[i] = 0.f;
            const uint32_t wa = sW + (c * WTAB + 64 + 16 * (wq - 3) + g - 2 * t) * 4;
            const uint64_t du = make_desc(sU + c * OP_UCH, OP_ULD, 128, 0);
            conv_group<0>(acc, wa, du);
            conv_group<1>(acc, wa, du);
            conv_group<2>(acc, wa, du);
            conv_group<3>(acc, wa, du);
            const uint32_t dw = (c & 2) ? dsk.y : dsk.x;
            const float D = (c & 1) ? bhi(dw) : blo(dw);
#pragma unroll
            for (int i = 0; i < 16; i++) {
                const int n = 8 * (i >> 2) + 2 * t + (i & 1), j = 2 * wq + ((i >> 1) & 1);
                const float u = __uint_as_float(lds16(sU + c * OP_UCH + j * OP_ULD + n * 16 + g * 2) << 16);
                const uint32_t o = __bfloat16_as_ushort(__float2bfloat16_rn(rbf(acc[i]) + rbf(u * D)));
                res[i][0] = __byte_perm(res[i][0], res[i][1], 0x5432); res[i][1] = __byte_perm(res[i][1], o, 0x5432);
            }
        }
        STAMP(blockIdx.x == 10 && ct == 0, 1004);
#pragma unroll
        for (int i = 0; i < 16; i++) {
            const int a = 31 - (8 * (i >> 2) + 2 * t + (i & 1)), b = 16 * wq + g + 8 * ((i >> 1) & 1);
            *reinterpret_cast<uint2*>(out + (size_t)(64 * a + b) * 1024 + 512 + d0) = make_uint2(res[i][0], res[i][1]);
        }
    } else {
        ssm_kgen_warp(sp, blockIdx.x * 4 + (warp & 3), wg, lane, sK + (warp & 3) * 648 * 4);
        named_sync(3, 384);
        expand_table(tid + 128, sW, sK);
        named_arrive(4, 384);
        float acc[64];
#pragma unroll 1
        for (int it = 0; it < 32; it++) {
            const int st = it & (OP_NS - 1);
            mbar_wait(full + 8 * st, (it / OP_NS) & 1);
            STAMP(blockIdx.x == 10 && tid == 0, 1009 + it);
            wg_fence();
            const uint32_t base = sb + st * 32768;
            const uint64_t da = desc_kmajor(base + wg * 8192), db = desc_mnmajor(base + 16384, 8192);
#pragma unroll
            for (int k = 0; k < 4; k++) wgmma_ss128<1>(acc, da + k * 2, db + k * 128, (it | k) != 0);
            wg_commit();
            if (it > 0 && it + OP_NS - 1 < 32) {
                wg_wait<1>();
                if (lane == 0) mbar_arrive(empty + 8 * ((it - 1) & (OP_NS - 1)));
            }
        }
        wg_wait<0>();
        uint32_t peer, pbar;
        asm volatile("mapa.shared::cluster.u32 %0, %1, %2;" : "=r"(peer) : "r"(sX + tid * 16), "r"(rank ^ 1));
        asm volatile("mapa.shared::cluster.u32 %0, %1, %2;" : "=r"(pbar) : "r"(xfull), "r"(rank ^ 1));
#pragma unroll
        for (int i = 0; i < 8; i++) {
            const float* s = acc + 4 * i;
            const float a = kr ? s[0] : s[32], b = kr ? s[1] : s[33], c = kr ? s[2] : s[34], d = kr ? s[3] : s[35];
            asm volatile("st.async.weak.shared::cluster.mbarrier::complete_tx::bytes.v4.f32 [%0], {%1,%2,%3,%4}, [%5];"
                         ::"r"(peer + i * 4096), "f"(a), "f"(b), "f"(c), "f"(d), "r"(pbar) : "memory");
        }
        STAMP(blockIdx.x == 10 && tid == 0, 1006);
        mbar_wait(xfull, 0);
        STAMP(blockIdx.x == 10 && tid == 0, 1007);
        float r[32];
#pragma unroll
        for (int i = 0; i < 8; i++) {
            float a, b, c, d;
            asm volatile("ld.shared.v4.f32 {%0,%1,%2,%3}, [%4];" : "=f"(a), "=f"(b), "=f"(c), "=f"(d) : "r"(sX + tid * 16 + i * 4096));
            const float* s = acc + 4 * i;
            r[4 * i] = a + (kr ? s[32] : s[0]); r[4 * i + 1] = b + (kr ? s[33] : s[1]);
            r[4 * i + 2] = c + (kr ? s[34] : s[2]); r[4 * i + 3] = d + (kr ? s[35] : s[3]);
        }
        const uint32_t stg = sb + wg * 8192;
        store_slab64(stg, (warp & 3) * 16, r, 1.f, 1.f, lane);
        fence_proxy_async();
        named_sync(1 + wg, 128);
        if ((tid & 127) == 0) {
            tma_store_2d(&tm_out, stg, n0 + kr * 64, m0 + wg * 64);
            bulk_commit();
            bulk_wait<0>();
            STAMP(blockIdx.x == 10 && tid == 0, 1008);
        }
    }
}

typedef CUresult (*EncodeFn)(CUtensorMap*, CUtensorMapDataType, cuuint32_t, void*, const cuuint64_t*, const cuuint64_t*,
                             const cuuint32_t*, const cuuint32_t*, CUtensorMapInterleave, CUtensorMapSwizzle,
                             CUtensorMapL2promotion, CUtensorMapFloatOOBfill);

static void make_map(EncodeFn fn, CUtensorMap* m, const void* p, uint64_t cols, uint64_t rows, uint32_t box_rows) {
    cuuint64_t dims[2] = {cols, rows};
    cuuint64_t strides[1] = {cols * 2};
    cuuint32_t box[2] = {64, box_rows};
    cuuint32_t es[2] = {1, 1};
    fn(m, CU_TENSOR_MAP_DATA_TYPE_BFLOAT16, 2, const_cast<void*>(p), dims, strides, box, es, CU_TENSOR_MAP_INTERLEAVE_NONE,
       CU_TENSOR_MAP_SWIZZLE_128B, CU_TENSOR_MAP_L2_PROMOTION_L2_256B, CU_TENSOR_MAP_FLOAT_OOB_FILL_NONE);
}

extern "C" void kernel_launch(void* const* d_in, const int* in_sizes, int n_in, void* d_out, int out_size) {
    void* fp = nullptr;
    cudaDriverEntryPointQueryResult qr;
    cudaGetDriverEntryPoint("cuTensorMapEncodeTiled", &fp, cudaEnableDefault, &qr);
    EncodeFn fn = (EncodeFn)fp;
    void *p_kv, *p_ctx;
    cudaGetSymbolAddress(&p_kv, g_kv);
    cudaGetSymbolAddress(&p_ctx, g_ctx);
    CUtensorMap tm_kv_st, tm_x, tm_c, tm_wq, tm_wk, tm_wv, tm_wo, tm_kv, tm_ctx, tm_out;
    make_map(fn, &tm_x, d_in[0], DM, SEQ, 128);
    make_map(fn, &tm_c, d_in[1], DM, SEQ, 128);
    make_map(fn, &tm_wq, d_in[2], HDALL, DM, 64);
    make_map(fn, &tm_wk, d_in[3], HDALL, DM, 64);
    make_map(fn, &tm_wv, d_in[4], HDALL, DM, 64);
    make_map(fn, &tm_wo, d_in[5], DM, HDALL, 64);
    make_map(fn, &tm_kv, p_kv, 2 * HDALL, SEQ, 128);
    make_map(fn, &tm_kv_st, p_kv, 2 * HDALL, SEQ, 64);
    make_map(fn, &tm_ctx, p_ctx, HDALL, SEQ, 64);
    make_map(fn, &tm_out, d_out, 1024, SEQ, 64);
    SsmParams sp;
    sp.u = (const bf16*)d_in[6]; sp.lar = (const bf16*)d_in[7]; sp.aim = (const bf16*)d_in[8];
    sp.cre = (const bf16*)d_in[9]; sp.cim = (const bf16*)d_in[10]; sp.ldt = (const bf16*)d_in[11]; sp.dskip = (const bf16*)d_in[12];
    cudaFuncSetAttribute(gemm_kv_kernel, cudaFuncAttributeMaxDynamicSharedMemorySize, G1_SMEM);
    cudaFuncSetAttribute(attn_kernel, cudaFuncAttributeMaxDynamicSharedMemorySize, AT_SMEM);
    cudaFuncSetAttribute(outproj_kernel, cudaFuncAttributeMaxDynamicSharedMemorySize, OP_SMEM);
    cudaStream_t st = cudaStreamPerThread;
    gemm_kv_kernel<<<128, G1_THREADS, G1_SMEM, st>>>(tm_c, tm_wk, tm_wv, tm_kv_st, (const bf16*)d_in[0], (const bf16*)d_in[2]);
    cudaLaunchAttribute at[1];
    at[0].id = cudaLaunchAttributeProgrammaticStreamSerialization;
    at[0].val.programmaticStreamSerializationAllowed = 1;
    cudaLaunchConfig_t cfg = {};
    cfg.stream = st; cfg.attrs = at; cfg.numAttrs = 1;
    cfg.gridDim = dim3(132); cfg.blockDim = dim3(384); cfg.dynamicSmemBytes = AT_SMEM;
    cudaLaunchKernelEx(&cfg, attn_kernel, tm_x, tm_wq, tm_kv, tm_ctx, sp.u, (const bf16*)d_in[5]);
    cfg.gridDim = dim3(128); cfg.blockDim = dim3(512); cfg.dynamicSmemBytes = OP_SMEM;
    cudaLaunchKernelEx(&cfg, outproj_kernel, tm_ctx, tm_wo, tm_out, sp, (bf16*)d_out);
}
```

```cpp
#include <cuda_runtime.h>
#include <cuda_bf16.h>
#include <cuda.h>
#include <stdint.h>

typedef __nv_bfloat16 bf16;

#define DEVI __device__ __forceinline__

constexpr int SEQ = 2048, DM = 512, NH = 32, HD = 128, HDALL = NH * HD;
constexpr int SSM_D = 512, SSM_N = 128;
constexpr int WTAB = 2112;

__device__ bf16 g_kv[(size_t)SEQ * 2 * HDALL];
__device__ bf16 g_ctx[(size_t)SEQ * HDALL];
__device__ unsigned int g_sched;

#define STAMP(cond, i)
DEVI uint32_t smem_u32(const void* p) { return (uint32_t)__cvta_generic_to_shared(p); }
DEVI void mbar_init(uint32_t a, uint32_t cnt) { asm volatile("mbarrier.init.shared::cta.b64 [%0], %1;" ::"r"(a), "r"(cnt)); }
DEVI void mbar_expect_tx(uint32_t a, uint32_t bytes) {
    asm volatile("mbarrier.arrive.expect_tx.shared::cta.b64 _, [%0], %1;" ::"r"(a), "r"(bytes) : "memory");
}
DEVI void mbar_arrive(uint32_t a) { asm volatile("mbarrier.arrive.shared::cta.b64 _, [%0];" ::"r"(a) : "memory"); }
DEVI void mbar_arrive_cluster(uint32_t a, uint32_t cta) {
    asm volatile("{\n.reg .b32 r;\nmapa.shared::cluster.u32 r, %0, %1;\n"
                 "mbarrier.arrive.shared::cluster.b64 _, [r];\n}" ::"r"(a), "r"(cta) : "memory");
}
#define MBAR_WAIT_ASM(OP)                                                                              \
    asm volatile("{\n.reg .pred p, q;\n.reg .u32 t0, t1;\n" OP " p, [%0], %1;\n@p bra D_%=;\n"         \
                 "mov.u32 t0, %%globaltimer_lo;\nW_%=:\n" OP " p, [%0], %1;\n"                         \
                 "mov.u32 t1, %%globaltimer_lo;\nsub.u32 t1, t1, t0;\n"                                \
                 "setp.gt.or.u32 q, t1, 4000000, p;\n@!q bra W_%=;\nD_%=:\n}" ::"r"(a), "r"(parity) : "memory")
DEVI void mbar_wait(uint32_t a, uint32_t parity) { MBAR_WAIT_ASM("mbarrier.try_wait.parity.shared::cta.b64"); }
DEVI void mbar_wait_cluster(uint32_t a, uint32_t parity) { MBAR_WAIT_ASM("mbarrier.try_wait.parity.acquire.cluster.shared::cta.b64"); }
DEVI void fence_barrier_init() { asm volatile("fence.mbarrier_init.release.cluster;" ::: "memory"); }
DEVI void fence_proxy_async() { asm volatile("fence.proxy.async.shared::cta;" ::: "memory"); }
DEVI void cluster_sync_all() {
    asm volatile("barrier.cluster.arrive.release.aligned;\nbarrier.cluster.wait.acquire.aligned;" ::: "memory");
}
DEVI uint32_t cluster_rank() { uint32_t r; asm volatile("mov.u32 %0, %%cluster_ctarank;" : "=r"(r)); return r; }
DEVI void tma_load_2d(uint32_t dst, const CUtensorMap* m, int c0, int c1, uint32_t bar) {
    asm volatile("cp.async.bulk.tensor.2d.shared::cluster.global.mbarrier::complete_tx::bytes [%0], [%1, {%3, %4}], [%2];"
                 ::"r"(dst), "l"(m), "r"(bar), "r"(c0), "r"(c1) : "memory");
}
DEVI void tma_load_2d_mc(uint32_t dst, const CUtensorMap* m, int c0, int c1, uint32_t bar, uint16_t mask) {
    asm volatile("cp.async.bulk.tensor.2d.shared::cluster.global.mbarrier::complete_tx::bytes.multicast::cluster [%0], [%1, {%3, %4}], [%2], %5;"
                 ::"r"(dst), "l"(m), "r"(bar), "r"(c0), "r"(c1), "h"(mask) : "memory");
}
DEVI void tma_prefetch_2d(const CUtensorMap* m, int c0, int c1) {
    asm volatile("cp.async.bulk.prefetch.tensor.2d.L2.global [%0, {%1, %2}];" ::"l"(m), "r"(c0), "r"(c1) : "memory");
}
DEVI void tma_store_2d(const CUtensorMap* m, uint32_t src, int c0, int c1) {
    asm volatile("cp.async.bulk.tensor.2d.global.shared::cta.bulk_group [%0, {%2, %3}], [%1];"
                 ::"l"(m), "r"(src), "r"(c0), "r"(c1) : "memory");
}
DEVI void bulk_load(uint32_t dst, const void* src, uint32_t bytes, uint32_t bar) {
    asm volatile("cp.async.bulk.shared::cluster.global.mbarrier::complete_tx::bytes [%0], [%1], %2, [%3];"
                 ::"r"(dst), "l"(src), "r"(bytes), "r"(bar) : "memory");
}
DEVI void bulk_prefetch(const void* src, uint32_t bytes) {
    asm volatile("cp.async.bulk.prefetch.L2.global [%0], %1;" ::"l"(src), "r"(bytes) : "memory");
}
DEVI void bulk_commit() { asm volatile("cp.async.bulk.commit_group;" ::: "memory"); }
template <int N> DEVI void bulk_wait_read() { asm volatile("cp.async.bulk.wait_group.read %0;" ::"n"(N) : "memory"); }
template <int N> DEVI void bulk_wait() { asm volatile("cp.async.bulk.wait_group %0;" ::"n"(N) : "memory"); }
DEVI void prefetch_tmap(const CUtensorMap* m) { asm volatile("prefetch.tensormap [%0];" ::"l"(m) : "memory"); }
DEVI void named_sync(int id, int n) { asm volatile("bar.sync %0, %1;" ::"r"(id), "r"(n) : "memory"); }
DEVI void named_arrive(int id, int n) { asm volatile("bar.arrive %0, %1;" ::"r"(id), "r"(n) : "memory"); }
DEVI void pdl_wait() { asm volatile("griddepcontrol.wait;" ::: "memory"); }
DEVI void pdl_launch() { asm volatile("griddepcontrol.launch_dependents;" ::: "memory"); }
template <int R> DEVI void reg_inc() { asm volatile("setmaxnreg.inc.sync.aligned.u32 %0;" ::"n"(R)); }
template <int R> DEVI void reg_dec() { asm volatile("setmaxnreg.dec.sync.aligned.u32 %0;" ::"n"(R)); }

DEVI void wg_fence() { asm volatile("wgmma.fence.sync.aligned;" ::: "memory"); }
DEVI void wg_commit() { asm volatile("wgmma.commit_group.sync.aligned;" ::: "memory"); }
template <int N> DEVI void wg_wait() { asm volatile("wgmma.wait_group.sync.aligned %0;" ::"n"(N) : "memory"); }

DEVI uint64_t make_desc(uint32_t addr, uint32_t lbo, uint32_t sbo, uint32_t swz) {
    return (uint64_t)((addr & 0x3FFFF) >> 4) | ((uint64_t)(lbo >> 4) << 16) | ((uint64_t)(sbo >> 4) << 32) | ((uint64_t)swz << 62);
}
DEVI uint64_t desc_kmajor(uint32_t addr) { return make_desc(addr, 16, 1024, 1); }
DEVI uint64_t desc_mnmajor(uint32_t addr, uint32_t lbo) { return make_desc(addr, lbo, 1024, 1); }

#define ACC8(d, o) "+f"(d[o + 0]), "+f"(d[o + 1]), "+f"(d[o + 2]), "+f"(d[o + 3]), "+f"(d[o + 4]), "+f"(d[o + 5]), "+f"(d[o + 6]), "+f"(d[o + 7])
#define ACC64(d) ACC8(d, 0), ACC8(d, 8), ACC8(d, 16), ACC8(d, 24), ACC8(d, 32), ACC8(d, 40), ACC8(d, 48), ACC8(d, 56)
#define R64 "{%0,%1,%2,%3,%4,%5,%6,%7,%8,%9,%10,%11,%12,%13,%14,%15,%16,%17,%18,%19,%20,%21,%22,%23,%24,%25,%26,%27,%28,%29,%30,%31," \
            "%32,%33,%34,%35,%36,%37,%38,%39,%40,%41,%42,%43,%44,%45,%46,%47,%48,%49,%50,%51,%52,%53,%54,%55,%56,%57,%58,%59,%60,%61,%62,%63}"

template <int TB> DEVI void wgmma_ss128(float* d, uint64_t da, uint64_t db, int acc) {
    asm volatile("{\n.reg .pred p;\nsetp.ne.b32 p, %66, 0;\n"
                 "wgmma.mma_async.sync.aligned.m64n128k16.f32.bf16.bf16 " R64 ", %64, %65, p, 1, 1, 0, %67;\n}"
                 : ACC64(d) : "l"(da), "l"(db), "r"(acc), "n"(TB));
}
template <int TB> DEVI void wgmma_rs128(float* d, const uint32_t* a, uint64_t db, int acc) {
    asm volatile("{\n.reg .pred p;\nsetp.ne.b32 p, %69, 0;\n"
                 "wgmma.mma_async.sync.aligned.m64n128k16.f32.bf16.bf16 " R64 ", {%64,%65,%66,%67}, %68, p, 1, 1, %70;\n}"
                 : ACC64(d) : "r"(a[0]), "r"(a[1]), "r"(a[2]), "r"(a[3]), "l"(db), "r"(acc), "n"(TB));
}
DEVI uint32_t pack_bf16(float lo, float hi) {
    uint32_t r;
    asm("cvt.rn.bf16x2.f32 %0, %1, %2;" : "=r"(r) : "f"(hi), "f"(lo));
    return r;
}
DEVI void stmatrix_x4(uint32_t addr, uint32_t r0, uint32_t r1, uint32_t r2, uint32_t r3) {
    asm volatile("stmatrix.sync.aligned.m8n8.x4.shared.b16 [%0], {%1,%2,%3,%4};" ::"r"(addr), "r"(r0), "r"(r1), "r"(r2), "r"(r3) : "memory");
}
DEVI float ex2(float x) { float y; asm("ex2.approx.ftz.f32 %0, %1;" : "=f"(y) : "f"(x)); return y; }

DEVI void store_slab64(uint32_t base, int row0, const float* d, float s0, float s1, int lane) {
    int mi = lane >> 3, r = lane & 7;
    int row = row0 + (mi & 1) * 8 + r;
#pragma unroll
    for (int j = 0; j < 8; j += 2) {
        uint32_t r0 = pack_bf16(d[4 * j + 0] * s0, d[4 * j + 1] * s0);
        uint32_t r1 = pack_bf16(d[4 * j + 2] * s1, d[4 * j + 3] * s1);
        uint32_t r2 = pack_bf16(d[4 * j + 4] * s0, d[4 * j + 5] * s0);
        uint32_t r3 = pack_bf16(d[4 * j + 6] * s1, d[4 * j + 7] * s1);
        int chunk = j + (mi >> 1);
        stmatrix_x4(base + row * 128 + ((chunk ^ (row & 7)) << 4), r0, r1, r2, r3);
    }
}
struct cf { float x, y; };
DEVI cf cmul(cf a, cf b) { cf r; r.x = fmaf(a.x, b.x, -a.y * b.y); r.y = fmaf(a.x, b.y, a.y * b.x); return r; }
DEVI cf csq(cf a) { cf r; r.x = fmaf(a.x, a.x, -a.y * a.y); r.y = (a.x + a.x) * a.y; return r; }
DEVI cf cexp_(float re, float im) {
    float m = __expf(re), s, c;
    __sincosf(im, &s, &c);
    cf r; r.x = m * c; r.y = m * s; return r;
}
DEVI uint32_t h2(cf v) { uint32_t r; asm("cvt.rn.f16x2.f32 %0, %1, %2;" : "=r"(r) : "f"(v.y), "f"(v.x)); return r; }
DEVI uint32_t h2c(cf v) { uint32_t r; asm("cvt.rn.f16x2.f32 %0, %1, %2;" : "=r"(r) : "f"(-v.y), "f"(v.x)); return r; }
DEVI void mma_group(float (*c)[4], const uint32_t (*a)[4], const uint32_t (*b)[2]) {
    asm volatile(
        "mma.sync.aligned.m16n8k16.row.col.f32.f16.f16.f32 {%0,%1,%2,%3}, {%20,%21,%22,%23}, {%40,%41}, {%0,%1,%2,%3};\n"
        "mma.sync.aligned.m16n8k16.row.col.f32.f16.f16.f32 {%4,%5,%6,%7}, {%24,%25,%26,%27}, {%40,%41}, {%4,%5,%6,%7};\n"
        "mma.sync.aligned.m16n8k16.row.col.f32.f16.f16.f32 {%8,%9,%10,%11}, {%28,%29,%30,%31}, {%42,%43}, {%8,%9,%10,%11};\n"
        "mma.sync.aligned.m16n8k16.row.col.f32.f16.f16.f32 {%12,%13,%14,%15}, {%32,%33,%34,%35}, {%44,%45}, {%12,%13,%14,%15};\n"
        "mma.sync.aligned.m16n8k16.row.col.f32.f16.f16.f32 {%16,%17,%18,%19}, {%36,%37,%38,%39}, {%46,%47}, {%16,%17,%18,%19};\n"
        : "+f"(c[0][0]), "+f"(c[0][1]), "+f"(c[0][2]), "+f"(c[0][3]), "+f"(c[1][0]), "+f"(c[1][1]), "+f"(c[1][2]), "+f"(c[1][3]),
          "+f"(c[2][0]), "+f"(c[2][1]), "+f"(c[2][2]), "+f"(c[2][3]), "+f"(c[3][0]), "+f"(c[3][1]), "+f"(c[3][2]), "+f"(c[3][3]),
          "+f"(c[4][0]), "+f"(c[4][1]), "+f"(c[4][2]), "+f"(c[4][3])
        : "r"(a[0][0]), "r"(a[0][1]), "r"(a[0][2]), "r"(a[0][3]), "r"(a[1][0]), "r"(a[1][1]), "r"(a[1][2]), "r"(a[1][3]),
          "r"(a[2][0]), "r"(a[2][1]), "r"(a[2][2]), "r"(a[2][3]), "r"(a[3][0]), "r"(a[3][1]), "r"(a[3][2]), "r"(a[3][3]),
          "r"(a[4][0]), "r"(a[4][1]), "r"(a[4][2]), "r"(a[4][3]),
          "r"(b[0][0]), "r"(b[0][1]), "r"(b[1][0]), "r"(b[1][1]), "r"(b[2][0]), "r"(b[2][1]), "r"(b[3][0]), "r"(b[3][1]));
}
DEVI float bf2f(bf16 v) { return __bfloat162float(v); }
DEVI float rbf(float v) { return __bfloat162float(__float2bfloat16_rn(v)); }

struct SsmParams { const bf16 *lar, *aim, *cre, *cim, *ldt, *dskip, *u; };

DEVI int kp_index(int l) {
    int p = (int)rbf((float)l);
    return p < 256 ? p : (p < 512 ? 128 + (p >> 1) : (p < 1024 ? 256 + (p >> 2) : 384 + (p >> 3)));
}

DEVI void reds(uint32_t a, float v) { asm volatile("red.shared.add.f32 [%0], %1;" ::"r"(a), "f"(v) : "memory"); }
DEVI void ssm_kgen_warp(const SsmParams& P, int d, int half, int lane, uint32_t kp) {
    const int g = lane >> 2, t = lane & 3;
    float ar[2], ai[2], cr[2], ci[2], gr[2], gi[2];
    bf16 raw[2][4];
    const bf16 rdt = P.ldt[d];
#pragma unroll
    for (int q = 0; q < 2; q++) {
        const int n = d * SSM_N + 64 * half + 32 * q + lane;
        raw[q][0] = P.lar[n]; raw[q][1] = P.aim[n]; raw[q][2] = P.cre[n]; raw[q][3] = P.cim[n];
    }
    const float dt = rbf(expf(bf2f(rdt)));
#pragma unroll
    for (int q = 0; q < 2; q++) {
        ar[q] = -rbf(expf(bf2f(raw[q][0]))) * dt;
        ai[q] = bf2f(raw[q][1]) * dt;
        cr[q] = 2.f * (bf2f(raw[q][2]) * dt);
        ci[q] = 2.f * (bf2f(raw[q][3]) * dt);
        float m = expf(ar[q] * 64.f), sn, cs;
        sincosf(ai[q] * 64.f, &sn, &cs);
        gr[q] = m * cs; gi[q] = m * sn;
    }
    float cm = 0.f;
#pragma unroll
    for (int q = 0; q < 2; q++) cm = fmaxf(cm, fmaxf(fabsf(cr[q]), fabsf(ci[q])));
#pragma unroll
    for (int o = 16; o; o >>= 1) cm = fmaxf(cm, __shfl_xor_sync(~0u, cm, o));
    const int ex = min(max((int)(__float_as_uint(cm) >> 23), 1), 253);
    const float cs_dn = __uint_as_float((uint32_t)(254 - ex) << 23), cs_up = __uint_as_float((uint32_t)ex << 23);
    float acc[5][4];
#pragma unroll
    for (int s = 0; s < 5; s++) { acc[s][0] = acc[s][1] = acc[s][2] = acc[s][3] = 0.f; }
    float klast = 0.f;
    const float gf = (float)g;
#pragma unroll
    for (int q = 0; q < 2; q++) {
#pragma unroll 1
        for (int g0 = 0; g0 < 8; g0 += 2) {
            uint32_t fa[5][4], fb[4][2];
#pragma unroll
            for (int h = 0; h < 2; h++) {
                const int src = ((g0 + h) << 2) | t;
                const float a_r = __shfl_sync(~0u, ar[q], src), a_i = __shfl_sync(~0u, ai[q], src);
                cf C, G;
                C.x = __shfl_sync(~0u, cr[q], src) * cs_dn; C.y = __shfl_sync(~0u, ci[q], src) * cs_dn;
                G.x = __shfl_sync(~0u, gr[q], src); G.y = __shfl_sync(~0u, gi[q], src);
                cf E = cexp_(a_r * gf, a_i * gf);
                cf B = csq(csq(csq(E)));
                fb[0][h] = h2c(cmul(C, B));
                cf EG = cmul(E, G);
                fa[0][2 * h] = h2(E); fa[0][2 * h + 1] = h2(EG);
                cf G2 = csq(G);
                cf X = cmul(E, G2), Xh = cmul(EG, G2);
                fa[1][2 * h] = h2(X); fa[1][2 * h + 1] = h2(Xh);
#pragma unroll
                for (int s = 2; s < 5; s++) {
                    B = csq(B); X = csq(X); Xh = csq(Xh);
                    fb[s - 1][h] = h2c(cmul(C, B));
                    fa[s][2 * h] = h2(X); fa[s][2 * h + 1] = h2(Xh);
                }
                X = csq(X);
                klast += fmaf(C.x, X.x, -C.y * X.y);
            }
            mma_group(acc, fa, fb);
        }
    }
    klast += __shfl_xor_sync(~0u, klast, 1);
    klast += __shfl_xor_sync(~0u, klast, 2);
#pragma unroll
    for (int s = 0; s < 5; s++) {
        const uint32_t b = kp + (128 * s + g + 16 * t) * 4;
        reds(b, acc[s][0] * cs_up); reds(b + 32, acc[s][1] * cs_up); reds(b + 256, acc[s][2] * cs_up); reds(b + 288, acc[s][3] * cs_up);
    }
    if (lane == 0) reds(kp + 2560, klast * cs_up);
}

constexpr int G1_THREADS = 384;
constexpr int G1_NS = 11;
constexpr int G1_SMEM = G1_NS * 16384 + 32768 + 256 + 1024;

__global__ void __cluster_dims__(2, 1, 1) __launch_bounds__(G1_THREADS, 1)
gemm_kv_kernel(const __grid_constant__ CUtensorMap tm_c, const __grid_constant__ CUtensorMap tm_wk,
               const __grid_constant__ CUtensorMap tm_wv, const __grid_constant__ CUtensorMap tm_kv_st,
               const bf16* __restrict__ px, const bf16* __restrict__ pwq) {
    extern __shared__ uint8_t smem_raw[];
    const uint32_t sb = (smem_u32(smem_raw) + 1023) & ~1023u;
    const uint32_t sC = sb + G1_NS * 16384, bars = sC + 32768;
    const uint32_t full = bars, empty = bars + 128;
    const int tid = threadIdx.x, warp = tid >> 5, lane = tid & 31, wg = tid >> 7;
    const uint32_t rank = cluster_rank();
    const int cl = blockIdx.x >> 1;
    const int m0 = ((cl & 7) * 2 + rank) * 128;
    const int ng = cl >> 3;
    STAMP(blockIdx.x == 10 && tid == 0, 0);
    if (tid == 0) {
        for (int i = 0; i < G1_NS; i++) { mbar_init(full + 8 * i, 1); mbar_init(empty + 8 * i, 16); }
        fence_barrier_init();
        for (int it = 0; it < 8; it++) {
            mbar_expect_tx(full + 8 * it, 16384);
            tma_load_2d(sb + it * 16384, &tm_c, it * 64, m0, full + 8 * it);
        }
    }
    __syncthreads();
    cluster_sync_all();
    pdl_launch();
    if (wg == 2) {
        reg_dec<40>();
        if (tid == 256) {
            const CUtensorMap* tw = ng < 4 ? &tm_wk : &tm_wv;
            const int n0 = (ng & 3) * 1024 + rank * 64;
            int st = 8; uint32_t ph = 1;
            for (int it = 0; it < 64; it++) {
                mbar_wait(empty + 8 * st, ph);
                mbar_expect_tx(full + 8 * st, 16384);
                tma_load_2d_mc(sb + st * 16384 + rank * 8192, tw, n0 + (it >> 3) * 128, (it & 7) * 64, full + 8 * st, 3);
                if (it < 2) {
                    for (int j = 3 + it * 8 + (cl & 7); j < 19; j += 16) tma_prefetch_2d(tw, n0 + (j >> 3) * 128, (j & 7) * 64);
                }
                if (it >= 3 && it + 16 < 64 && (it & 7) == (cl & 7)) tma_prefetch_2d(tw, n0 + ((it + 16) >> 3) * 128, (it & 7) * 64);
                if (it == 24) bulk_prefetch(px + blockIdx.x * 8192, 16384);
                if (it == 32) bulk_prefetch(pwq + blockIdx.x * 16384, 32768);
                if (++st == G1_NS) { st = 0; ph ^= 1; }
            }
        }
        __syncwarp();
    } else {
        reg_inc<232>();
        uint32_t af[128];
        float acc[64];
        const int wq = warp & 3;
        const int row = wg * 64 + wq * 16 + (lane & 15);
        const uint32_t stg = sC + wg * 16384;
        int st = 8, pst = 0; uint32_t ph = 0;
#pragma unroll
        for (int kc = 0; kc < 8; kc++) {
            mbar_wait(full + 8 * kc, 0);
#pragma unroll
            for (int k = 0; k < 4; k++) {
                const uint32_t a = sb + kc * 16384 + row * 128 + (((2 * k + (lane >> 4)) ^ (row & 7)) << 4);
                uint32_t* f = af + kc * 16 + k * 4;
                asm volatile("ldmatrix.sync.aligned.m8n8.x4.shared.b16 {%0,%1,%2,%3}, [%4];"
                             : "=r"(f[0]), "=r"(f[1]), "=r"(f[2]), "=r"(f[3]) : "r"(a) : "memory");
            }
            __syncwarp();
            if (lane < 2) mbar_arrive_cluster(empty + 8 * kc, lane);
        }
#pragma unroll 1
        for (int t = 0; t < 8; t++) {
            if (wg == 1 || t > 0) named_sync(3 + wg, 256);
#pragma unroll
            for (int kc = 0; kc < 8; kc++) {
                mbar_wait(full + 8 * st, ph);
                STAMP(blockIdx.x == 10 && (tid & 127) == 0, 1 + wg * 96 + t * 12 + kc);
                wg_fence();
                const uint64_t db = desc_mnmajor(sb + st * 16384, 8192);
#pragma unroll
                for (int k = 0; k < 4; k++) wgmma_rs128<1>(acc, af + kc * 16 + k * 4, db + k * 128, (kc | k) != 0);
                wg_commit();
                if (kc == 3 && (wg == 0 || t < 7)) named_arrive(3 + (wg ^ 1), 256);
                if (kc > 0) {
                    wg_wait<1>();
                    if (lane < 2) mbar_arrive_cluster(empty + 8 * pst, lane);
                }
                pst = st;
                if (++st == G1_NS) { st = 0; ph ^= 1; }
            }
            if ((tid & 127) == 0) bulk_wait_read<0>();
            named_sync(1 + wg, 128);
            wg_wait<0>();
            STAMP(blockIdx.x == 10 && (tid & 127) == 0, 9 + wg * 96 + t * 12);
            if (lane < 2) mbar_arrive_cluster(empty + 8 * pst, lane);
            store_slab64(stg, wq * 16, acc, 1.f, 1.f, lane);
            store_slab64(stg + 8192, wq * 16, acc + 32, 1.f, 1.f, lane);
            fence_proxy_async();
            named_sync(1 + wg, 128);
            if ((tid & 127) == 0) {
                tma_store_2d(&tm_kv_st, stg, ng * 1024 + t * 128, m0 + wg * 64);
                tma_store_2d(&tm_kv_st, stg + 8192, ng * 1024 + t * 128 + 64, m0 + wg * 64);
                bulk_commit();
            }
            STAMP(blockIdx.x == 10 && (tid & 127) == 0, 10 + wg * 96 + t * 12);
        }
        if ((tid & 127) == 0) bulk_wait<0>();
        __syncwarp();
    }
    asm volatile("barrier.cluster.arrive.relaxed.aligned;\nbarrier.cluster.wait.aligned;" ::: "memory");
}
constexpr int AT_NS = 6;
constexpr int AT_SMEM = AT_NS * 32768 + 32768 + 256 + 1024;
constexpr int AT_ITEMS = 512;

DEVI uint32_t hmax2(uint32_t a, uint32_t b) { uint32_t r; asm("max.bf16x2 %0, %1, %2;" : "=r"(r) : "r"(a), "r"(b)); return r; }
DEVI uint32_t hmul2(uint32_t a, uint32_t b) { uint32_t r; asm("mul.rn.bf16x2 %0, %1, %2;" : "=r"(r) : "r"(a), "r"(b)); return r; }
DEVI uint32_t hfma2(uint32_t a, uint32_t b, uint32_t c) { uint32_t r; asm("fma.rn.bf16x2 %0, %1, %2, %3;" : "=r"(r) : "r"(a), "r"(b), "r"(c)); return r; }
DEVI float blo(uint32_t v) { return __uint_as_float(v << 16); }
DEVI float bhi(uint32_t v) { return __uint_as_float(v & 0xffff0000u); }

template <bool FIRST>
DEVI void softmax_tile(float* s, float& m0, float& m1, float& l0, float& l1, float& al0, float& al1) {
    const uint32_t HI = 0x3DB53DB5u;
    const uint32_t LO = 0x371E371Eu;
    const float L2E = 1.4426950408889634f;
    uint32_t x0 = 0xFF80FF80u, x1 = 0xFF80FF80u;
#pragma unroll
    for (int j = 0; j < 16; j++) {
        uint32_t a = pack_bf16(s[4 * j], s[4 * j + 1]), b = pack_bf16(s[4 * j + 2], s[4 * j + 3]);
        a = hfma2(a, HI, hmul2(a, LO));
        b = hfma2(b, HI, hmul2(b, LO));
        s[4 * j] = __uint_as_float(a); s[4 * j + 2] = __uint_as_float(b);
        x0 = hmax2(x0, a); x1 = hmax2(x1, b);
    }
    uint32_t x = hmax2(__byte_perm(x0, x1, 0x5410), __byte_perm(x0, x1, 0x7632));
    x = hmax2(x, __shfl_xor_sync(~0u, x, 1));
    x = hmax2(x, __shfl_xor_sync(~0u, x, 2));
    float n0 = blo(x), n1 = bhi(x);
    if (!FIRST) {
        n0 = fmaxf(n0, m0); n1 = fmaxf(n1, m1);
        al0 = ex2((m0 - n0) * L2E); al1 = ex2((m1 - n1) * L2E);
    }
    m0 = n0; m1 = n1;
    const float c0 = -n0 * L2E, c1 = -n1 * L2E;
    float s0 = 0.f, s1 = 0.f;
#pragma unroll
    for (int j = 0; j < 16; j++) {
        uint32_t a = __float_as_uint(s[4 * j]), b = __float_as_uint(s[4 * j + 2]);
        float e0 = ex2(fmaf(blo(a), L2E, c0)), e1 = ex2(fmaf(bhi(a), L2E, c0));
        float e2 = ex2(fmaf(blo(b), L2E, c1)), e3 = ex2(fmaf(bhi(b), L2E, c1));
        s0 += e0 + e1; s1 += e2 + e3;
        s[4 * j] = e0; s[4 * j + 1] = e1; s[4 * j + 2] = e2; s[4 * j + 3] = e3;
    }
    if (FIRST) { l0 = s0; l1 = s1; }
    else { l0 = fmaf(l0, al0, s0); l1 = fmaf(l1, al1, s1); }
}

struct Ring {
    int st; uint32_t ph;
    DEVI void next() { if (++st == AT_NS) { st = 0; ph ^= 1; } }
};

__global__ void __launch_bounds__(384, 1)
attn_kernel(const __grid_constant__ CUtensorMap tm_x, const __grid_constant__ CUtensorMap tm_wq,
            const __grid_constant__ CUtensorMap tm_kv, const __grid_constant__ CUtensorMap tm_ctx_st,
            const bf16* __restrict__ pu, const bf16* __restrict__ pwo) {
    extern __shared__ uint8_t smem_raw[];
    const uint32_t sb = (smem_u32(smem_raw) + 1023) & ~1023u;
    const uint32_t sO = sb + AT_NS * 32768, bars = sO + 32768;
    const uint32_t full = bars, empty = bars + 64;
    volatile int* slots = reinterpret_cast<volatile int*>(smem_raw + (bars + 128 - smem_u32(smem_raw)));
    const int tid = threadIdx.x, warp = tid >> 5, lane = tid & 31, wg = tid >> 7;
    if (tid == 0) {
        for (int i = 0; i < AT_NS; i++) { mbar_init(full + 8 * i, 1); mbar_init(empty + 8 * i, 8); }
        fence_barrier_init();
    }
    __syncthreads();
    if (wg == 2) {
        reg_dec<24>();
        if (warp == 8 && lane == 0) {
            Ring r{0, 1};
            int n = 0;
            while (true) {
                int idx = (int)atomicInc(&g_sched, AT_ITEMS + gridDim.x - 1);
                if (idx >= AT_ITEMS - 128 && idx < AT_ITEMS) {
                    bulk_prefetch(pu + (idx - (AT_ITEMS - 128)) * 8192, 16384);
                    bulk_prefetch(pwo + (idx - (AT_ITEMS - 128)) * 16384, 32768);
                }
                mbar_wait(empty + 8 * r.st, r.ph);
                if (idx >= AT_ITEMS) {
                    slots[n & 3] = -1;
                    mbar_arrive(full + 8 * r.st);
                    break;
                }
                slots[n & 3] = idx;
                const int qi = 15 - (idx >> 5), h = idx & 31;
                for (int kc = 0; kc < 8; kc++) {
                    if (kc) mbar_wait(empty + 8 * r.st, r.ph);
                    const uint32_t fb = full + 8 * r.st, dst = sb + r.st * 32768;
                    mbar_expect_tx(fb, 32768);
                    tma_load_2d(dst, &tm_x, kc * 64, qi * 128, fb);
                    tma_load_2d(dst + 16384, &tm_wq, h * 128, kc * 64, fb);
                    tma_load_2d(dst + 24576, &tm_wq, h * 128 + 64, kc * 64, fb);
                    r.next();
                }
                if (n == 0) { pdl_wait(); pdl_launch(); }
                for (int j = qi; j >= -1; j--) {
#pragma unroll
                    for (int v = 0; v < 2; v++) {
                        const int jj = j + v;
                        if (jj < 0 || jj > qi || (v == 0 && j < 0)) continue;
                        mbar_wait(empty + 8 * r.st, r.ph);
                        const uint32_t fb = full + 8 * r.st, dst = sb + r.st * 32768;
                        mbar_expect_tx(fb, 32768);
                        tma_load_2d(dst, &tm_kv, v * HDALL + h * 128, jj * 128, fb);
                        tma_load_2d(dst + 16384, &tm_kv, v * HDALL + h * 128 + 64, jj * 128, fb);
                        r.next();
                    }
                }
                n++;
            }
            if (n == 0) { pdl_wait(); pdl_launch(); }
        }
    } else {
        reg_inc<240>();
        Ring r{0, 0};
        float o[64], s[64];
        uint32_t qf[32], pa[32];
        const int g = lane >> 2, t = lane & 3, wq = warp & 3;
        const uint32_t stg = sO + wg * 16384;
        if (wg == 1) named_arrive(3, 256);
        for (int n = 0;; n++) {
            mbar_wait(full + 8 * r.st, r.ph);
            const int idx = slots[n & 3];
            if (idx < 0) break;
            const int qi = 15 - (idx >> 5), h = idx & 31;
#pragma unroll 1
            for (int kc = 0; kc < 8; kc++) {
                if (kc) mbar_wait(full + 8 * r.st, r.ph);
                wg_fence();
                const uint32_t base = sb + r.st * 32768;
                const uint64_t da = desc_kmajor(base + wg * 8192), db = desc_mnmajor(base + 16384, 8192);
#pragma unroll
                for (int k = 0; k < 4; k++) wgmma_ss128<1>(s, da + k * 2, db + k * 128, (kc | k) != 0);
                wg_commit();
                if (kc) {
                    wg_wait<1>();
                    if (lane == 0) mbar_arrive(empty + 8 * (r.st == 0 ? AT_NS - 1 : r.st - 1));
                }
                r.next();
            }
            wg_wait<0>();
            if (lane == 0) mbar_arrive(empty + 8 * (r.st == 0 ? AT_NS - 1 : r.st - 1));
#pragma unroll
            for (int i = 0; i < 32; i++) qf[i] = pack_bf16(s[2 * i], s[2 * i + 1]);
            float m0, m1, l0, l1, al0, al1;
            auto issue_qk = [&]() {
                mbar_wait(full + 8 * r.st, r.ph);
                wg_fence();
                const uint64_t db = desc_kmajor(sb + r.st * 32768);
#pragma unroll
                for (int k = 0; k < 8; k++) wgmma_rs128<0>(s, qf + 4 * k, db + (k >> 2) * 1024 + (k & 3) * 2, k != 0);
                wg_commit();
            };
            auto issue_pv = [&](const uint32_t* p, int st, uint32_t ph, int acc) {
                mbar_wait(full + 8 * st, ph);
                wg_fence();
                const uint64_t db = desc_mnmajor(sb + st * 32768, 16384);
#pragma unroll
                for (int k = 0; k < 8; k++) wgmma_rs128<1>(o, p + 4 * k, db + k * 128, acc | k);
                wg_commit();
            };
            issue_qk();
            wg_wait<0>();
            if (lane == 0) mbar_arrive(empty + 8 * r.st);
            r.next();
            {
                const int row = wg * 64 + wq * 16 + g;
#pragma unroll
                for (int j = 0; j < 16; j++) {
                    const int c = 8 * j + 2 * t;
                    if (c > row) s[4 * j] = -INFINITY;
                    if (c + 1 > row) s[4 * j + 1] = -INFINITY;
                    if (c > row + 8) s[4 * j + 2] = -INFINITY;
                    if (c + 1 > row + 8) s[4 * j + 3] = -INFINITY;
                }
            }
            softmax_tile<true>(s, m0, m1, l0, l1, al0, al1);
#pragma unroll
            for (int i = 0; i < 32; i++) pa[i] = pack_bf16(s[2 * i], s[2 * i + 1]);
            int first = 0;
#pragma unroll 1
            for (int j = qi; j >= 1; j--) {
                named_sync(3 + wg, 256);
                issue_qk();
                const int kst = r.st;
                r.next();
                issue_pv(pa, r.st, r.ph, first);
                named_arrive(3 + (wg ^ 1), 256);
                wg_wait<1>();
                if (lane == 0) mbar_arrive(empty + 8 * kst);
                softmax_tile<false>(s, m0, m1, l0, l1, al0, al1);
                wg_wait<0>();
                if (lane == 0) mbar_arrive(empty + 8 * r.st);
                r.next();
#pragma unroll
                for (int i = 0; i < 32; i++) pa[i] = pack_bf16(s[2 * i], s[2 * i + 1]);
#pragma unroll
                for (int i = 0; i < 16; i++) {
                    o[4 * i] *= al0; o[4 * i + 1] *= al0; o[4 * i + 2] *= al1; o[4 * i + 3] *= al1;
                }
                first = 1;
            }
            issue_pv(pa, r.st, r.ph, first);
            l0 += __shfl_xor_sync(~0u, l0, 1); l0 += __shfl_xor_sync(~0u, l0, 2);
            l1 += __shfl_xor_sync(~0u, l1, 1); l1 += __shfl_xor_sync(~0u, l1, 2);
            const float i0 = 1.f / l0, i1 = 1.f / l1;
            if ((tid & 127) == 0) bulk_wait_read<0>();
            named_sync(1 + wg, 128);
            wg_wait<0>();
            if (lane == 0) mbar_arrive(empty + 8 * r.st);
            r.next();
            store_slab64(stg, wq * 16, o, i0, i1, lane);
            store_slab64(stg + 8192, wq * 16, o + 32, i0, i1, lane);
            fence_proxy_async();
            named_sync(1 + wg, 128);
            if ((tid & 127) == 0) {
                tma_store_2d(&tm_ctx_st, stg, h * 128, qi * 128 + wg * 64);
                tma_store_2d(&tm_ctx_st, stg + 8192, h * 128 + 64, qi * 128 + wg * 64);
                bulk_commit();
            }
        }
        if ((tid & 127) == 0) bulk_wait<0>();
    }
}
constexpr int OP_NS = 4;
constexpr int OP_ULD = 41 * 16;
constexpr int OP_UCH = 8 * OP_ULD;
constexpr int OP_SMEM = OP_NS * 32768 + 32768 + 4 * WTAB * 4 + 4 * OP_UCH + 4 * 648 * 4 + 256 + 1024;

template <int N> DEVI void wgmma_conv(float* d, const uint32_t* a, uint64_t db);
template <> DEVI void wgmma_conv<32>(float* d, const uint32_t* a, uint64_t db) {
    asm volatile("wgmma.mma_async.sync.aligned.m64n32k16.f32.bf16.bf16 {%0,%1,%2,%3,%4,%5,%6,%7,%8,%9,%10,%11,%12,%13,%14,%15}, "
                 "{%16,%17,%18,%19}, %20, 1, 1, 1, 0;"
                 : ACC8(d, 0), ACC8(d, 8) : "r"(a[0]), "r"(a[1]), "r"(a[2]), "r"(a[3]), "l"(db));
}
template <> DEVI void wgmma_conv<24>(float* d, const uint32_t* a, uint64_t db) {
    asm volatile("wgmma.mma_async.sync.aligned.m64n24k16.f32.bf16.bf16 {%0,%1,%2,%3,%4,%5,%6,%7,%8,%9,%10,%11}, "
                 "{%12,%13,%14,%15}, %16, 1, 1, 1, 0;"
                 : ACC8(d, 0), "+f"(d[8]), "+f"(d[9]), "+f"(d[10]), "+f"(d[11]) : "r"(a[0]), "r"(a[1]), "r"(a[2]), "r"(a[3]), "l"(db));
}
template <> DEVI void wgmma_conv<16>(float* d, const uint32_t* a, uint64_t db) {
    asm volatile("wgmma.mma_async.sync.aligned.m64n16k16.f32.bf16.bf16 {%0,%1,%2,%3,%4,%5,%6,%7}, "
                 "{%8,%9,%10,%11}, %12, 1, 1, 1, 0;"
                 : ACC8(d, 0) : "r"(a[0]), "r"(a[1]), "r"(a[2]), "r"(a[3]), "l"(db));
}
template <> DEVI void wgmma_conv<8>(float* d, const uint32_t* a, uint64_t db) {
    asm volatile("wgmma.mma_async.sync.aligned.m64n8k16.f32.bf16.bf16 {%0,%1,%2,%3}, "
                 "{%4,%5,%6,%7}, %8, 1, 1, 1, 0;"
                 : "+f"(d[0]), "+f"(d[1]), "+f"(d[2]), "+f"(d[3]) : "r"(a[0]), "r"(a[1]), "r"(a[2]), "r"(a[3]), "l"(db));
}
DEVI uint32_t lds32(uint32_t a) { uint32_t v; asm volatile("ld.shared.b32 %0, [%1];" : "=r"(v) : "r"(a)); return v; }
DEVI uint32_t lds16(uint32_t a) { uint16_t v; asm volatile("ld.shared.b16 %0, [%1];" : "=h"(v) : "r"(a)); return v; }

template <int J> DEVI void conv_pair(float* acc, uint32_t* f, uint32_t wa, uint64_t du, int c) {
#pragma unroll
    for (int i = 0; i < 8; i++) {
        f[4 * i] = lds32(wa + i * 64); f[4 * i + 1] = lds32(wa + i * 64 + 32);
        f[4 * i + 2] = i ? f[4 * i - 3] : lds32(wa - 32); f[4 * i + 3] = f[4 * i];
    }
    wg_fence();
#pragma unroll
    for (int i = 0; i < 8; i++) {
        const int kk = 3 - (i & 3);
        const uint64_t db = du + (uint64_t)(kk * 2 * (OP_ULD / 16) + (i >> 2) + c);
        wgmma_conv<32 - 8 * J>(acc, f + 4 * i, db);
    }
    wg_commit();
}
template <int J> DEVI void conv_group(float* acc, uint32_t wa, uint64_t du) {
    uint32_t fa[32], fb[32];
#pragma unroll
    for (int h = 0; h < 2; h++) {
        const int c = 8 * J + 4 * h;
        conv_pair<J>(acc, fa, wa + c * 256, du, c);
        wg_wait<1>();
        conv_pair<J>(acc, fb, wa + (c + 2) * 256, du, c + 2);
        wg_wait<1>();
    }
    wg_wait<0>();
}

DEVI void expand_table(int ct, uint32_t sW, uint32_t sK) {
#pragma unroll 1
    for (int i = ct; i < WTAB; i += 384) {
        const int c = (i >> 3) & 3, qd = (i & 7) | ((i >> 5) << 3);
        float k[5];
#pragma unroll
        for (int e = 0; e < 5; e++) {
            const int l = qd * 4 - 65 + e;
            const int hi = (int)__bfloat16_as_ushort(__float2bfloat16_rn((float)l)) - 17024;
            k[e] = __uint_as_float(lds32(sK + (c * 648 + (l < 0 ? 644 : (l < 128 ? l : hi))) * 4));
        }
        asm volatile("st.shared.v4.b32 [%0], {%1,%2,%3,%4};" ::"r"(sW + (c * WTAB + qd * 4) * 4), "r"(pack_bf16(k[1], k[0])),
                     "r"(pack_bf16(k[2], k[1])), "r"(pack_bf16(k[3], k[2])), "r"(pack_bf16(k[4], k[3])) : "memory");
    }
}

__global__ void __cluster_dims__(2, 1, 1) __launch_bounds__(512, 1)
outproj_kernel(const __grid_constant__ CUtensorMap tm_ctx, const __grid_constant__ CUtensorMap tm_wo,
               const __grid_constant__ CUtensorMap tm_out, const __grid_constant__ CUtensorMap tm_u, SsmParams sp, bf16* __restrict__ out) {
    extern __shared__ uint8_t smem_raw[];
    const uint32_t sb = (smem_u32(smem_raw) + 1023) & ~1023u;
    const uint32_t sX = sb + OP_NS * 32768, sW = sX + 32768, sU = sW + 4 * WTAB * 4, sK = sU + 4 * OP_UCH, bars = sK + 4 * 648 * 4;
    const uint32_t full = bars, empty = bars + 64, xfull = bars + 128, wfull = bars + 136, xfree = bars + 144;
    const int tid = threadIdx.x, warp = tid >> 5, lane = tid & 31, wg = tid >> 7;
    const uint32_t rank = cluster_rank();
    const uint32_t kr = rank;
    const int cl = blockIdx.x >> 1;
    const int m0 = (cl >> 2) * 128, n0 = (cl & 3) * 128, k0 = kr * 2048;
    STAMP(blockIdx.x == 10 && tid == 0, 1000);
    if (tid == 0) {
        for (int i = 0; i < OP_NS; i++) { mbar_init(full + 8 * i, 1); mbar_init(empty + 8 * i, 8); }
        mbar_init(xfull, 1);
        mbar_init(wfull, 1);
        mbar_init(xfree, 1);
        fence_barrier_init();
        mbar_expect_tx(wfull, 32768);
        for (int i = 0; i < 8; i++) tma_load_2d(sX + i * 4096, &tm_u, cl * 8, i * 256, wfull);
    }
    for (int i = tid; i < 648; i += 512) asm volatile("st.shared.v4.b32 [%0], {%1,%1,%1,%1};" ::"r"(sK + i * 16), "r"(0) : "memory");
    __syncthreads();
    cluster_sync_all();
    if (wg == 3) {
        reg_dec<40>();
        if (tid == 384) {
            mbar_expect_tx(xfull, 32768);
            for (int it = 0; it < OP_NS; it++) {
                const uint32_t dst = sb + it * 32768, fb = full + 8 * it;
                mbar_expect_tx(fb, 32768);
                tma_load_2d(dst + 16384, &tm_wo, n0, k0 + it * 64, fb);
                tma_load_2d(dst + 24576, &tm_wo, n0 + 64, k0 + it * 64, fb);
            }
            for (int i = 0; i < 16; i++) bulk_prefetch(out + (size_t)(blockIdx.x * 16 + i) * 1024 + 512, 1024);
            pdl_wait();
            STAMP(blockIdx.x == 10, 1005);
            for (int it = 0; it < 32; it++) {
                const int st = it & (OP_NS - 1);
                const uint32_t dst = sb + st * 32768, fb = full + 8 * st;
                if (it >= OP_NS) {
                    mbar_wait(empty + 8 * st, ((it / OP_NS) & 1) ^ 1);
                    mbar_expect_tx(fb, 32768);
                    tma_load_2d(dst + 16384, &tm_wo, n0, k0 + it * 64, fb);
                    tma_load_2d(dst + 24576, &tm_wo, n0 + 64, k0 + it * 64, fb);
                }
                tma_load_2d(dst, &tm_ctx, k0 + it * 64, m0, fb);
                tma_load_2d(dst + 8192, &tm_ctx, k0 + it * 64, m0 + 64, fb);
            }
        }
        __syncwarp();
    } else {
      const int ct = tid & 127, wq = warp & 3;
      if (wg == 2) {
        for (int i = ct; i < 4 * 8 * 8; i += 128) {
            const uint32_t a = sU + (i >> 3) * OP_ULD + (32 + (i & 7)) * 16;
            asm volatile("st.shared.v4.b32 [%0], {%1,%1,%1,%1};" ::"r"(a), "r"(0) : "memory");
        }
        const bool mine = ((lane >> 2) & 1) == (int)rank;
        const uint32_t ub = sU + (lane & 3) * OP_UCH + ((lane >> 3) + 4 * (wq & 1)) * OP_ULD + (31 - (wq >> 1)) * 16;
        mbar_wait(wfull, 0);
#pragma unroll 4
        for (int i = 0; i < 16; i++) {
            uint32_t r0, r1, r2, r3;
            asm volatile("ldmatrix.sync.aligned.m8n8.x4.trans.shared.b16 {%0,%1,%2,%3}, [%4];"
                         : "=r"(r0), "=r"(r1), "=r"(r2), "=r"(r3) : "r"(sX + (i * 128 + ct) * 16) : "memory");
            asm volatile("stmatrix.sync.aligned.m8n8.x4.shared.b16 [%0], {%1,%2,%3,%4};"
                         ::"r"(mine ? ub - i * 32 : sW + lane * 16), "r"(r0), "r"(r1), "r"(r2), "r"(r3) : "memory");
        }
        fence_proxy_async();
        STAMP(blockIdx.x == 10 && ct == 0, 1001);
      } else {
        ssm_kgen_warp(sp, blockIdx.x * 4 + wq, wg, lane, sK + wq * 648 * 4);
      }
      named_sync(3, 384);
      if (tid == 256) mbar_arrive_cluster(xfree, rank ^ 1);
      STAMP(blockIdx.x == 10 && tid == 257, 1002);
      expand_table(tid, sW, sK);
      if (wg == 2) {
        reg_inc<208>();
        const int g = lane >> 2, t = lane & 3;
        const int d0 = blockIdx.x * 4;
        const uint2 dsk = __ldg(reinterpret_cast<const uint2*>(sp.dskip + d0));
        named_sync(4, 384);
        uint32_t res[16][2];
        STAMP(blockIdx.x == 10 && ct == 0, 1003);
#pragma unroll 1
        for (int c = 0; c < 4; c++) {
            float acc[16];
#pragma unroll
            for (int i = 0; i < 16; i++) acc[i] = 0.f;
            const uint32_t wa = sW + (c * WTAB + 64 + 16 * (wq - 3) + g - 2 * t) * 4;
            const uint64_t du = make_desc(sU + c * OP_UCH, OP_ULD, 128, 0);
            conv_group<0>(acc, wa, du);
            conv_group<1>(acc, wa, du);
            conv_group<2>(acc, wa, du);
            conv_group<3>(acc, wa, du);
            const uint32_t dw = (c & 2) ? dsk.y : dsk.x;
            const float D = (c & 1) ? bhi(dw) : blo(dw);
#pragma unroll
            for (int i = 0; i < 16; i++) {
                const int n = 8 * (i >> 2) + 2 * t + (i & 1), j = 2 * wq + ((i >> 1) & 1);
                const float u = __uint_as_float(lds16(sU + c * OP_UCH + j * OP_ULD + n * 16 + g * 2) << 16);
                const uint32_t o = __bfloat16_as_ushort(__float2bfloat16_rn(rbf(acc[i]) + rbf(u * D)));
                res[i][0] = __byte_perm(res[i][0], res[i][1], 0x5432); res[i][1] = __byte_perm(res[i][1], o, 0x5432);
            }
        }
        STAMP(blockIdx.x == 10 && ct == 0, 1004);
#pragma unroll
        for (int i = 0; i < 16; i++) {
            const int a = 31 - (8 * (i >> 2) + 2 * t + (i & 1)), b = 16 * wq + g + 8 * ((i >> 1) & 1);
            *reinterpret_cast<uint2*>(out + (size_t)(64 * a + b) * 1024 + 512 + d0) = make_uint2(res[i][0], res[i][1]);
        }
      } else {
        named_arrive(4, 384);
        float acc[64];
#pragma unroll 1
        for (int it = 0; it < 32; it++) {
            const int st = it & (OP_NS - 1);
            mbar_wait(full + 8 * st, (it / OP_NS) & 1);
            STAMP(blockIdx.x == 10 && tid == 0, 1009 + it);
            wg_fence();
            const uint32_t base = sb + st * 32768;
            const uint64_t da = desc_kmajor(base + wg * 8192), db = desc_mnmajor(base + 16384, 8192);
#pragma unroll
            for (int k = 0; k < 4; k++) wgmma_ss128<1>(acc, da + k * 2, db + k * 128, (it | k) != 0);
            wg_commit();
            if (it > 0 && it + OP_NS - 1 < 32) {
                wg_wait<1>();
                if (lane == 0) mbar_arrive(empty + 8 * ((it - 1) & (OP_NS - 1)));
            }
        }
        wg_wait<0>();
        mbar_wait(xfree, 0);
        uint32_t peer, pbar;
        asm volatile("mapa.shared::cluster.u32 %0, %1, %2;" : "=r"(peer) : "r"(sX + tid * 16), "r"(rank ^ 1));
        asm volatile("mapa.shared::cluster.u32 %0, %1, %2;" : "=r"(pbar) : "r"(xfull), "r"(rank ^ 1));
#pragma unroll
        for (int i = 0; i < 8; i++) {
            const float* s = acc + 4 * i;
            const float a = kr ? s[0] : s[32], b = kr ? s[1] : s[33], c = kr ? s[2] : s[34], d = kr ? s[3] : s[35];
            asm volatile("st.async.weak.shared::cluster.mbarrier::complete_tx::bytes.v4.f32 [%0], {%1,%2,%3,%4}, [%5];"
                         ::"r"(peer + i * 4096), "f"(a), "f"(b), "f"(c), "f"(d), "r"(pbar) : "memory");
        }
        STAMP(blockIdx.x == 10 && tid == 0, 1006);
        mbar_wait(xfull, 0);
        STAMP(blockIdx.x == 10 && tid == 0, 1007);
        float r[32];
#pragma unroll
        for (int i = 0; i < 8; i++) {
            float a, b, c, d;
            asm volatile("ld.shared.v4.f32 {%0,%1,%2,%3}, [%4];" : "=f"(a), "=f"(b), "=f"(c), "=f"(d) : "r"(sX + tid * 16 + i * 4096));
            const float* s = acc + 4 * i;
            r[4 * i] = a + (kr ? s[32] : s[0]); r[4 * i + 1] = b + (kr ? s[33] : s[1]);
            r[4 * i + 2] = c + (kr ? s[34] : s[2]); r[4 * i + 3] = d + (kr ? s[35] : s[3]);
        }
        const uint32_t stg = sb + wg * 8192;
        store_slab64(stg, (warp & 3) * 16, r, 1.f, 1.f, lane);
        fence_proxy_async();
        named_sync(1 + wg, 128);
        if ((tid & 127) == 0) {
            tma_store_2d(&tm_out, stg, n0 + kr * 64, m0 + wg * 64);
            bulk_commit();
            bulk_wait<0>();
            STAMP(blockIdx.x == 10 && tid == 0, 1008);
        }
      }
    }
}

typedef CUresult (*EncodeFn)(CUtensorMap*, CUtensorMapDataType, cuuint32_t, void*, const cuuint64_t*, const cuuint64_t*,
                             const cuuint32_t*, const cuuint32_t*, CUtensorMapInterleave, CUtensorMapSwizzle,
                             CUtensorMapL2promotion, CUtensorMapFloatOOBfill);

static void make_map(EncodeFn fn, CUtensorMap* m, const void* p, uint64_t cols, uint64_t rows, uint32_t box_rows) {
    cuuint64_t dims[2] = {cols, rows};
    cuuint64_t strides[1] = {cols * 2};
    cuuint32_t box[2] = {64, box_rows};
    cuuint32_t es[2] = {1, 1};
    fn(m, CU_TENSOR_MAP_DATA_TYPE_BFLOAT16, 2, const_cast<void*>(p), dims, strides, box, es, CU_TENSOR_MAP_INTERLEAVE_NONE,
       CU_TENSOR_MAP_SWIZZLE_128B, CU_TENSOR_MAP_L2_PROMOTION_L2_256B, CU_TENSOR_MAP_FLOAT_OOB_FILL_NONE);
}

extern "C" void kernel_launch(void* const* d_in, const int* in_sizes, int n_in, void* d_out, int out_size) {
    void* fp = nullptr;
    cudaDriverEntryPointQueryResult qr;
    cudaGetDriverEntryPoint("cuTensorMapEncodeTiled", &fp, cudaEnableDefault, &qr);
    EncodeFn fn = (EncodeFn)fp;
    void *p_kv, *p_ctx;
    cudaGetSymbolAddress(&p_kv, g_kv);
    cudaGetSymbolAddress(&p_ctx, g_ctx);
    CUtensorMap tm_kv_st, tm_x, tm_c, tm_wq, tm_wk, tm_wv, tm_wo, tm_kv, tm_ctx, tm_out;
    make_map(fn, &tm_x, d_in[0], DM, SEQ, 128);
    make_map(fn, &tm_c, d_in[1], DM, SEQ, 128);
    make_map(fn, &tm_wq, d_in[2], HDALL, DM, 64);
    make_map(fn, &tm_wk, d_in[3], HDALL, DM, 64);
    make_map(fn, &tm_wv, d_in[4], HDALL, DM, 64);
    make_map(fn, &tm_wo, d_in[5], DM, HDALL, 64);
    make_map(fn, &tm_kv, p_kv, 2 * HDALL, SEQ, 128);
    make_map(fn, &tm_kv_st, p_kv, 2 * HDALL, SEQ, 64);
    make_map(fn, &tm_ctx, p_ctx, HDALL, SEQ, 64);
    make_map(fn, &tm_out, d_out, 1024, SEQ, 64);
    CUtensorMap tm_u;
    {
        cuuint64_t dims[2] = {512, 2048}, strides[1] = {1024};
        cuuint32_t box[2] = {8, 256}, es[2] = {1, 1};
        fn(&tm_u, CU_TENSOR_MAP_DATA_TYPE_BFLOAT16, 2, d_in[6], dims, strides, box, es, CU_TENSOR_MAP_INTERLEAVE_NONE,
           CU_TENSOR_MAP_SWIZZLE_NONE, CU_TENSOR_MAP_L2_PROMOTION_NONE, CU_TENSOR_MAP_FLOAT_OOB_FILL_NONE);
    }
    SsmParams sp;
    sp.u = (const bf16*)d_in[6]; sp.lar = (const bf16*)d_in[7]; sp.aim = (const bf16*)d_in[8];
    sp.cre = (const bf16*)d_in[9]; sp.cim = (const bf16*)d_in[10]; sp.ldt = (const bf16*)d_in[11]; sp.dskip = (const bf16*)d_in[12];
    cudaFuncSetAttribute(gemm_kv_kernel, cudaFuncAttributeMaxDynamicSharedMemorySize, G1_SMEM);
    cudaFuncSetAttribute(attn_kernel, cudaFuncAttributeMaxDynamicSharedMemorySize, AT_SMEM);
    cudaFuncSetAttribute(outproj_kernel, cudaFuncAttributeMaxDynamicSharedMemorySize, OP_SMEM);
    cudaStream_t st = cudaStreamPerThread;
    gemm_kv_kernel<<<128, G1_THREADS, G1_SMEM, st>>>(tm_c, tm_wk, tm_wv, tm_kv_st, (const bf16*)d_in[0], (const bf16*)d_in[2]);
    cudaLaunchAttribute at[1];
    at[0].id = cudaLaunchAttributeProgrammaticStreamSerialization;
    at[0].val.programmaticStreamSerializationAllowed = 1;
    cudaLaunchConfig_t cfg = {};
    cfg.stream = st; cfg.attrs = at; cfg.numAttrs = 1;
    cfg.gridDim = dim3(132); cfg.blockDim = dim3(384); cfg.dynamicSmemBytes = AT_SMEM;
    cudaLaunchKernelEx(&cfg, attn_kernel, tm_x, tm_wq, tm_kv, tm_ctx, sp.u, (const bf16*)d_in[5]);
    cfg.gridDim = dim3(128); cfg.blockDim = dim3(512); cfg.dynamicSmemBytes = OP_SMEM;
    cudaLaunchKernelEx(&cfg, outproj_kernel, tm_ctx, tm_wo, tm_out, tm_u, sp, (bf16*)d_out);
}
```

```cpp
#include <cuda_runtime.h>
#include <cuda_bf16.h>
#include <cuda.h>
#include <stdint.h>

typedef __nv_bfloat16 bf16;

#define DEVI __device__ __forceinline__

constexpr int SEQ = 2048, DM = 512, NH = 32, HD = 128, HDALL = NH * HD;
constexpr int SSM_D = 512, SSM_N = 128;
constexpr int WTAB = 2112;

__device__ bf16 g_kv[(size_t)SEQ * 2 * HDALL];
__device__ bf16 g_ctx[(size_t)SEQ * HDALL];
__device__ uint4 g_y[32 * 4 * 4 * 2 * 128];
__device__ unsigned int g_ycnt[32];
__device__ unsigned int g_sched;

#define STAMP(cond, i)
DEVI uint32_t smem_u32(const void* p) { return (uint32_t)__cvta_generic_to_shared(p); }
DEVI void mbar_init(uint32_t a, uint32_t cnt) { asm volatile("mbarrier.init.shared::cta.b64 [%0], %1;" ::"r"(a), "r"(cnt)); }
DEVI void mbar_expect_tx(uint32_t a, uint32_t bytes) {
    asm volatile("mbarrier.arrive.expect_tx.shared::cta.b64 _, [%0], %1;" ::"r"(a), "r"(bytes) : "memory");
}
DEVI void mbar_arrive(uint32_t a) { asm volatile("mbarrier.arrive.shared::cta.b64 _, [%0];" ::"r"(a) : "memory"); }
DEVI void mbar_arrive_cluster(uint32_t a, uint32_t cta) {
    asm volatile("{\n.reg .b32 r;\nmapa.shared::cluster.u32 r, %0, %1;\n"
                 "mbarrier.arrive.shared::cluster.b64 _, [r];\n}" ::"r"(a), "r"(cta) : "memory");
}
#define MBAR_WAIT_ASM(OP)                                                                              \
    asm volatile("{\n.reg .pred p, q;\n.reg .u32 t0, t1;\n" OP " p, [%0], %1;\n@p bra D_%=;\n"         \
                 "mov.u32 t0, %%globaltimer_lo;\nW_%=:\n" OP " p, [%0], %1;\n"                         \
                 "mov.u32 t1, %%globaltimer_lo;\nsub.u32 t1, t1, t0;\n"                                \
                 "setp.gt.or.u32 q, t1, 4000000, p;\n@!q bra W_%=;\nD_%=:\n}" ::"r"(a), "r"(parity) : "memory")
DEVI void mbar_wait(uint32_t a, uint32_t parity) { MBAR_WAIT_ASM("mbarrier.try_wait.parity.shared::cta.b64"); }
DEVI void mbar_wait_cluster(uint32_t a, uint32_t parity) { MBAR_WAIT_ASM("mbarrier.try_wait.parity.acquire.cluster.shared::cta.b64"); }
DEVI void fence_barrier_init() { asm volatile("fence.mbarrier_init.release.cluster;" ::: "memory"); }
DEVI void fence_proxy_async() { asm volatile("fence.proxy.async.shared::cta;" ::: "memory"); }
DEVI void cluster_sync_all() {
    asm volatile("barrier.cluster.arrive.relaxed.aligned;\nbarrier.cluster.wait.aligned;" ::: "memory");
}
DEVI void cluster_arrive() { asm volatile("barrier.cluster.arrive.relaxed.aligned;" ::: "memory"); }
DEVI void cluster_wait() { asm volatile("barrier.cluster.wait.aligned;" ::: "memory"); }
DEVI uint32_t cluster_rank() { uint32_t r; asm volatile("mov.u32 %0, %%cluster_ctarank;" : "=r"(r)); return r; }
DEVI void tma_load_2d(uint32_t dst, const CUtensorMap* m, int c0, int c1, uint32_t bar) {
    asm volatile("cp.async.bulk.tensor.2d.shared::cluster.global.mbarrier::complete_tx::bytes [%0], [%1, {%3, %4}], [%2];"
                 ::"r"(dst), "l"(m), "r"(bar), "r"(c0), "r"(c1) : "memory");
}
DEVI void tma_load_2d_mc(uint32_t dst, const CUtensorMap* m, int c0, int c1, uint32_t bar, uint16_t mask) {
    asm volatile("cp.async.bulk.tensor.2d.shared::cluster.global.mbarrier::complete_tx::bytes.multicast::cluster [%0], [%1, {%3, %4}], [%2], %5;"
                 ::"r"(dst), "l"(m), "r"(bar), "r"(c0), "r"(c1), "h"(mask) : "memory");
}
DEVI void tma_prefetch_2d(const CUtensorMap* m, int c0, int c1) {
    asm volatile("cp.async.bulk.prefetch.tensor.2d.L2.global [%0, {%1, %2}];" ::"l"(m), "r"(c0), "r"(c1) : "memory");
}
DEVI void tma_store_2d(const CUtensorMap* m, uint32_t src, int c0, int c1) {
    asm volatile("cp.async.bulk.tensor.2d.global.shared::cta.bulk_group [%0, {%2, %3}], [%1];"
                 ::"l"(m), "r"(src), "r"(c0), "r"(c1) : "memory");
}
DEVI void bulk_load(uint32_t dst, const void* src, uint32_t bytes, uint32_t bar) {
    asm volatile("cp.async.bulk.shared::cluster.global.mbarrier::complete_tx::bytes [%0], [%1], %2, [%3];"
                 ::"r"(dst), "l"(src), "r"(bytes), "r"(bar) : "memory");
}
DEVI void bulk_prefetch(const void* src, uint32_t bytes) {
    asm volatile("cp.async.bulk.prefetch.L2.global [%0], %1;" ::"l"(src), "r"(bytes) : "memory");
}
DEVI void bulk_commit() { asm volatile("cp.async.bulk.commit_group;" ::: "memory"); }
template <int N> DEVI void bulk_wait_read() { asm volatile("cp.async.bulk.wait_group.read %0;" ::"n"(N) : "memory"); }
template <int N> DEVI void bulk_wait() { asm volatile("cp.async.bulk.wait_group %0;" ::"n"(N) : "memory"); }
DEVI void prefetch_tmap(const CUtensorMap* m) { asm volatile("prefetch.tensormap [%0];" ::"l"(m) : "memory"); }
DEVI void named_sync(int id, int n) { asm volatile("bar.sync %0, %1;" ::"r"(id), "r"(n) : "memory"); }
DEVI void named_arrive(int id, int n) { asm volatile("bar.arrive %0, %1;" ::"r"(id), "r"(n) : "memory"); }
DEVI void pdl_wait() { asm volatile("griddepcontrol.wait;" ::: "memory"); }
DEVI void pdl_launch() { asm volatile("griddepcontrol.launch_dependents;" ::: "memory"); }
template <int R> DEVI void reg_inc() { asm volatile("setmaxnreg.inc.sync.aligned.u32 %0;" ::"n"(R)); }
template <int R> DEVI void reg_dec() { asm volatile("setmaxnreg.dec.sync.aligned.u32 %0;" ::"n"(R)); }

DEVI void wg_fence() { asm volatile("wgmma.fence.sync.aligned;" ::: "memory"); }
DEVI void wg_commit() { asm volatile("wgmma.commit_group.sync.aligned;" ::: "memory"); }
template <int N> DEVI void wg_wait() { asm volatile("wgmma.wait_group.sync.aligned %0;" ::"n"(N) : "memory"); }

DEVI uint64_t make_desc(uint32_t addr, uint32_t lbo, uint32_t sbo, uint32_t swz) {
    return (uint64_t)((addr & 0x3FFFF) >> 4) | ((uint64_t)(lbo >> 4) << 16) | ((uint64_t)(sbo >> 4) << 32) | ((uint64_t)swz << 62);
}
DEVI uint64_t desc_kmajor(uint32_t addr) { return make_desc(addr, 16, 1024, 1); }
DEVI uint64_t desc_mnmajor(uint32_t addr, uint32_t lbo) { return make_desc(addr, lbo, 1024, 1); }

#define ACC8(d, o) "+f"(d[o + 0]), "+f"(d[o + 1]), "+f"(d[o + 2]), "+f"(d[o + 3]), "+f"(d[o + 4]), "+f"(d[o + 5]), "+f"(d[o + 6]), "+f"(d[o + 7])
#define ACC64(d) ACC8(d, 0), ACC8(d, 8), ACC8(d, 16), ACC8(d, 24), ACC8(d, 32), ACC8(d, 40), ACC8(d, 48), ACC8(d, 56)
#define R64 "{%0,%1,%2,%3,%4,%5,%6,%7,%8,%9,%10,%11,%12,%13,%14,%15,%16,%17,%18,%19,%20,%21,%22,%23,%24,%25,%26,%27,%28,%29,%30,%31," \
            "%32,%33,%34,%35,%36,%37,%38,%39,%40,%41,%42,%43,%44,%45,%46,%47,%48,%49,%50,%51,%52,%53,%54,%55,%56,%57,%58,%59,%60,%61,%62,%63}"

template <int TB> DEVI void wgmma_ss128(float* d, uint64_t da, uint64_t db, int acc) {
    asm volatile("{\n.reg .pred p;\nsetp.ne.b32 p, %66, 0;\n"
                 "wgmma.mma_async.sync.aligned.m64n128k16.f32.bf16.bf16 " R64 ", %64, %65, p, 1, 1, 0, %67;\n}"
                 : ACC64(d) : "l"(da), "l"(db), "r"(acc), "n"(TB));
}
template <int TB> DEVI void wgmma_rs128(float* d, const uint32_t* a, uint64_t db, int acc) {
    asm volatile("{\n.reg .pred p;\nsetp.ne.b32 p, %69, 0;\n"
                 "wgmma.mma_async.sync.aligned.m64n128k16.f32.bf16.bf16 " R64 ", {%64,%65,%66,%67}, %68, p, 1, 1, %70;\n}"
                 : ACC64(d) : "r"(a[0]), "r"(a[1]), "r"(a[2]), "r"(a[3]), "l"(db), "r"(acc), "n"(TB));
}
DEVI uint32_t pack_bf16(float lo, float hi) {
    uint32_t r;
    asm("cvt.rn.bf16x2.f32 %0, %1, %2;" : "=r"(r) : "f"(hi), "f"(lo));
    return r;
}
DEVI void stmatrix_x4(uint32_t addr, uint32_t r0, uint32_t r1, uint32_t r2, uint32_t r3) {
    asm volatile("stmatrix.sync.aligned.m8n8.x4.shared.b16 [%0], {%1,%2,%3,%4};" ::"r"(addr), "r"(r0), "r"(r1), "r"(r2), "r"(r3) : "memory");
}
DEVI float ex2(float x) { float y; asm("ex2.approx.ftz.f32 %0, %1;" : "=f"(y) : "f"(x)); return y; }

DEVI void store_slab64(uint32_t base, int row0, const float* d, float s0, float s1, int lane) {
    int mi = lane >> 3, r = lane & 7;
    int row = row0 + (mi & 1) * 8 + r;
#pragma unroll
    for (int j = 0; j < 8; j += 2) {
        uint32_t r0 = pack_bf16(d[4 * j + 0] * s0, d[4 * j + 1] * s0);
        uint32_t r1 = pack_bf16(d[4 * j + 2] * s1, d[4 * j + 3] * s1);
        uint32_t r2 = pack_bf16(d[4 * j + 4] * s0, d[4 * j + 5] * s0);
        uint32_t r3 = pack_bf16(d[4 * j + 6] * s1, d[4 * j + 7] * s1);
        int chunk = j + (mi >> 1);
        stmatrix_x4(base + row * 128 + ((chunk ^ (row & 7)) << 4), r0, r1, r2, r3);
    }
}
struct cf { float x, y; };
DEVI cf cmul(cf a, cf b) { cf r; r.x = fmaf(a.x, b.x, -a.y * b.y); r.y = fmaf(a.x, b.y, a.y * b.x); return r; }
DEVI cf csq(cf a) { cf r; r.x = fmaf(a.x, a.x, -a.y * a.y); r.y = (a.x + a.x) * a.y; return r; }
DEVI cf cexp_(float re, float im) {
    float m = __expf(re), s, c;
    __sincosf(im, &s, &c);
    cf r; r.x = m * c; r.y = m * s; return r;
}
DEVI uint32_t h2(cf v) { uint32_t r; asm("cvt.rn.f16x2.f32 %0, %1, %2;" : "=r"(r) : "f"(v.y), "f"(v.x)); return r; }
DEVI uint32_t h2c(cf v) { uint32_t r; asm("cvt.rn.f16x2.f32 %0, %1, %2;" : "=r"(r) : "f"(-v.y), "f"(v.x)); return r; }
DEVI void mma_group(float (*c)[4], const uint32_t (*a)[4], const uint32_t (*b)[2]) {
    asm volatile(
        "mma.sync.aligned.m16n8k16.row.col.f32.f16.f16.f32 {%0,%1,%2,%3}, {%20,%21,%22,%23}, {%40,%41}, {%0,%1,%2,%3};\n"
        "mma.sync.aligned.m16n8k16.row.col.f32.f16.f16.f32 {%4,%5,%6,%7}, {%24,%25,%26,%27}, {%40,%41}, {%4,%5,%6,%7};\n"
        "mma.sync.aligned.m16n8k16.row.col.f32.f16.f16.f32 {%8,%9,%10,%11}, {%28,%29,%30,%31}, {%42,%43}, {%8,%9,%10,%11};\n"
        "mma.sync.aligned.m16n8k16.row.col.f32.f16.f16.f32 {%12,%13,%14,%15}, {%32,%33,%34,%35}, {%44,%45}, {%12,%13,%14,%15};\n"
        "mma.sync.aligned.m16n8k16.row.col.f32.f16.f16.f32 {%16,%17,%18,%19}, {%36,%37,%38,%39}, {%46,%47}, {%16,%17,%18,%19};\n"
        : "+f"(c[0][0]), "+f"(c[0][1]), "+f"(c[0][2]), "+f"(c[0][3]), "+f"(c[1][0]), "+f"(c[1][1]), "+f"(c[1][2]), "+f"(c[1][3]),
          "+f"(c[2][0]), "+f"(c[2][1]), "+f"(c[2][2]), "+f"(c[2][3]), "+f"(c[3][0]), "+f"(c[3][1]), "+f"(c[3][2]), "+f"(c[3][3]),
          "+f"(c[4][0]), "+f"(c[4][1]), "+f"(c[4][2]), "+f"(c[4][3])
        : "r"(a[0][0]), "r"(a[0][1]), "r"(a[0][2]), "r"(a[0][3]), "r"(a[1][0]), "r"(a[1][1]), "r"(a[1][2]), "r"(a[1][3]),
          "r"(a[2][0]), "r"(a[2][1]), "r"(a[2][2]), "r"(a[2][3]), "r"(a[3][0]), "r"(a[3][1]), "r"(a[3][2]), "r"(a[3][3]),
          "r"(a[4][0]), "r"(a[4][1]), "r"(a[4][2]), "r"(a[4][3]),
          "r"(b[0][0]), "r"(b[0][1]), "r"(b[1][0]), "r"(b[1][1]), "r"(b[2][0]), "r"(b[2][1]), "r"(b[3][0]), "r"(b[3][1]));
}
DEVI float bf2f(bf16 v) { return __bfloat162float(v); }
DEVI float rbf(float v) { return __bfloat162float(__float2bfloat16_rn(v)); }

struct SsmParams { const bf16 *lar, *aim, *cre, *cim, *ldt, *dskip, *u; };

DEVI int kp_index(int l) {
    int p = (int)rbf((float)l);
    return p < 256 ? p : (p < 512 ? 128 + (p >> 1) : (p < 1024 ? 256 + (p >> 2) : 384 + (p >> 3)));
}

DEVI void reds(uint32_t a, float v) { asm volatile("red.shared.add.f32 [%0], %1;" ::"r"(a), "f"(v) : "memory"); }
DEVI void ssm_kgen_warp(const SsmParams& P, int d, int half, int lane, uint32_t kp) {
    const int g = lane >> 2, t = lane & 3;
    float ar[2], ai[2], cr[2], ci[2], gr[2], gi[2];
    bf16 raw[2][4];
    const bf16 rdt = P.ldt[d];
#pragma unroll
    for (int q = 0; q < 2; q++) {
        const int n = d * SSM_N + 64 * half + 32 * q + lane;
        raw[q][0] = P.lar[n]; raw[q][1] = P.aim[n]; raw[q][2] = P.cre[n]; raw[q][3] = P.cim[n];
    }
    const float dt = rbf(expf(bf2f(rdt)));
#pragma unroll
    for (int q = 0; q < 2; q++) {
        ar[q] = -rbf(expf(bf2f(raw[q][0]))) * dt;
        ai[q] = bf2f(raw[q][1]) * dt;
        cr[q] = 2.f * (bf2f(raw[q][2]) * dt);
        ci[q] = 2.f * (bf2f(raw[q][3]) * dt);
        float m = expf(ar[q] * 64.f), sn, cs;
        sincosf(ai[q] * 64.f, &sn, &cs);
        gr[q] = m * cs; gi[q] = m * sn;
    }
    float cm = 0.f;
#pragma unroll
    for (int q = 0; q < 2; q++) cm = fmaxf(cm, fmaxf(fabsf(cr[q]), fabsf(ci[q])));
#pragma unroll
    for (int o = 16; o; o >>= 1) cm = fmaxf(cm, __shfl_xor_sync(~0u, cm, o));
    const int ex = min(max((int)(__float_as_uint(cm) >> 23), 1), 253);
    const float cs_dn = __uint_as_float((uint32_t)(254 - ex) << 23), cs_up = __uint_as_float((uint32_t)ex << 23);
    float acc[5][4];
#pragma unroll
    for (int s = 0; s < 5; s++) { acc[s][0] = acc[s][1] = acc[s][2] = acc[s][3] = 0.f; }
    float klast = 0.f;
    const float gf = (float)g;
#pragma unroll
    for (int q = 0; q < 2; q++) {
#pragma unroll 1
        for (int g0 = 0; g0 < 8; g0 += 2) {
            uint32_t fa[5][4], fb[4][2];
#pragma unroll
            for (int h = 0; h < 2; h++) {
                const int src = ((g0 + h) << 2) | t;
                const float a_r = __shfl_sync(~0u, ar[q], src), a_i = __shfl_sync(~0u, ai[q], src);
                cf C, G;
                C.x = __shfl_sync(~0u, cr[q], src) * cs_dn; C.y = __shfl_sync(~0u, ci[q], src) * cs_dn;
                G.x = __shfl_sync(~0u, gr[q], src); G.y = __shfl_sync(~0u, gi[q], src);
                cf E = cexp_(a_r * gf, a_i * gf);
                cf B = csq(csq(csq(E)));
                fb[0][h] = h2c(cmul(C, B));
                cf EG = cmul(E, G);
                fa[0][2 * h] = h2(E); fa[0][2 * h + 1] = h2(EG);
                cf G2 = csq(G);
                cf X = cmul(E, G2), Xh = cmul(EG, G2);
                fa[1][2 * h] = h2(X); fa[1][2 * h + 1] = h2(Xh);
#pragma unroll
                for (int s = 2; s < 5; s++) {
                    B = csq(B); X = csq(X); Xh = csq(Xh);
                    fb[s - 1][h] = h2c(cmul(C, B));
                    fa[s][2 * h] = h2(X); fa[s][2 * h + 1] = h2(Xh);
                }
                X = csq(X);
                klast += fmaf(C.x, X.x, -C.y * X.y);
            }
            mma_group(acc, fa, fb);
        }
    }
    klast += __shfl_xor_sync(~0u, klast, 1);
    klast += __shfl_xor_sync(~0u, klast, 2);
#pragma unroll
    for (int s = 0; s < 5; s++) {
        const uint32_t b = kp + (128 * s + g + 16 * t) * 4;
        reds(b, acc[s][0] * cs_up); reds(b + 32, acc[s][1] * cs_up); reds(b + 256, acc[s][2] * cs_up); reds(b + 288, acc[s][3] * cs_up);
    }
    if (lane == 0) reds(kp + 2560, klast * cs_up);
}

constexpr int G1_THREADS = 384;
constexpr int G1_NS = 11;
constexpr int G1_SMEM = G1_NS * 16384 + 32768 + 256 + 1024;

__global__ void __cluster_dims__(2, 1, 1) __launch_bounds__(G1_THREADS, 1)
gemm_kv_kernel(const __grid_constant__ CUtensorMap tm_c, const __grid_constant__ CUtensorMap tm_wk,
               const __grid_constant__ CUtensorMap tm_wv, const __grid_constant__ CUtensorMap tm_kv_st,
               const bf16* __restrict__ px, const bf16* __restrict__ pwq) {
    extern __shared__ uint8_t smem_raw[];
    const uint32_t sb = (smem_u32(smem_raw) + 1023) & ~1023u;
    const uint32_t sC = sb + G1_NS * 16384, bars = sC + 32768;
    const uint32_t full = bars, empty = bars + 128;
    const int tid = threadIdx.x, warp = tid >> 5, lane = tid & 31, wg = tid >> 7;
    const uint32_t rank = cluster_rank();
    const int cl = blockIdx.x >> 1;
    const int m0 = ((cl & 7) * 2 + rank) * 128;
    const int ng = cl >> 3;
    STAMP(blockIdx.x == 10 && tid == 0, 0);
    if (tid == 0) {
        for (int i = 0; i < G1_NS; i++) { mbar_init(full + 8 * i, 1); mbar_init(empty + 8 * i, 16); }
        fence_barrier_init();
        for (int it = 0; it < 8; it++) {
            mbar_expect_tx(full + 8 * it, 16384);
            tma_load_2d(sb + it * 16384, &tm_c, it * 64, m0, full + 8 * it);
        }
    }
    __syncthreads();
    cluster_sync_all();
    pdl_launch();
    if (wg == 2) {
        reg_dec<40>();
        if (tid == 256) {
            const CUtensorMap* tw = ng < 4 ? &tm_wk : &tm_wv;
            const int n0 = (ng & 3) * 1024 + rank * 64;
            int st = 8; uint32_t ph = 1;
            for (int it = 0; it < 64; it++) {
                mbar_wait(empty + 8 * st, ph);
                mbar_expect_tx(full + 8 * st, 16384);
                tma_load_2d_mc(sb + st * 16384 + rank * 8192, tw, n0 + (it >> 3) * 128, (it & 7) * 64, full + 8 * st, 3);
                if (it < 2) {
                    for (int j = 3 + it * 8 + (cl & 7); j < 19; j += 16) tma_prefetch_2d(tw, n0 + (j >> 3) * 128, (j & 7) * 64);
                }
                if (it >= 3 && it + 16 < 64 && (it & 7) == (cl & 7)) tma_prefetch_2d(tw, n0 + ((it + 16) >> 3) * 128, (it & 7) * 64);
                if (it == 24) bulk_prefetch(px + blockIdx.x * 8192, 16384);
                if (it == 32) bulk_prefetch(pwq + blockIdx.x * 16384, 32768);
                if (++st == G1_NS) { st = 0; ph ^= 1; }
            }
        }
        __syncwarp();
    } else {
        reg_inc<232>();
        uint32_t af[128];
        float acc[64];
        const int wq = warp & 3;
        const int row = wg * 64 + wq * 16 + (lane & 15);
        const uint32_t stg = sC + wg * 16384;
        int st = 8, pst = 0; uint32_t ph = 0;
#pragma unroll
        for (int kc = 0; kc < 8; kc++) {
            mbar_wait(full + 8 * kc, 0);
#pragma unroll
            for (int k = 0; k < 4; k++) {
                const uint32_t a = sb + kc * 16384 + row * 128 + (((2 * k + (lane >> 4)) ^ (row & 7)) << 4);
                uint32_t* f = af + kc * 16 + k * 4;
                asm volatile("ldmatrix.sync.aligned.m8n8.x4.shared.b16 {%0,%1,%2,%3}, [%4];"
                             : "=r"(f[0]), "=r"(f[1]), "=r"(f[2]), "=r"(f[3]) : "r"(a) : "memory");
            }
            __syncwarp();
            if (lane < 2) mbar_arrive_cluster(empty + 8 * kc, lane);
        }
#pragma unroll 1
        for (int t = 0; t < 8; t++) {
            if (wg == 1 || t > 0) named_sync(3 + wg, 256);
#pragma unroll
            for (int kc = 0; kc < 8; kc++) {
                mbar_wait(full + 8 * st, ph);
                STAMP(blockIdx.x == 10 && (tid & 127) == 0, 1 + wg * 96 + t * 12 + kc);
                wg_fence();
                const uint64_t db = desc_mnmajor(sb + st * 16384, 8192);
#pragma unroll
                for (int k = 0; k < 4; k++) wgmma_rs128<1>(acc, af + kc * 16 + k * 4, db + k * 128, (kc | k) != 0);
                wg_commit();
                if (kc == 3 && (wg == 0 || t < 7)) named_arrive(3 + (wg ^ 1), 256);
                if (kc > 0) {
                    wg_wait<1>();
                    if (lane < 2) mbar_arrive_cluster(empty + 8 * pst, lane);
                }
                pst = st;
                if (++st == G1_NS) { st = 0; ph ^= 1; }
            }
            if ((tid & 127) == 0) bulk_wait_read<0>();
            named_sync(1 + wg, 128);
            wg_wait<0>();
            STAMP(blockIdx.x == 10 && (tid & 127) == 0, 9 + wg * 96 + t * 12);
            if (lane < 2) mbar_arrive_cluster(empty + 8 * pst, lane);
            store_slab64(stg, wq * 16, acc, 1.f, 1.f, lane);
            store_slab64(stg + 8192, wq * 16, acc + 32, 1.f, 1.f, lane);
            fence_proxy_async();
            named_sync(1 + wg, 128);
            if ((tid & 127) == 0) {
                tma_store_2d(&tm_kv_st, stg, ng * 1024 + t * 128, m0 + wg * 64);
                tma_store_2d(&tm_kv_st, stg + 8192, ng * 1024 + t * 128 + 64, m0 + wg * 64);
                bulk_commit();
            }
            STAMP(blockIdx.x == 10 && (tid & 127) == 0, 10 + wg * 96 + t * 12);
        }
        if ((tid & 127) == 0) bulk_wait<0>();
        __syncwarp();
    }
    asm volatile("barrier.cluster.arrive.relaxed.aligned;\nbarrier.cluster.wait.aligned;" ::: "memory");
}
constexpr int AT_NS = 6;
constexpr int AT_SMEM = AT_NS * 32768 + 32768 + 256 + 1024;
constexpr int AT_ITEMS = 512;

DEVI uint32_t hmax2(uint32_t a, uint32_t b) { uint32_t r; asm("max.bf16x2 %0, %1, %2;" : "=r"(r) : "r"(a), "r"(b)); return r; }
DEVI uint32_t hmul2(uint32_t a, uint32_t b) { uint32_t r; asm("mul.rn.bf16x2 %0, %1, %2;" : "=r"(r) : "r"(a), "r"(b)); return r; }
DEVI uint32_t hfma2(uint32_t a, uint32_t b, uint32_t c) { uint32_t r; asm("fma.rn.bf16x2 %0, %1, %2, %3;" : "=r"(r) : "r"(a), "r"(b), "r"(c)); return r; }
DEVI float blo(uint32_t v) { return __uint_as_float(v << 16); }
DEVI float bhi(uint32_t v) { return __uint_as_float(v & 0xffff0000u); }

template <bool FIRST>
DEVI void softmax_tile(float* s, float& m0, float& m1, float& l0, float& l1, float& al0, float& al1) {
    const uint32_t HI = 0x3DB53DB5u;
    const uint32_t LO = 0x371E371Eu;
    const float L2E = 1.4426950408889634f;
    uint32_t x0 = 0xFF80FF80u, x1 = 0xFF80FF80u;
#pragma unroll
    for (int j = 0; j < 16; j++) {
        uint32_t a = pack_bf16(s[4 * j], s[4 * j + 1]), b = pack_bf16(s[4 * j + 2], s[4 * j + 3]);
        a = hfma2(a, HI, hmul2(a, LO));
        b = hfma2(b, HI, hmul2(b, LO));
        s[4 * j] = __uint_as_float(a); s[4 * j + 2] = __uint_as_float(b);
        x0 = hmax2(x0, a); x1 = hmax2(x1, b);
    }
    uint32_t x = hmax2(__byte_perm(x0, x1, 0x5410), __byte_perm(x0, x1, 0x7632));
    x = hmax2(x, __shfl_xor_sync(~0u, x, 1));
    x = hmax2(x, __shfl_xor_sync(~0u, x, 2));
    float n0 = blo(x), n1 = bhi(x);
    if (!FIRST) {
        n0 = fmaxf(n0, m0); n1 = fmaxf(n1, m1);
        al0 = ex2((m0 - n0) * L2E); al1 = ex2((m1 - n1) * L2E);
    }
    m0 = n0; m1 = n1;
    const float c0 = -n0 * L2E, c1 = -n1 * L2E;
    float s0 = 0.f, s1 = 0.f;
#pragma unroll
    for (int j = 0; j < 16; j++) {
        uint32_t a = __float_as_uint(s[4 * j]), b = __float_as_uint(s[4 * j + 2]);
        float e0 = ex2(fmaf(blo(a), L2E, c0)), e1 = ex2(fmaf(bhi(a), L2E, c0));
        float e2 = ex2(fmaf(blo(b), L2E, c1)), e3 = ex2(fmaf(bhi(b), L2E, c1));
        s0 += e0 + e1; s1 += e2 + e3;
        s[4 * j] = e0; s[4 * j + 1] = e1; s[4 * j + 2] = e2; s[4 * j + 3] = e3;
    }
    if (FIRST) { l0 = s0; l1 = s1; }
    else { l0 = fmaf(l0, al0, s0); l1 = fmaf(l1, al1, s1); }
}

struct Ring {
    int st; uint32_t ph;
    DEVI void next() { if (++st == AT_NS) { st = 0; ph ^= 1; } }
};

__global__ void __launch_bounds__(384, 1)
attn_kernel(const __grid_constant__ CUtensorMap tm_x, const __grid_constant__ CUtensorMap tm_wq,
            const __grid_constant__ CUtensorMap tm_kv, const __grid_constant__ CUtensorMap tm_ctx_st,
            const bf16* __restrict__ pu, const bf16* __restrict__ pwo) {
    extern __shared__ uint8_t smem_raw[];
    const uint32_t sb = (smem_u32(smem_raw) + 1023) & ~1023u;
    const uint32_t sO = sb + AT_NS * 32768, bars = sO + 32768;
    const uint32_t full = bars, empty = bars + 64;
    volatile int* slots = reinterpret_cast<volatile int*>(smem_raw + (bars + 128 - smem_u32(smem_raw)));
    const int tid = threadIdx.x, warp = tid >> 5, lane = tid & 31, wg = tid >> 7;
    if (tid == 0) {
        for (int i = 0; i < AT_NS; i++) { mbar_init(full + 8 * i, 1); mbar_init(empty + 8 * i, 8); }
        fence_barrier_init();
    }
    __syncthreads();
    if (wg == 2) {
        reg_dec<24>();
        if (warp == 8 && lane == 0) {
            Ring r{0, 1};
            int n = 0;
            while (true) {
                int idx = (int)atomicInc(&g_sched, AT_ITEMS + gridDim.x - 1);
                if (idx >= AT_ITEMS - 128 && idx < AT_ITEMS) {
                    bulk_prefetch(pu + (idx - (AT_ITEMS - 128)) * 8192, 16384);
                    bulk_prefetch(pwo + (idx - (AT_ITEMS - 128)) * 16384, 32768);
                }
                mbar_wait(empty + 8 * r.st, r.ph);
                if (idx >= AT_ITEMS) {
                    slots[n & 3] = -1;
                    mbar_arrive(full + 8 * r.st);
                    break;
                }
                slots[n & 3] = idx;
                const int qi = 15 - (idx >> 5), h = idx & 31;
                for (int kc = 0; kc < 8; kc++) {
                    if (kc) mbar_wait(empty + 8 * r.st, r.ph);
                    const uint32_t fb = full + 8 * r.st, dst = sb + r.st * 32768;
                    mbar_expect_tx(fb, 32768);
                    tma_load_2d(dst, &tm_x, kc * 64, qi * 128, fb);
                    tma_load_2d(dst + 16384, &tm_wq, h * 128, kc * 64, fb);
                    tma_load_2d(dst + 24576, &tm_wq, h * 128 + 64, kc * 64, fb);
                    r.next();
                }
                if (n == 0) { pdl_wait(); pdl_launch(); }
                for (int j = qi; j >= -1; j--) {
#pragma unroll
                    for (int v = 0; v < 2; v++) {
                        const int jj = j + v;
                        if (jj < 0 || jj > qi || (v == 0 && j < 0)) continue;
                        mbar_wait(empty + 8 * r.st, r.ph);
                        const uint32_t fb = full + 8 * r.st, dst = sb + r.st * 32768;
                        mbar_expect_tx(fb, 32768);
                        tma_load_2d(dst, &tm_kv, v * HDALL + h * 128, jj * 128, fb);
                        tma_load_2d(dst + 16384, &tm_kv, v * HDALL + h * 128 + 64, jj * 128, fb);
                        r.next();
                    }
                }
                n++;
            }
            if (n == 0) { pdl_wait(); pdl_launch(); }
        }
    } else {
        reg_inc<240>();
        Ring r{0, 0};
        float o[64], s[64];
        uint32_t qf[32], pa[32];
        const int g = lane >> 2, t = lane & 3, wq = warp & 3;
        const uint32_t stg = sO + wg * 16384;
        if (wg == 1) named_arrive(3, 256);
        for (int n = 0;; n++) {
            mbar_wait(full + 8 * r.st, r.ph);
            const int idx = slots[n & 3];
            if (idx < 0) break;
            const int qi = 15 - (idx >> 5), h = idx & 31;
#pragma unroll 1
            for (int kc = 0; kc < 8; kc++) {
                if (kc) mbar_wait(full + 8 * r.st, r.ph);
                wg_fence();
                const uint32_t base = sb + r.st * 32768;
                const uint64_t da = desc_kmajor(base + wg * 8192), db = desc_mnmajor(base + 16384, 8192);
#pragma unroll
                for (int k = 0; k < 4; k++) wgmma_ss128<1>(s, da + k * 2, db + k * 128, (kc | k) != 0);
                wg_commit();
                if (kc) {
                    wg_wait<1>();
                    if (lane == 0) mbar_arrive(empty + 8 * (r.st == 0 ? AT_NS - 1 : r.st - 1));
                }
                r.next();
            }
            wg_wait<0>();
            if (lane == 0) mbar_arrive(empty + 8 * (r.st == 0 ? AT_NS - 1 : r.st - 1));
#pragma unroll
            for (int i = 0; i < 32; i++) qf[i] = pack_bf16(s[2 * i], s[2 * i + 1]);
            float m0, m1, l0, l1, al0, al1;
            auto issue_qk = [&]() {
                mbar_wait(full + 8 * r.st, r.ph);
                wg_fence();
                const uint64_t db = desc_kmajor(sb + r.st * 32768);
#pragma unroll
                for (int k = 0; k < 8; k++) wgmma_rs128<0>(s, qf + 4 * k, db + (k >> 2) * 1024 + (k & 3) * 2, k != 0);
                wg_commit();
            };
            auto issue_pv = [&](const uint32_t* p, int st, uint32_t ph, int acc) {
                mbar_wait(full + 8 * st, ph);
                wg_fence();
                const uint64_t db = desc_mnmajor(sb + st * 32768, 16384);
#pragma unroll
                for (int k = 0; k < 8; k++) wgmma_rs128<1>(o, p + 4 * k, db + k * 128, acc | k);
                wg_commit();
            };
            issue_qk();
            wg_wait<0>();
            if (lane == 0) mbar_arrive(empty + 8 * r.st);
            r.next();
            {
                const int row = wg * 64 + wq * 16 + g;
#pragma unroll
                for (int j = 0; j < 16; j++) {
                    const int c = 8 * j + 2 * t;
                    if (c > row) s[4 * j] = -INFINITY;
                    if (c + 1 > row) s[4 * j + 1] = -INFINITY;
                    if (c > row + 8) s[4 * j + 2] = -INFINITY;
                    if (c + 1 > row + 8) s[4 * j + 3] = -INFINITY;
                }
            }
            softmax_tile<true>(s, m0, m1, l0, l1, al0, al1);
#pragma unroll
            for (int i = 0; i < 32; i++) pa[i] = pack_bf16(s[2 * i], s[2 * i + 1]);
            int first = 0;
#pragma unroll 1
            for (int j = qi; j >= 1; j--) {
                named_sync(3 + wg, 256);
                issue_qk();
                const int kst = r.st;
                r.next();
                issue_pv(pa, r.st, r.ph, first);
                named_arrive(3 + (wg ^ 1), 256);
                wg_wait<1>();
                if (lane == 0) mbar_arrive(empty + 8 * kst);
                softmax_tile<false>(s, m0, m1, l0, l1, al0, al1);
                wg_wait<0>();
                if (lane == 0) mbar_arrive(empty + 8 * r.st);
                r.next();
#pragma unroll
                for (int i = 0; i < 32; i++) pa[i] = pack_bf16(s[2 * i], s[2 * i + 1]);
#pragma unroll
                for (int i = 0; i < 16; i++) {
                    o[4 * i] *= al0; o[4 * i + 1] *= al0; o[4 * i + 2] *= al1; o[4 * i + 3] *= al1;
                }
                first = 1;
            }
            issue_pv(pa, r.st, r.ph, first);
            l0 += __shfl_xor_sync(~0u, l0, 1); l0 += __shfl_xor_sync(~0u, l0, 2);
            l1 += __shfl_xor_sync(~0u, l1, 1); l1 += __shfl_xor_sync(~0u, l1, 2);
            const float i0 = 1.f / l0, i1 = 1.f / l1;
            if ((tid & 127) == 0) bulk_wait_read<0>();
            named_sync(1 + wg, 128);
            wg_wait<0>();
            if (lane == 0) mbar_arrive(empty + 8 * r.st);
            r.next();
            store_slab64(stg, wq * 16, o, i0, i1, lane);
            store_slab64(stg + 8192, wq * 16, o + 32, i0, i1, lane);
            fence_proxy_async();
            named_sync(1 + wg, 128);
            if ((tid & 127) == 0) {
                tma_store_2d(&tm_ctx_st, stg, h * 128, qi * 128 + wg * 64);
                tma_store_2d(&tm_ctx_st, stg + 8192, h * 128 + 64, qi * 128 + wg * 64);
                bulk_commit();
            }
        }
        if ((tid & 127) == 0) bulk_wait<0>();
    }
}
constexpr int OP_NS = 4;
constexpr int OP_ULD = 41 * 16;
constexpr int OP_UCH = 8 * OP_ULD;
constexpr int OP_SMEM = OP_NS * 32768 + 32768 + 4 * WTAB * 4 + 4 * OP_UCH + 4 * 648 * 4 + 256 + 1024;

template <int N> DEVI void wgmma_conv(float* d, const uint32_t* a, uint64_t db);
template <> DEVI void wgmma_conv<32>(float* d, const uint32_t* a, uint64_t db) {
    asm volatile("wgmma.mma_async.sync.aligned.m64n32k16.f32.bf16.bf16 {%0,%1,%2,%3,%4,%5,%6,%7,%8,%9,%10,%11,%12,%13,%14,%15}, "
                 "{%16,%17,%18,%19}, %20, 1, 1, 1, 0;"
                 : ACC8(d, 0), ACC8(d, 8) : "r"(a[0]), "r"(a[1]), "r"(a[2]), "r"(a[3]), "l"(db));
}
template <> DEVI void wgmma_conv<24>(float* d, const uint32_t* a, uint64_t db) {
    asm volatile("wgmma.mma_async.sync.aligned.m64n24k16.f32.bf16.bf16 {%0,%1,%2,%3,%4,%5,%6,%7,%8,%9,%10,%11}, "
                 "{%12,%13,%14,%15}, %16, 1, 1, 1, 0;"
                 : ACC8(d, 0), "+f"(d[8]), "+f"(d[9]), "+f"(d[10]), "+f"(d[11]) : "r"(a[0]), "r"(a[1]), "r"(a[2]), "r"(a[3]), "l"(db));
}
template <> DEVI void wgmma_conv<16>(float* d, const uint32_t* a, uint64_t db) {
    asm volatile("wgmma.mma_async.sync.aligned.m64n16k16.f32.bf16.bf16 {%0,%1,%2,%3,%4,%5,%6,%7}, "
                 "{%8,%9,%10,%11}, %12, 1, 1, 1, 0;"
                 : ACC8(d, 0) : "r"(a[0]), "r"(a[1]), "r"(a[2]), "r"(a[3]), "l"(db));
}
template <> DEVI void wgmma_conv<8>(float* d, const uint32_t* a, uint64_t db) {
    asm volatile("wgmma.mma_async.sync.aligned.m64n8k16.f32.bf16.bf16 {%0,%1,%2,%3}, "
                 "{%4,%5,%6,%7}, %8, 1, 1, 1, 0;"
                 : "+f"(d[0]), "+f"(d[1]), "+f"(d[2]), "+f"(d[3]) : "r"(a[0]), "r"(a[1]), "r"(a[2]), "r"(a[3]), "l"(db));
}
DEVI uint32_t lds32(uint32_t a) { uint32_t v; asm volatile("ld.shared.b32 %0, [%1];" : "=r"(v) : "r"(a)); return v; }
DEVI uint32_t lds16(uint32_t a) { uint16_t v; asm volatile("ld.shared.b16 %0, [%1];" : "=h"(v) : "r"(a)); return v; }

template <int J> DEVI void conv_pair(float* acc, uint32_t* f, uint32_t wa, uint64_t du, int c) {
#pragma unroll
    for (int i = 0; i < 8; i++) {
        f[4 * i] = lds32(wa + i * 64); f[4 * i + 1] = lds32(wa + i * 64 + 32);
        f[4 * i + 2] = i ? f[4 * i - 3] : lds32(wa - 32); f[4 * i + 3] = f[4 * i];
    }
    wg_fence();
#pragma unroll
    for (int i = 0; i < 8; i++) {
        const int kk = 3 - (i & 3);
        const uint64_t db = du + (uint64_t)(kk * 2 * (OP_ULD / 16) + (i >> 2) + c);
        wgmma_conv<32 - 8 * J>(acc, f + 4 * i, db);
    }
    wg_commit();
}
template <int J> DEVI void conv_group(float* acc, uint32_t wa, uint64_t du) {
    uint32_t fa[32], fb[32];
#pragma unroll
    for (int h = 0; h < 2; h++) {
        const int c = 8 * J + 4 * h;
        conv_pair<J>(acc, fa, wa + c * 256, du, c);
        wg_wait<1>();
        conv_pair<J>(acc, fb, wa + (c + 2) * 256, du, c + 2);
        wg_wait<1>();
    }
    wg_wait<0>();
}

DEVI void expand_table(int ct, uint32_t sW, uint32_t sK) {
#pragma unroll 1
    for (int i = ct; i < WTAB; i += 384) {
        const int c = (i >> 3) & 3, qd = (i & 7) | ((i >> 5) << 3);
        float k[5];
#pragma unroll
        for (int e = 0; e < 5; e++) {
            const int l = qd * 4 - 65 + e;
            const int hi = (int)__bfloat16_as_ushort(__float2bfloat16_rn((float)l)) - 17024;
            k[e] = __uint_as_float(lds32(sK + (c * 648 + (l < 0 ? 644 : (l < 128 ? l : hi))) * 4));
        }
        asm volatile("st.shared.v4.b32 [%0], {%1,%2,%3,%4};" ::"r"(sW + (c * WTAB + qd * 4) * 4), "r"(pack_bf16(k[1], k[0])),
                     "r"(pack_bf16(k[2], k[1])), "r"(pack_bf16(k[3], k[2])), "r"(pack_bf16(k[4], k[3])) : "memory");
    }
}

__global__ void __cluster_dims__(2, 1, 1) __launch_bounds__(512, 1)
outproj_kernel(const __grid_constant__ CUtensorMap tm_ctx, const __grid_constant__ CUtensorMap tm_wo,
               const __grid_constant__ CUtensorMap tm_out, const __grid_constant__ CUtensorMap tm_u, SsmParams sp, bf16* __restrict__ out) {
    extern __shared__ uint8_t smem_raw[];
    const uint32_t sb = (smem_u32(smem_raw) + 1023) & ~1023u;
    const uint32_t sX = sb + OP_NS * 32768, sW = sX + 32768, sU = sW + 4 * WTAB * 4, sK = sU + 4 * OP_UCH, bars = sK + 4 * 648 * 4;
    const uint32_t full = bars, empty = bars + 64, xfull = bars + 128, wfull = bars + 136, xfree = bars + 144;
    const int tid = threadIdx.x, warp = tid >> 5, lane = tid & 31, wg = tid >> 7;
    const uint32_t rank = cluster_rank();
    const uint32_t kr = rank;
    const int cl = blockIdx.x >> 1;
    const int m0 = (cl >> 2) * 128, n0 = (cl & 3) * 128, k0 = kr * 2048;
    STAMP(blockIdx.x == 10 && tid == 0, 1000);
    if (tid == 0) {
        for (int i = 0; i < OP_NS; i++) { mbar_init(full + 8 * i, 1); mbar_init(empty + 8 * i, 8); }
        mbar_init(xfull, 1);
        mbar_init(wfull, 1);
        mbar_init(xfree, 1);
        fence_barrier_init();
        mbar_expect_tx(wfull, 32768);
        for (int i = 0; i < 8; i++) tma_load_2d(sX + i * 4096, &tm_u, cl * 8, i * 256, wfull);
    }
    for (int i = tid; i < 648; i += 512) asm volatile("st.shared.v4.b32 [%0], {%1,%1,%1,%1};" ::"r"(sK + i * 16), "r"(0) : "memory");
    __syncthreads();
    cluster_arrive();
    if (wg == 3) {
        reg_dec<40>();
        cluster_wait();
        if (tid == 384) {
            mbar_expect_tx(xfull, 32768);
            for (int it = 0; it < OP_NS; it++) {
                const uint32_t dst = sb + it * 32768, fb = full + 8 * it;
                mbar_expect_tx(fb, 32768);
                tma_load_2d(dst + 16384, &tm_wo, n0, k0 + it * 64, fb);
                tma_load_2d(dst + 24576, &tm_wo, n0 + 64, k0 + it * 64, fb);
            }
            pdl_wait();
            STAMP(blockIdx.x == 10, 1005);
            for (int it = 0; it < 32; it++) {
                const int st = it & (OP_NS - 1);
                const uint32_t dst = sb + st * 32768, fb = full + 8 * st;
                if (it >= OP_NS) {
                    mbar_wait(empty + 8 * st, ((it / OP_NS) & 1) ^ 1);
                    mbar_expect_tx(fb, 32768);
                    tma_load_2d(dst + 16384, &tm_wo, n0, k0 + it * 64, fb);
                    tma_load_2d(dst + 24576, &tm_wo, n0 + 64, k0 + it * 64, fb);
                }
                tma_load_2d(dst, &tm_ctx, k0 + it * 64, m0, fb);
                tma_load_2d(dst + 8192, &tm_ctx, k0 + it * 64, m0 + 64, fb);
            }
        }
        __syncwarp();
    } else {
      const int ct = tid & 127, wq = warp & 3;
      if (wg == 2) {
        for (int i = ct; i < 4 * 8 * 8; i += 128) {
            const uint32_t a = sU + (i >> 3) * OP_ULD + (32 + (i & 7)) * 16;
            asm volatile("st.shared.v4.b32 [%0], {%1,%1,%1,%1};" ::"r"(a), "r"(0) : "memory");
        }
        const bool mine = ((lane >> 2) & 1) == (int)rank;
        const uint32_t ub = sU + (lane & 3) * OP_UCH + ((lane >> 3) + 4 * (wq & 1)) * OP_ULD + (31 - (wq >> 1)) * 16;
        mbar_wait(wfull, 0);
#pragma unroll 4
        for (int i = 0; i < 16; i++) {
            uint32_t r0, r1, r2, r3;
            asm volatile("ldmatrix.sync.aligned.m8n8.x4.trans.shared.b16 {%0,%1,%2,%3}, [%4];"
                         : "=r"(r0), "=r"(r1), "=r"(r2), "=r"(r3) : "r"(sX + (i * 128 + ct) * 16) : "memory");
            asm volatile("stmatrix.sync.aligned.m8n8.x4.shared.b16 [%0], {%1,%2,%3,%4};"
                         ::"r"(mine ? ub - i * 32 : sW + lane * 16), "r"(r0), "r"(r1), "r"(r2), "r"(r3) : "memory");
        }
        fence_proxy_async();
        STAMP(blockIdx.x == 10 && ct == 0, 1001);
      } else {
        ssm_kgen_warp(sp, blockIdx.x * 4 + wq, wg, lane, sK + wq * 648 * 4);
      }
      cluster_wait();
      named_sync(3, 384);
      if (tid == 256) mbar_arrive_cluster(xfree, rank ^ 1);
      STAMP(blockIdx.x == 10 && tid == 257, 1002);
      expand_table(tid, sW, sK);
      if (wg == 2) {
        reg_inc<208>();
        const int g = lane >> 2, t = lane & 3;
        const int d0 = blockIdx.x * 4;
        const uint2 dsk = __ldg(reinterpret_cast<const uint2*>(sp.dskip + d0));
        named_sync(4, 384);
        uint32_t res[16][2];
        STAMP(blockIdx.x == 10 && ct == 0, 1003);
#pragma unroll 1
        for (int c = 0; c < 4; c++) {
            float acc[16];
#pragma unroll
            for (int i = 0; i < 16; i++) acc[i] = 0.f;
            const uint32_t wa = sW + (c * WTAB + 64 + 16 * (wq - 3) + g - 2 * t) * 4;
            const uint64_t du = make_desc(sU + c * OP_UCH, OP_ULD, 128, 0);
            conv_group<0>(acc, wa, du);
            conv_group<1>(acc, wa, du);
            conv_group<2>(acc, wa, du);
            conv_group<3>(acc, wa, du);
            const uint32_t dw = (c & 2) ? dsk.y : dsk.x;
            const float D = (c & 1) ? bhi(dw) : blo(dw);
#pragma unroll
            for (int i = 0; i < 16; i++) {
                const int n = 8 * (i >> 2) + 2 * t + (i & 1), j = 2 * wq + ((i >> 1) & 1);
                const float u = __uint_as_float(lds16(sU + c * OP_UCH + j * OP_ULD + n * 16 + g * 2) << 16);
                const uint32_t o = __bfloat16_as_ushort(__float2bfloat16_rn(rbf(acc[i]) + rbf(u * D)));
                res[i][0] = __byte_perm(res[i][0], res[i][1], 0x5432); res[i][1] = __byte_perm(res[i][1], o, 0x5432);
            }
        }
        STAMP(blockIdx.x == 10 && ct == 0, 1004);
        const int grp = blockIdx.x >> 2, me = blockIdx.x & 3;
#pragma unroll
        for (int i = 0; i < 8; i++)
            __stcg(g_y + (((grp * 4 + (i >> 1)) * 4 + me) * 2 + (i & 1)) * 128 + ct,
                   make_uint4(res[2 * i][0], res[2 * i][1], res[2 * i + 1][0], res[2 * i + 1][1]));
        named_sync(5, 128);
        if (ct == 0) {
            __threadfence();
            const unsigned int target = (atomicAdd(g_ycnt + grp, 1u) & ~3u) + 4u;
            uint32_t t0, t1, v;
            asm volatile("mov.u32 %0, %%globaltimer_lo;" : "=r"(t0));
            do {
                asm volatile("ld.acquire.gpu.global.u32 %0, [%1];" : "=r"(v) : "l"(g_ycnt + grp) : "memory");
                asm volatile("mov.u32 %0, %%globaltimer_lo;" : "=r"(t1));
            } while ((int)(v - target) < 0 && t1 - t0 < 4000000u);
        }
        named_sync(5, 128);
        uint4 y[8];
#pragma unroll
        for (int i = 0; i < 8; i++)
            y[i] = __ldcg(g_y + ((blockIdx.x * 4 + 2 * (t & 1) + ((i >> 1) & 1)) * 2 + (i & 1)) * 128 + (ct & ~1) + (i >> 2));
#pragma unroll
        for (int i = 0; i < 8; i++) {
            const int a = 31 - (8 * me + 2 * ((t & 2) + (i >> 2)) + (i & 1)), b = 16 * wq + g + 8 * ((i >> 1) & 1);
            const uint4 p = y[(i & 4) + ((i >> 1) & 1)], q = y[(i & 4) + 2 + ((i >> 1) & 1)];
            *reinterpret_cast<uint4*>(out + (size_t)(64 * a + b) * 1024 + 512 + grp * 16 + (t & 1) * 8) =
                (i & 1) ? make_uint4(p.z, p.w, q.z, q.w) : make_uint4(p.x, p.y, q.x, q.y);
        }
      } else {
        named_arrive(4, 384);
        float acc[64];
#pragma unroll 1
        for (int it = 0; it < 32; it++) {
            const int st = it & (OP_NS - 1);
            mbar_wait(full + 8 * st, (it / OP_NS) & 1);
            STAMP(blockIdx.x == 10 && tid == 0, 1009 + it);
            wg_fence();
            const uint32_t base = sb + st * 32768;
            const uint64_t da = desc_kmajor(base + wg * 8192), db = desc_mnmajor(base + 16384, 8192);
#pragma unroll
            for (int k = 0; k < 4; k++) wgmma_ss128<1>(acc, da + k * 2, db + k * 128, (it | k) != 0);
            wg_commit();
            if (it > 0 && it + OP_NS - 1 < 32) {
                wg_wait<1>();
                if (lane == 0) mbar_arrive(empty + 8 * ((it - 1) & (OP_NS - 1)));
            }
        }
        wg_wait<0>();
        mbar_wait(xfree, 0);
        uint32_t peer, pbar;
        asm volatile("mapa.shared::cluster.u32 %0, %1, %2;" : "=r"(peer) : "r"(sX + tid * 16), "r"(rank ^ 1));
        asm volatile("mapa.shared::cluster.u32 %0, %1, %2;" : "=r"(pbar) : "r"(xfull), "r"(rank ^ 1));
#pragma unroll
        for (int i = 0; i < 8; i++) {
            const float* s = acc + 4 * i;
            const float a = kr ? s[0] : s[32], b = kr ? s[1] : s[33], c = kr ? s[2] : s[34], d = kr ? s[3] : s[35];
            asm volatile("st.async.weak.shared::cluster.mbarrier::complete_tx::bytes.v4.f32 [%0], {%1,%2,%3,%4}, [%5];"
                         ::"r"(peer + i * 4096), "f"(a), "f"(b), "f"(c), "f"(d), "r"(pbar) : "memory");
        }
        STAMP(blockIdx.x == 10 && tid == 0, 1006);
        mbar_wait(xfull, 0);
        STAMP(blockIdx.x == 10 && tid == 0, 1007);
        float r[32];
#pragma unroll
        for (int i = 0; i < 8; i++) {
            float a, b, c, d;
            asm volatile("ld.shared.v4.f32 {%0,%1,%2,%3}, [%4];" : "=f"(a), "=f"(b), "=f"(c), "=f"(d) : "r"(sX + tid * 16 + i * 4096));
            const float* s = acc + 4 * i;
            r[4 * i] = a + (kr ? s[32] : s[0]); r[4 * i + 1] = b + (kr ? s[33] : s[1]);
            r[4 * i + 2] = c + (kr ? s[34] : s[2]); r[4 * i + 3] = d + (kr ? s[35] : s[3]);
        }
        const uint32_t stg = sb + wg * 8192;
        store_slab64(stg, (warp & 3) * 16, r, 1.f, 1.f, lane);
        fence_proxy_async();
        named_sync(1 + wg, 128);
        if ((tid & 127) == 0) {
            tma_store_2d(&tm_out, stg, n0 + kr * 64, m0 + wg * 64);
            bulk_commit();
            bulk_wait<0>();
            STAMP(blockIdx.x == 10 && tid == 0, 1008);
        }
      }
    }
}

typedef CUresult (*EncodeFn)(CUtensorMap*, CUtensorMapDataType, cuuint32_t, void*, const cuuint64_t*, const cuuint64_t*,
                             const cuuint32_t*, const cuuint32_t*, CUtensorMapInterleave, CUtensorMapSwizzle,
                             CUtensorMapL2promotion, CUtensorMapFloatOOBfill);

static void make_map(EncodeFn fn, CUtensorMap* m, const void* p, uint64_t cols, uint64_t rows, uint32_t box_rows) {
    cuuint64_t dims[2] = {cols, rows};
    cuuint64_t strides[1] = {cols * 2};
    cuuint32_t box[2] = {64, box_rows};
    cuuint32_t es[2] = {1, 1};
    fn(m, CU_TENSOR_MAP_DATA_TYPE_BFLOAT16, 2, const_cast<void*>(p), dims, strides, box, es, CU_TENSOR_MAP_INTERLEAVE_NONE,
       CU_TENSOR_MAP_SWIZZLE_128B, CU_TENSOR_MAP_L2_PROMOTION_L2_256B, CU_TENSOR_MAP_FLOAT_OOB_FILL_NONE);
}

extern "C" void kernel_launch(void* const* d_in, const int* in_sizes, int n_in, void* d_out, int out_size) {
    void* fp = nullptr;
    cudaDriverEntryPointQueryResult qr;
    cudaGetDriverEntryPoint("cuTensorMapEncodeTiled", &fp, cudaEnableDefault, &qr);
    EncodeFn fn = (EncodeFn)fp;
    void *p_kv, *p_ctx;
    cudaGetSymbolAddress(&p_kv, g_kv);
    cudaGetSymbolAddress(&p_ctx, g_ctx);
    CUtensorMap tm_kv_st, tm_x, tm_c, tm_wq, tm_wk, tm_wv, tm_wo, tm_kv, tm_ctx, tm_out;
    make_map(fn, &tm_x, d_in[0], DM, SEQ, 128);
    make_map(fn, &tm_c, d_in[1], DM, SEQ, 128);
    make_map(fn, &tm_wq, d_in[2], HDALL, DM, 64);
    make_map(fn, &tm_wk, d_in[3], HDALL, DM, 64);
    make_map(fn, &tm_wv, d_in[4], HDALL, DM, 64);
    make_map(fn, &tm_wo, d_in[5], DM, HDALL, 64);
    make_map(fn, &tm_kv, p_kv, 2 * HDALL, SEQ, 128);
    make_map(fn, &tm_kv_st, p_kv, 2 * HDALL, SEQ, 64);
    make_map(fn, &tm_ctx, p_ctx, HDALL, SEQ, 64);
    make_map(fn, &tm_out, d_out, 1024, SEQ, 64);
    CUtensorMap tm_u;
    {
        cuuint64_t dims[2] = {512, 2048}, strides[1] = {1024};
        cuuint32_t box[2] = {8, 256}, es[2] = {1, 1};
        fn(&tm_u, CU_TENSOR_MAP_DATA_TYPE_BFLOAT16, 2, d_in[6], dims, strides, box, es, CU_TENSOR_MAP_INTERLEAVE_NONE,
           CU_TENSOR_MAP_SWIZZLE_NONE, CU_TENSOR_MAP_L2_PROMOTION_NONE, CU_TENSOR_MAP_FLOAT_OOB_FILL_NONE);
    }
    SsmParams sp;
    sp.u = (const bf16*)d_in[6]; sp.lar = (const bf16*)d_in[7]; sp.aim = (const bf16*)d_in[8];
    sp.cre = (const bf16*)d_in[9]; sp.cim = (const bf16*)d_in[10]; sp.ldt = (const bf16*)d_in[11]; sp.dskip = (const bf16*)d_in[12];
    cudaFuncSetAttribute(gemm_kv_kernel, cudaFuncAttributeMaxDynamicSharedMemorySize, G1_SMEM);
    cudaFuncSetAttribute(attn_kernel, cudaFuncAttributeMaxDynamicSharedMemorySize, AT_SMEM);
    cudaFuncSetAttribute(outproj_kernel, cudaFuncAttributeMaxDynamicSharedMemorySize, OP_SMEM);
    cudaStream_t st = cudaStreamPerThread;
    gemm_kv_kernel<<<128, G1_THREADS, G1_SMEM, st>>>(tm_c, tm_wk, tm_wv, tm_kv_st, (const bf16*)d_in[0], (const bf16*)d_in[2]);
    cudaLaunchAttribute at[1];
    at[0].id = cudaLaunchAttributeProgrammaticStreamSerialization;
    at[0].val.programmaticStreamSerializationAllowed = 1;
    cudaLaunchConfig_t cfg = {};
    cfg.stream = st; cfg.attrs = at; cfg.numAttrs = 1;
    cfg.gridDim = dim3(132); cfg.blockDim = dim3(384); cfg.dynamicSmemBytes = AT_SMEM;
    cudaLaunchKernelEx(&cfg, attn_kernel, tm_x, tm_wq, tm_kv, tm_ctx, sp.u, (const bf16*)d_in[5]);
    cfg.gridDim = dim3(128); cfg.blockDim = dim3(512); cfg.dynamicSmemBytes = OP_SMEM;
    cudaLaunchKernelEx(&cfg, outproj_kernel, tm_ctx, tm_wo, tm_out, tm_u, sp, (bf16*)d_out);
}
```

```cpp
#include <cuda_runtime.h>
#include <cuda_bf16.h>
#include <cuda.h>
#include <stdint.h>

typedef __nv_bfloat16 bf16;

#define DEVI __device__ __forceinline__

constexpr int SEQ = 2048, DM = 512, NH = 32, HD = 128, HDALL = NH * HD;
constexpr int SSM_D = 512, SSM_N = 128;
constexpr int WTAB = 2112;

__device__ bf16 g_kv[(size_t)SEQ * 2 * HDALL];
__device__ bf16 g_ctx[(size_t)SEQ * HDALL];
__device__ uint4 g_y[32 * 4 * 4 * 2 * 128];
__device__ unsigned int g_ycnt[32];
__device__ unsigned int g_sched;

#define STAMP(cond, i)
DEVI uint32_t smem_u32(const void* p) { return (uint32_t)__cvta_generic_to_shared(p); }
DEVI void mbar_init(uint32_t a, uint32_t cnt) { asm volatile("mbarrier.init.shared::cta.b64 [%0], %1;" ::"r"(a), "r"(cnt)); }
DEVI void mbar_expect_tx(uint32_t a, uint32_t bytes) {
    asm volatile("mbarrier.arrive.expect_tx.shared::cta.b64 _, [%0], %1;" ::"r"(a), "r"(bytes) : "memory");
}
DEVI void mbar_arrive(uint32_t a) { asm volatile("mbarrier.arrive.shared::cta.b64 _, [%0];" ::"r"(a) : "memory"); }
DEVI void mbar_arrive_cluster(uint32_t a, uint32_t cta) {
    asm volatile("{\n.reg .b32 r;\nmapa.shared::cluster.u32 r, %0, %1;\n"
                 "mbarrier.arrive.shared::cluster.b64 _, [r];\n}" ::"r"(a), "r"(cta) : "memory");
}
#define MBAR_WAIT_ASM(OP)                                                                              \
    asm volatile("{\n.reg .pred p, q;\n.reg .u32 t0, t1;\n" OP " p, [%0], %1;\n@p bra D_%=;\n"         \
                 "mov.u32 t0, %%globaltimer_lo;\nW_%=:\n" OP " p, [%0], %1;\n"                         \
                 "mov.u32 t1, %%globaltimer_lo;\nsub.u32 t1, t1, t0;\n"                                \
                 "setp.gt.or.u32 q, t1, 4000000, p;\n@!q bra W_%=;\nD_%=:\n}" ::"r"(a), "r"(parity) : "memory")
DEVI void mbar_wait(uint32_t a, uint32_t parity) { MBAR_WAIT_ASM("mbarrier.try_wait.parity.shared::cta.b64"); }
DEVI void mbar_wait_cluster(uint32_t a, uint32_t parity) { MBAR_WAIT_ASM("mbarrier.try_wait.parity.acquire.cluster.shared::cta.b64"); }
DEVI void fence_barrier_init() { asm volatile("fence.mbarrier_init.release.cluster;" ::: "memory"); }
DEVI void fence_proxy_async() { asm volatile("fence.proxy.async.shared::cta;" ::: "memory"); }
DEVI void cluster_sync_all() {
    asm volatile("barrier.cluster.arrive.relaxed.aligned;\nbarrier.cluster.wait.aligned;" ::: "memory");
}
DEVI void cluster_arrive() { asm volatile("barrier.cluster.arrive.relaxed.aligned;" ::: "memory"); }
DEVI void cluster_wait() { asm volatile("barrier.cluster.wait.aligned;" ::: "memory"); }
DEVI uint32_t cluster_rank() { uint32_t r; asm volatile("mov.u32 %0, %%cluster_ctarank;" : "=r"(r)); return r; }
DEVI void tma_load_2d(uint32_t dst, const CUtensorMap* m, int c0, int c1, uint32_t bar) {
    asm volatile("cp.async.bulk.tensor.2d.shared::cluster.global.mbarrier::complete_tx::bytes [%0], [%1, {%3, %4}], [%2];"
                 ::"r"(dst), "l"(m), "r"(bar), "r"(c0), "r"(c1) : "memory");
}
DEVI void tma_load_2d_mc(uint32_t dst, const CUtensorMap* m, int c0, int c1, uint32_t bar, uint16_t mask) {
    asm volatile("cp.async.bulk.tensor.2d.shared::cluster.global.mbarrier::complete_tx::bytes.multicast::cluster [%0], [%1, {%3, %4}], [%2], %5;"
                 ::"r"(dst), "l"(m), "r"(bar), "r"(c0), "r"(c1), "h"(mask) : "memory");
}
DEVI void tma_prefetch_2d(const CUtensorMap* m, int c0, int c1) {
    asm volatile("cp.async.bulk.prefetch.tensor.2d.L2.global [%0, {%1, %2}];" ::"l"(m), "r"(c0), "r"(c1) : "memory");
}
DEVI void tma_store_2d(const CUtensorMap* m, uint32_t src, int c0, int c1) {
    asm volatile("cp.async.bulk.tensor.2d.global.shared::cta.bulk_group [%0, {%2, %3}], [%1];"
                 ::"l"(m), "r"(src), "r"(c0), "r"(c1) : "memory");
}
DEVI void bulk_load(uint32_t dst, const void* src, uint32_t bytes, uint32_t bar) {
    asm volatile("cp.async.bulk.shared::cluster.global.mbarrier::complete_tx::bytes [%0], [%1], %2, [%3];"
                 ::"r"(dst), "l"(src), "r"(bytes), "r"(bar) : "memory");
}
DEVI void bulk_prefetch(const void* src, uint32_t bytes) {
    asm volatile("cp.async.bulk.prefetch.L2.global [%0], %1;" ::"l"(src), "r"(bytes) : "memory");
}
DEVI void bulk_commit() { asm volatile("cp.async.bulk.commit_group;" ::: "memory"); }
template <int N> DEVI void bulk_wait_read() { asm volatile("cp.async.bulk.wait_group.read %0;" ::"n"(N) : "memory"); }
template <int N> DEVI void bulk_wait() { asm volatile("cp.async.bulk.wait_group %0;" ::"n"(N) : "memory"); }
DEVI void prefetch_tmap(const CUtensorMap* m) { asm volatile("prefetch.tensormap [%0];" ::"l"(m) : "memory"); }
DEVI void named_sync(int id, int n) { asm volatile("bar.sync %0, %1;" ::"r"(id), "r"(n) : "memory"); }
DEVI void named_arrive(int id, int n) { asm volatile("bar.arrive %0, %1;" ::"r"(id), "r"(n) : "memory"); }
DEVI void pdl_wait() { asm volatile("griddepcontrol.wait;" ::: "memory"); }
DEVI void pdl_launch() { asm volatile("griddepcontrol.launch_dependents;" ::: "memory"); }
template <int R> DEVI void reg_inc() { asm volatile("setmaxnreg.inc.sync.aligned.u32 %0;" ::"n"(R)); }
template <int R> DEVI void reg_dec() { asm volatile("setmaxnreg.dec.sync.aligned.u32 %0;" ::"n"(R)); }

DEVI void wg_fence() { asm volatile("wgmma.fence.sync.aligned;" ::: "memory"); }
DEVI void wg_commit() { asm volatile("wgmma.commit_group.sync.aligned;" ::: "memory"); }
template <int N> DEVI void wg_wait() { asm volatile("wgmma.wait_group.sync.aligned %0;" ::"n"(N) : "memory"); }

DEVI uint64_t make_desc(uint32_t addr, uint32_t lbo, uint32_t sbo, uint32_t swz) {
    return (uint64_t)((addr & 0x3FFFF) >> 4) | ((uint64_t)(lbo >> 4) << 16) | ((uint64_t)(sbo >> 4) << 32) | ((uint64_t)swz << 62);
}
DEVI uint64_t desc_kmajor(uint32_t addr) { return make_desc(addr, 16, 1024, 1); }
DEVI uint64_t desc_mnmajor(uint32_t addr, uint32_t lbo) { return make_desc(addr, lbo, 1024, 1); }

#define ACC8(d, o) "+f"(d[o + 0]), "+f"(d[o + 1]), "+f"(d[o + 2]), "+f"(d[o + 3]), "+f"(d[o + 4]), "+f"(d[o + 5]), "+f"(d[o + 6]), "+f"(d[o + 7])
#define ACC64(d) ACC8(d, 0), ACC8(d, 8), ACC8(d, 16), ACC8(d, 24), ACC8(d, 32), ACC8(d, 40), ACC8(d, 48), ACC8(d, 56)
#define R64 "{%0,%1,%2,%3,%4,%5,%6,%7,%8,%9,%10,%11,%12,%13,%14,%15,%16,%17,%18,%19,%20,%21,%22,%23,%24,%25,%26,%27,%28,%29,%30,%31," \
            "%32,%33,%34,%35,%36,%37,%38,%39,%40,%41,%42,%43,%44,%45,%46,%47,%48,%49,%50,%51,%52,%53,%54,%55,%56,%57,%58,%59,%60,%61,%62,%63}"

template <int TB> DEVI void wgmma_ss128(float* d, uint64_t da, uint64_t db, int acc) {
    asm volatile("{\n.reg .pred p;\nsetp.ne.b32 p, %66, 0;\n"
                 "wgmma.mma_async.sync.aligned.m64n128k16.f32.bf16.bf16 " R64 ", %64, %65, p, 1, 1, 0, %67;\n}"
                 : ACC64(d) : "l"(da), "l"(db), "r"(acc), "n"(TB));
}
template <int TB> DEVI void wgmma_rs128(float* d, const uint32_t* a, uint64_t db, int acc) {
    asm volatile("{\n.reg .pred p;\nsetp.ne.b32 p, %69, 0;\n"
                 "wgmma.mma_async.sync.aligned.m64n128k16.f32.bf16.bf16 " R64 ", {%64,%65,%66,%67}, %68, p, 1, 1, %70;\n}"
                 : ACC64(d) : "r"(a[0]), "r"(a[1]), "r"(a[2]), "r"(a[3]), "l"(db), "r"(acc), "n"(TB));
}
DEVI uint32_t pack_bf16(float lo, float hi) {
    uint32_t r;
    asm("cvt.rn.bf16x2.f32 %0, %1, %2;" : "=r"(r) : "f"(hi), "f"(lo));
    return r;
}
DEVI void stmatrix_x4(uint32_t addr, uint32_t r0, uint32_t r1, uint32_t r2, uint32_t r3) {
    asm volatile("stmatrix.sync.aligned.m8n8.x4.shared.b16 [%0], {%1,%2,%3,%4};" ::"r"(addr), "r"(r0), "r"(r1), "r"(r2), "r"(r3) : "memory");
}
DEVI float ex2(float x) { float y; asm("ex2.approx.ftz.f32 %0, %1;" : "=f"(y) : "f"(x)); return y; }

DEVI void store_slab64(uint32_t base, int row0, const float* d, float s0, float s1, int lane) {
    int mi = lane >> 3, r = lane & 7;
    int row = row0 + (mi & 1) * 8 + r;
#pragma unroll
    for (int j = 0; j < 8; j += 2) {
        uint32_t r0 = pack_bf16(d[4 * j + 0] * s0, d[4 * j + 1] * s0);
        uint32_t r1 = pack_bf16(d[4 * j + 2] * s1, d[4 * j + 3] * s1);
        uint32_t r2 = pack_bf16(d[4 * j + 4] * s0, d[4 * j + 5] * s0);
        uint32_t r3 = pack_bf16(d[4 * j + 6] * s1, d[4 * j + 7] * s1);
        int chunk = j + (mi >> 1);
        stmatrix_x4(base + row * 128 + ((chunk ^ (row & 7)) << 4), r0, r1, r2, r3);
    }
}
struct cf { float x, y; };
DEVI cf cmul(cf a, cf b) { cf r; r.x = fmaf(a.x, b.x, -a.y * b.y); r.y = fmaf(a.x, b.y, a.y * b.x); return r; }
DEVI cf csq(cf a) { cf r; r.x = fmaf(a.x, a.x, -a.y * a.y); r.y = (a.x + a.x) * a.y; return r; }
DEVI cf cexp_(float re, float im) {
    float m = __expf(re), s, c;
    __sincosf(im, &s, &c);
    cf r; r.x = m * c; r.y = m * s; return r;
}
DEVI uint32_t h2(cf v) { uint32_t r; asm("cvt.rn.f16x2.f32 %0, %1, %2;" : "=r"(r) : "f"(v.y), "f"(v.x)); return r; }
DEVI uint32_t h2c(cf v) { uint32_t r; asm("cvt.rn.f16x2.f32 %0, %1, %2;" : "=r"(r) : "f"(-v.y), "f"(v.x)); return r; }
DEVI void mma_group(float (*c)[4], const uint32_t (*a)[4], const uint32_t (*b)[2]) {
    asm volatile(
        "mma.sync.aligned.m16n8k16.row.col.f32.f16.f16.f32 {%0,%1,%2,%3}, {%20,%21,%22,%23}, {%40,%41}, {%0,%1,%2,%3};\n"
        "mma.sync.aligned.m16n8k16.row.col.f32.f16.f16.f32 {%4,%5,%6,%7}, {%24,%25,%26,%27}, {%40,%41}, {%4,%5,%6,%7};\n"
        "mma.sync.aligned.m16n8k16.row.col.f32.f16.f16.f32 {%8,%9,%10,%11}, {%28,%29,%30,%31}, {%42,%43}, {%8,%9,%10,%11};\n"
        "mma.sync.aligned.m16n8k16.row.col.f32.f16.f16.f32 {%12,%13,%14,%15}, {%32,%33,%34,%35}, {%44,%45}, {%12,%13,%14,%15};\n"
        "mma.sync.aligned.m16n8k16.row.col.f32.f16.f16.f32 {%16,%17,%18,%19}, {%36,%37,%38,%39}, {%46,%47}, {%16,%17,%18,%19};\n"
        : "+f"(c[0][0]), "+f"(c[0][1]), "+f"(c[0][2]), "+f"(c[0][3]), "+f"(c[1][0]), "+f"(c[1][1]), "+f"(c[1][2]), "+f"(c[1][3]),
          "+f"(c[2][0]), "+f"(c[2][1]), "+f"(c[2][2]), "+f"(c[2][3]), "+f"(c[3][0]), "+f"(c[3][1]), "+f"(c[3][2]), "+f"(c[3][3]),
          "+f"(c[4][0]), "+f"(c[4][1]), "+f"(c[4][2]), "+f"(c[4][3])
        : "r"(a[0][0]), "r"(a[0][1]), "r"(a[0][2]), "r"(a[0][3]), "r"(a[1][0]), "r"(a[1][1]), "r"(a[1][2]), "r"(a[1][3]),
          "r"(a[2][0]), "r"(a[2][1]), "r"(a[2][2]), "r"(a[2][3]), "r"(a[3][0]), "r"(a[3][1]), "r"(a[3][2]), "r"(a[3][3]),
          "r"(a[4][0]), "r"(a[4][1]), "r"(a[4][2]), "r"(a[4][3]),
          "r"(b[0][0]), "r"(b[0][1]), "r"(b[1][0]), "r"(b[1][1]), "r"(b[2][0]), "r"(b[2][1]), "r"(b[3][0]), "r"(b[3][1]));
}
DEVI float bf2f(bf16 v) { return __bfloat162float(v); }
DEVI float rbf(float v) { return __bfloat162float(__float2bfloat16_rn(v)); }

struct SsmParams { const bf16 *lar, *aim, *cre, *cim, *ldt, *dskip, *u; };

DEVI int kp_index(int l) {
    int p = (int)rbf((float)l);
    return p < 256 ? p : (p < 512 ? 128 + (p >> 1) : (p < 1024 ? 256 + (p >> 2) : 384 + (p >> 3)));
}

DEVI void reds(uint32_t a, float v) { asm volatile("red.shared.add.f32 [%0], %1;" ::"r"(a), "f"(v) : "memory"); }
DEVI void ssm_kgen_warp(const SsmParams& P, int d, int half, int lane, uint32_t kp) {
    const int g = lane >> 2, t = lane & 3;
    float ar[2], ai[2], cr[2], ci[2], gr[2], gi[2];
    bf16 raw[2][4];
    const bf16 rdt = P.ldt[d];
#pragma unroll
    for (int q = 0; q < 2; q++) {
        const int n = d * SSM_N + 64 * half + 32 * q + lane;
        raw[q][0] = P.lar[n]; raw[q][1] = P.aim[n]; raw[q][2] = P.cre[n]; raw[q][3] = P.cim[n];
    }
    const float dt = rbf(expf(bf2f(rdt)));
#pragma unroll
    for (int q = 0; q < 2; q++) {
        ar[q] = -rbf(expf(bf2f(raw[q][0]))) * dt;
        ai[q] = bf2f(raw[q][1]) * dt;
        cr[q] = 2.f * (bf2f(raw[q][2]) * dt);
        ci[q] = 2.f * (bf2f(raw[q][3]) * dt);
        float m = expf(ar[q] * 64.f), sn, cs;
        sincosf(ai[q] * 64.f, &sn, &cs);
        gr[q] = m * cs; gi[q] = m * sn;
    }
    float cm = 0.f;
#pragma unroll
    for (int q = 0; q < 2; q++) cm = fmaxf(cm, fmaxf(fabsf(cr[q]), fabsf(ci[q])));
#pragma unroll
    for (int o = 16; o; o >>= 1) cm = fmaxf(cm, __shfl_xor_sync(~0u, cm, o));
    const int ex = min(max((int)(__float_as_uint(cm) >> 23), 1), 253);
    const float cs_dn = __uint_as_float((uint32_t)(254 - ex) << 23), cs_up = __uint_as_float((uint32_t)ex << 23);
    float acc[5][4];
#pragma unroll
    for (int s = 0; s < 5; s++) { acc[s][0] = acc[s][1] = acc[s][2] = acc[s][3] = 0.f; }
    float klast = 0.f;
    const float gf = (float)g;
#pragma unroll
    for (int q = 0; q < 2; q++) {
#pragma unroll 1
        for (int g0 = 0; g0 < 8; g0 += 2) {
            uint32_t fa[5][4], fb[4][2];
#pragma unroll
            for (int h = 0; h < 2; h++) {
                const int src = ((g0 + h) << 2) | t;
                const float a_r = __shfl_sync(~0u, ar[q], src), a_i = __shfl_sync(~0u, ai[q], src);
                cf C, G;
                C.x = __shfl_sync(~0u, cr[q], src) * cs_dn; C.y = __shfl_sync(~0u, ci[q], src) * cs_dn;
                G.x = __shfl_sync(~0u, gr[q], src); G.y = __shfl_sync(~0u, gi[q], src);
                cf E = cexp_(a_r * gf, a_i * gf);
                cf B = csq(csq(csq(E)));
                fb[0][h] = h2c(cmul(C, B));
                cf EG = cmul(E, G);
                fa[0][2 * h] = h2(E); fa[0][2 * h + 1] = h2(EG);
                cf G2 = csq(G);
                cf X = cmul(E, G2), Xh = cmul(EG, G2);
                fa[1][2 * h] = h2(X); fa[1][2 * h + 1] = h2(Xh);
#pragma unroll
                for (int s = 2; s < 5; s++) {
                    B = csq(B); X = csq(X); Xh = csq(Xh);
                    fb[s - 1][h] = h2c(cmul(C, B));
                    fa[s][2 * h] = h2(X); fa[s][2 * h + 1] = h2(Xh);
                }
                X = csq(X);
                klast += fmaf(C.x, X.x, -C.y * X.y);
            }
            mma_group(acc, fa, fb);
        }
    }
    klast += __shfl_xor_sync(~0u, klast, 1);
    klast += __shfl_xor_sync(~0u, klast, 2);
#pragma unroll
    for (int s = 0; s < 5; s++) {
        const uint32_t b = kp + (128 * s + g + 16 * t) * 4;
        reds(b, acc[s][0] * cs_up); reds(b + 32, acc[s][1] * cs_up); reds(b + 256, acc[s][2] * cs_up); reds(b + 288, acc[s][3] * cs_up);
    }
    if (lane == 0) reds(kp + 2560, klast * cs_up);
}

constexpr int G1_THREADS = 384;
constexpr int G1_NS = 11;
constexpr int G1_SMEM = G1_NS * 16384 + 32768 + 256 + 1024;

__global__ void __cluster_dims__(2, 1, 1) __launch_bounds__(G1_THREADS, 1)
gemm_kv_kernel(const __grid_constant__ CUtensorMap tm_c, const __grid_constant__ CUtensorMap tm_wk,
               const __grid_constant__ CUtensorMap tm_wv, const __grid_constant__ CUtensorMap tm_kv_st,
               const bf16* __restrict__ px, const bf16* __restrict__ pwq) {
    extern __shared__ uint8_t smem_raw[];
    const uint32_t sb = (smem_u32(smem_raw) + 1023) & ~1023u;
    const uint32_t sC = sb + G1_NS * 16384, bars = sC + 32768;
    const uint32_t full = bars, empty = bars + 128;
    const int tid = threadIdx.x, warp = tid >> 5, lane = tid & 31, wg = tid >> 7;
    const uint32_t rank = cluster_rank();
    const int cl = blockIdx.x >> 1;
    const int m0 = ((cl & 7) * 2 + rank) * 128;
    const int ng = cl >> 3;
    STAMP(blockIdx.x == 10 && tid == 0, 0);
    if (tid == 0) {
        for (int i = 0; i < G1_NS; i++) { mbar_init(full + 8 * i, 1); mbar_init(empty + 8 * i, 16); }
        fence_barrier_init();
        for (int it = 0; it < 8; it++) {
            mbar_expect_tx(full + 8 * it, 16384);
            tma_load_2d(sb + it * 16384, &tm_c, it * 64, m0, full + 8 * it);
        }
    }
    __syncthreads();
    cluster_sync_all();
    pdl_launch();
    if (wg == 2) {
        reg_dec<40>();
        if (tid == 256) {
            const CUtensorMap* tw = ng < 4 ? &tm_wk : &tm_wv;
            const int n0 = (ng & 3) * 1024 + rank * 64;
            int st = 8; uint32_t ph = 1;
            for (int it = 0; it < 64; it++) {
                mbar_wait(empty + 8 * st, ph);
                mbar_expect_tx(full + 8 * st, 16384);
                tma_load_2d_mc(sb + st * 16384 + rank * 8192, tw, n0 + (it >> 3) * 128, (it & 7) * 64, full + 8 * st, 3);
                if (it < 2) {
                    for (int j = 3 + it * 8 + (cl & 7); j < 19; j += 16) tma_prefetch_2d(tw, n0 + (j >> 3) * 128, (j & 7) * 64);
                }
                if (it >= 3 && it + 16 < 64 && (it & 7) == (cl & 7)) tma_prefetch_2d(tw, n0 + ((it + 16) >> 3) * 128, (it & 7) * 64);
                if (it == 24) bulk_prefetch(px + blockIdx.x * 8192, 16384);
                if (it == 32) bulk_prefetch(pwq + blockIdx.x * 16384, 32768);
                if (++st == G1_NS) { st = 0; ph ^= 1; }
            }
        }
        __syncwarp();
    } else {
        reg_inc<232>();
        uint32_t af[128];
        float acc[64];
        const int wq = warp & 3;
        const int row = wg * 64 + wq * 16 + (lane & 15);
        const uint32_t stg = sC + wg * 16384;
        int st = 8, pst = 0; uint32_t ph = 0;
#pragma unroll
        for (int kc = 0; kc < 8; kc++) {
            mbar_wait(full + 8 * kc, 0);
#pragma unroll
            for (int k = 0; k < 4; k++) {
                const uint32_t a = sb + kc * 16384 + row * 128 + (((2 * k + (lane >> 4)) ^ (row & 7)) << 4);
                uint32_t* f = af + kc * 16 + k * 4;
                asm volatile("ldmatrix.sync.aligned.m8n8.x4.shared.b16 {%0,%1,%2,%3}, [%4];"
                             : "=r"(f[0]), "=r"(f[1]), "=r"(f[2]), "=r"(f[3]) : "r"(a) : "memory");
            }
            __syncwarp();
            if (lane < 2) mbar_arrive_cluster(empty + 8 * kc, lane);
        }
#pragma unroll 1
        for (int t = 0; t < 8; t++) {
            if (wg == 1 || t > 0) named_sync(3 + wg, 256);
#pragma unroll
            for (int kc = 0; kc < 8; kc++) {
                mbar_wait(full + 8 * st, ph);
                STAMP(blockIdx.x == 10 && (tid & 127) == 0, 1 + wg * 96 + t * 12 + kc);
                wg_fence();
                const uint64_t db = desc_mnmajor(sb + st * 16384, 8192);
#pragma unroll
                for (int k = 0; k < 4; k++) wgmma_rs128<1>(acc, af + kc * 16 + k * 4, db + k * 128, (kc | k) != 0);
                wg_commit();
                if (kc == 3 && (wg == 0 || t < 7)) named_arrive(3 + (wg ^ 1), 256);
                if (kc > 0) {
                    wg_wait<1>();
                    if (lane < 2) mbar_arrive_cluster(empty + 8 * pst, lane);
                }
                pst = st;
                if (++st == G1_NS) { st = 0; ph ^= 1; }
            }
            if ((tid & 127) == 0) bulk_wait_read<0>();
            named_sync(1 + wg, 128);
            wg_wait<0>();
            STAMP(blockIdx.x == 10 && (tid & 127) == 0, 9 + wg * 96 + t * 12);
            if (lane < 2) mbar_arrive_cluster(empty + 8 * pst, lane);
            store_slab64(stg, wq * 16, acc, 1.f, 1.f, lane);
            store_slab64(stg + 8192, wq * 16, acc + 32, 1.f, 1.f, lane);
            fence_proxy_async();
            named_sync(1 + wg, 128);
            if ((tid & 127) == 0) {
                tma_store_2d(&tm_kv_st, stg, ng * 1024 + t * 128, m0 + wg * 64);
                tma_store_2d(&tm_kv_st, stg + 8192, ng * 1024 + t * 128 + 64, m0 + wg * 64);
                bulk_commit();
            }
            STAMP(blockIdx.x == 10 && (tid & 127) == 0, 10 + wg * 96 + t * 12);
        }
        if ((tid & 127) == 0) bulk_wait<0>();
        __syncwarp();
    }
    asm volatile("barrier.cluster.arrive.relaxed.aligned;\nbarrier.cluster.wait.aligned;" ::: "memory");
}
constexpr int AT_NS = 6;
constexpr int AT_SMEM = AT_NS * 32768 + 32768 + 256 + 1024;
constexpr int AT_ITEMS = 512;

DEVI uint32_t hmax2(uint32_t a, uint32_t b) { uint32_t r; asm("max.bf16x2 %0, %1, %2;" : "=r"(r) : "r"(a), "r"(b)); return r; }
DEVI uint32_t hmul2(uint32_t a, uint32_t b) { uint32_t r; asm("mul.rn.bf16x2 %0, %1, %2;" : "=r"(r) : "r"(a), "r"(b)); return r; }
DEVI uint32_t hfma2(uint32_t a, uint32_t b, uint32_t c) { uint32_t r; asm("fma.rn.bf16x2 %0, %1, %2, %3;" : "=r"(r) : "r"(a), "r"(b), "r"(c)); return r; }
DEVI float blo(uint32_t v) { return __uint_as_float(v << 16); }
DEVI float bhi(uint32_t v) { return __uint_as_float(v & 0xffff0000u); }

template <bool FIRST>
DEVI void softmax_tile(float* s, float& m0, float& m1, float& l0, float& l1, float& al0, float& al1) {
    const uint32_t HI = 0x3DB53DB5u;
    const uint32_t LO = 0x371E371Eu;
    const float L2E = 1.4426950408889634f;
    uint32_t x0 = 0xFF80FF80u, x1 = 0xFF80FF80u;
#pragma unroll
    for (int j = 0; j < 16; j++) {
        uint32_t a = pack_bf16(s[4 * j], s[4 * j + 1]), b = pack_bf16(s[4 * j + 2], s[4 * j + 3]);
        a = hfma2(a, HI, hmul2(a, LO));
        b = hfma2(b, HI, hmul2(b, LO));
        s[4 * j] = __uint_as_float(a); s[4 * j + 2] = __uint_as_float(b);
        x0 = hmax2(x0, a); x1 = hmax2(x1, b);
    }
    uint32_t x = hmax2(__byte_perm(x0, x1, 0x5410), __byte_perm(x0, x1, 0x7632));
    x = hmax2(x, __shfl_xor_sync(~0u, x, 1));
    x = hmax2(x, __shfl_xor_sync(~0u, x, 2));
    float n0 = blo(x), n1 = bhi(x);
    if (!FIRST) {
        n0 = fmaxf(n0, m0); n1 = fmaxf(n1, m1);
        al0 = ex2((m0 - n0) * L2E); al1 = ex2((m1 - n1) * L2E);
    }
    m0 = n0; m1 = n1;
    const float c0 = -n0 * L2E, c1 = -n1 * L2E;
    float s0 = 0.f, s1 = 0.f;
#pragma unroll
    for (int j = 0; j < 16; j++) {
        uint32_t a = __float_as_uint(s[4 * j]), b = __float_as_uint(s[4 * j + 2]);
        float e0 = ex2(fmaf(blo(a), L2E, c0)), e1 = ex2(fmaf(bhi(a), L2E, c0));
        float e2 = ex2(fmaf(blo(b), L2E, c1)), e3 = ex2(fmaf(bhi(b), L2E, c1));
        s0 += e0 + e1; s1 += e2 + e3;
        s[4 * j] = e0; s[4 * j + 1] = e1; s[4 * j + 2] = e2; s[4 * j + 3] = e3;
    }
    if (FIRST) { l0 = s0; l1 = s1; }
    else { l0 = fmaf(l0, al0, s0); l1 = fmaf(l1, al1, s1); }
}

struct Ring {
    int st; uint32_t ph;
    DEVI void next() { if (++st == AT_NS) { st = 0; ph ^= 1; } }
};

__global__ void __launch_bounds__(384, 1)
attn_kernel(const __grid_constant__ CUtensorMap tm_x, const __grid_constant__ CUtensorMap tm_wq,
            const __grid_constant__ CUtensorMap tm_kv, const __grid_constant__ CUtensorMap tm_ctx_st,
            const bf16* __restrict__ pu, const bf16* __restrict__ pwo) {
    extern __shared__ uint8_t smem_raw[];
    const uint32_t sb = (smem_u32(smem_raw) + 1023) & ~1023u;
    const uint32_t sO = sb + AT_NS * 32768, bars = sO + 32768;
    const uint32_t full = bars, empty = bars + 64;
    volatile int* slots = reinterpret_cast<volatile int*>(smem_raw + (bars + 128 - smem_u32(smem_raw)));
    const int tid = threadIdx.x, warp = tid >> 5, lane = tid & 31, wg = tid >> 7;
    if (tid == 0) {
        for (int i = 0; i < AT_NS; i++) { mbar_init(full + 8 * i, 1); mbar_init(empty + 8 * i, 8); }
        fence_barrier_init();
    }
    __syncthreads();
    if (wg == 2) {
        reg_dec<24>();
        if (warp == 8 && lane == 0) {
            Ring r{0, 1};
            int n = 0;
            while (true) {
                int idx = (int)atomicInc(&g_sched, AT_ITEMS + gridDim.x - 1);
                if (idx >= AT_ITEMS - 128 && idx < AT_ITEMS) {
                    bulk_prefetch(pu + (idx - (AT_ITEMS - 128)) * 8192, 16384);
                    bulk_prefetch(pwo + (idx - (AT_ITEMS - 128)) * 16384, 32768);
                }
                mbar_wait(empty + 8 * r.st, r.ph);
                if (idx >= AT_ITEMS) {
                    slots[n & 3] = -1;
                    mbar_arrive(full + 8 * r.st);
                    break;
                }
                slots[n & 3] = idx;
                const int qi = 15 - (idx >> 5), h = idx & 31;
                for (int kc = 0; kc < 8; kc++) {
                    if (kc) mbar_wait(empty + 8 * r.st, r.ph);
                    const uint32_t fb = full + 8 * r.st, dst = sb + r.st * 32768;
                    mbar_expect_tx(fb, 32768);
                    tma_load_2d(dst, &tm_x, kc * 64, qi * 128, fb);
                    tma_load_2d(dst + 16384, &tm_wq, h * 128, kc * 64, fb);
                    tma_load_2d(dst + 24576, &tm_wq, h * 128 + 64, kc * 64, fb);
                    r.next();
                }
                if (n == 0) { pdl_wait(); pdl_launch(); }
                for (int j = qi; j >= -1; j--) {
#pragma unroll
                    for (int v = 0; v < 2; v++) {
                        const int jj = j + v;
                        if (jj < 0 || jj > qi || (v == 0 && j < 0)) continue;
                        mbar_wait(empty + 8 * r.st, r.ph);
                        const uint32_t fb = full + 8 * r.st, dst = sb + r.st * 32768;
                        mbar_expect_tx(fb, 32768);
                        tma_load_2d(dst, &tm_kv, v * HDALL + h * 128, jj * 128, fb);
                        tma_load_2d(dst + 16384, &tm_kv, v * HDALL + h * 128 + 64, jj * 128, fb);
                        r.next();
                    }
                }
                n++;
            }
            if (n == 0) { pdl_wait(); pdl_launch(); }
        }
    } else {
        reg_inc<240>();
        Ring r{0, 0};
        float o[64], s[64];
        uint32_t qf[32], pa[32];
        const int g = lane >> 2, t = lane & 3, wq = warp & 3;
        const uint32_t stg = sO + wg * 16384;
        if (wg == 1) named_arrive(3, 256);
        for (int n = 0;; n++) {
            mbar_wait(full + 8 * r.st, r.ph);
            const int idx = slots[n & 3];
            if (idx < 0) break;
            const int qi = 15 - (idx >> 5), h = idx & 31;
#pragma unroll 1
            for (int kc = 0; kc < 8; kc++) {
                if (kc) mbar_wait(full + 8 * r.st, r.ph);
                wg_fence();
                const uint32_t base = sb + r.st * 32768;
                const uint64_t da = desc_kmajor(base + wg * 8192), db = desc_mnmajor(base + 16384, 8192);
#pragma unroll
                for (int k = 0; k < 4; k++) wgmma_ss128<1>(s, da + k * 2, db + k * 128, (kc | k) != 0);
                wg_commit();
                if (kc) {
                    wg_wait<1>();
                    if (lane == 0) mbar_arrive(empty + 8 * (r.st == 0 ? AT_NS - 1 : r.st - 1));
                }
                r.next();
            }
            wg_wait<0>();
            if (lane == 0) mbar_arrive(empty + 8 * (r.st == 0 ? AT_NS - 1 : r.st - 1));
#pragma unroll
            for (int i = 0; i < 32; i++) qf[i] = pack_bf16(s[2 * i], s[2 * i + 1]);
            float m0, m1, l0, l1, al0, al1;
            auto issue_qk = [&]() {
                mbar_wait(full + 8 * r.st, r.ph);
                wg_fence();
                const uint64_t db = desc_kmajor(sb + r.st * 32768);
#pragma unroll
                for (int k = 0; k < 8; k++) wgmma_rs128<0>(s, qf + 4 * k, db + (k >> 2) * 1024 + (k & 3) * 2, k != 0);
                wg_commit();
            };
            auto issue_pv = [&](const uint32_t* p, int st, uint32_t ph, int acc) {
                mbar_wait(full + 8 * st, ph);
                wg_fence();
                const uint64_t db = desc_mnmajor(sb + st * 32768, 16384);
#pragma unroll
                for (int k = 0; k < 8; k++) wgmma_rs128<1>(o, p + 4 * k, db + k * 128, acc | k);
                wg_commit();
            };
            issue_qk();
            wg_wait<0>();
            if (lane == 0) mbar_arrive(empty + 8 * r.st);
            r.next();
            {
                const int row = wg * 64 + wq * 16 + g;
#pragma unroll
                for (int j = 0; j < 16; j++) {
                    const int c = 8 * j + 2 * t;
                    if (c > row) s[4 * j] = -INFINITY;
                    if (c + 1 > row) s[4 * j + 1] = -INFINITY;
                    if (c > row + 8) s[4 * j + 2] = -INFINITY;
                    if (c + 1 > row + 8) s[4 * j + 3] = -INFINITY;
                }
            }
            softmax_tile<true>(s, m0, m1, l0, l1, al0, al1);
#pragma unroll
            for (int i = 0; i < 32; i++) pa[i] = pack_bf16(s[2 * i], s[2 * i + 1]);
            int first = 0;
#pragma unroll 1
            for (int j = qi; j >= 1; j--) {
                named_sync(3 + wg, 256);
                issue_qk();
                const int kst = r.st;
                r.next();
                issue_pv(pa, r.st, r.ph, first);
                named_arrive(3 + (wg ^ 1), 256);
                wg_wait<1>();
                if (lane == 0) mbar_arrive(empty + 8 * kst);
                softmax_tile<false>(s, m0, m1, l0, l1, al0, al1);
                wg_wait<0>();
                if (lane == 0) mbar_arrive(empty + 8 * r.st);
                r.next();
#pragma unroll
                for (int i = 0; i < 32; i++) pa[i] = pack_bf16(s[2 * i], s[2 * i + 1]);
#pragma unroll
                for (int i = 0; i < 16; i++) {
                    o[4 * i] *= al0; o[4 * i + 1] *= al0; o[4 * i + 2] *= al1; o[4 * i + 3] *= al1;
                }
                first = 1;
            }
            issue_pv(pa, r.st, r.ph, first);
            l0 += __shfl_xor_sync(~0u, l0, 1); l0 += __shfl_xor_sync(~0u, l0, 2);
            l1 += __shfl_xor_sync(~0u, l1, 1); l1 += __shfl_xor_sync(~0u, l1, 2);
            const float i0 = 1.f / l0, i1 = 1.f / l1;
            if ((tid & 127) == 0) bulk_wait_read<0>();
            named_sync(1 + wg, 128);
            wg_wait<0>();
            if (lane == 0) mbar_arrive(empty + 8 * r.st);
            r.next();
            store_slab64(stg, wq * 16, o, i0, i1, lane);
            store_slab64(stg + 8192, wq * 16, o + 32, i0, i1, lane);
            fence_proxy_async();
            named_sync(1 + wg, 128);
            if ((tid & 127) == 0) {
                tma_store_2d(&tm_ctx_st, stg, h * 128, qi * 128 + wg * 64);
                tma_store_2d(&tm_ctx_st, stg + 8192, h * 128 + 64, qi * 128 + wg * 64);
                bulk_commit();
            }
        }
        if ((tid & 127) == 0) bulk_wait<0>();
    }
}
constexpr int OP_NS = 4;
constexpr int OP_ULD = 164 * 16;
constexpr int OP_UCH = 2 * OP_ULD;
constexpr int OP_SMEM = OP_NS * 32768 + 32768 + 4 * WTAB * 4 + 4 * OP_UCH + 4 * 648 * 4 + 256 + 1024;

template <int N> DEVI void wgmma_conv(float* d, const uint32_t* a, uint64_t db);
template <> DEVI void wgmma_conv<128>(float* d, const uint32_t* a, uint64_t db) {
    asm volatile("wgmma.mma_async.sync.aligned.m64n128k16.f32.bf16.bf16 {%0,%1,%2,%3,%4,%5,%6,%7,%8,%9,%10,%11,%12,%13,%14,%15,%16,%17,%18,%19,%20,%21,%22,%23,%24,%25,%26,%27,%28,%29,%30,%31,%32,%33,%34,%35,%36,%37,%38,%39,%40,%41,%42,%43,%44,%45,%46,%47,%48,%49,%50,%51,%52,%53,%54,%55,%56,%57,%58,%59,%60,%61,%62,%63}, "
                 "{%64,%65,%66,%67}, %68, 1, 1, 1, 0;"
                 : ACC8(d, 0), ACC8(d, 8), ACC8(d, 16), ACC8(d, 24), ACC8(d, 32), ACC8(d, 40), ACC8(d, 48), ACC8(d, 56) : "r"(a[0]), "r"(a[1]), "r"(a[2]), "r"(a[3]), "l"(db));
}
template <> DEVI void wgmma_conv<96>(float* d, const uint32_t* a, uint64_t db) {
    asm volatile("wgmma.mma_async.sync.aligned.m64n96k16.f32.bf16.bf16 {%0,%1,%2,%3,%4,%5,%6,%7,%8,%9,%10,%11,%12,%13,%14,%15,%16,%17,%18,%19,%20,%21,%22,%23,%24,%25,%26,%27,%28,%29,%30,%31,%32,%33,%34,%35,%36,%37,%38,%39,%40,%41,%42,%43,%44,%45,%46,%47}, "
                 "{%48,%49,%50,%51}, %52, 1, 1, 1, 0;"
                 : ACC8(d, 0), ACC8(d, 8), ACC8(d, 16), ACC8(d, 24), ACC8(d, 32), ACC8(d, 40) : "r"(a[0]), "r"(a[1]), "r"(a[2]), "r"(a[3]), "l"(db));
}
template <> DEVI void wgmma_conv<64>(float* d, const uint32_t* a, uint64_t db) {
    asm volatile("wgmma.mma_async.sync.aligned.m64n64k16.f32.bf16.bf16 {%0,%1,%2,%3,%4,%5,%6,%7,%8,%9,%10,%11,%12,%13,%14,%15,%16,%17,%18,%19,%20,%21,%22,%23,%24,%25,%26,%27,%28,%29,%30,%31}, "
                 "{%32,%33,%34,%35}, %36, 1, 1, 1, 0;"
                 : ACC8(d, 0), ACC8(d, 8), ACC8(d, 16), ACC8(d, 24) : "r"(a[0]), "r"(a[1]), "r"(a[2]), "r"(a[3]), "l"(db));
}
template <> DEVI void wgmma_conv<32>(float* d, const uint32_t* a, uint64_t db) {
    asm volatile("wgmma.mma_async.sync.aligned.m64n32k16.f32.bf16.bf16 {%0,%1,%2,%3,%4,%5,%6,%7,%8,%9,%10,%11,%12,%13,%14,%15}, "
                 "{%16,%17,%18,%19}, %20, 1, 1, 1, 0;"
                 : ACC8(d, 0), ACC8(d, 8) : "r"(a[0]), "r"(a[1]), "r"(a[2]), "r"(a[3]), "l"(db));
}
DEVI uint32_t lds32(uint32_t a) { uint32_t v; asm volatile("ld.shared.b32 %0, [%1];" : "=r"(v) : "r"(a)); return v; }
DEVI uint32_t lds16(uint32_t a) { uint16_t v; asm volatile("ld.shared.b16 %0, [%1];" : "=h"(v) : "r"(a)); return v; }

DEVI void sts32(uint32_t a, float v) { asm volatile("st.shared.f32 [%0], %1;" ::"r"(a), "f"(v) : "memory"); }
template <int J> DEVI void conv_group(float* acc, uint32_t* f, uint32_t wa, uint64_t du) {
#pragma unroll
    for (int i = 0; i < 8; i++) {
        const uint32_t w = wa + (8 * J + i) * 256;
        f[4 * i] = lds32(w); f[4 * i + 1] = lds32(w + 32); f[4 * i + 2] = lds32(w - 32); f[4 * i + 3] = f[4 * i];
    }
    wg_fence();
#pragma unroll
    for (int i = 0; i < 8; i++) wgmma_conv<128 - 32 * J>(acc, f + 4 * i, du + (uint64_t)(4 * (8 * J + i)));
    wg_commit();
}
DEVI uint32_t ypos(int a, int b) { return (uint32_t)((a * 16 + b) ^ ((((a >> 1) ^ (a >> 3)) & 3) << 3)) * 4; }

DEVI void expand_table(int ct, uint32_t sW, uint32_t sK) {
#pragma unroll 1
    for (int i = ct; i < WTAB; i += 384) {
        const int c = (i >> 3) & 3, qd = (i & 7) | ((i >> 5) << 3);
        float k[5];
#pragma unroll
        for (int e = 0; e < 5; e++) {
            const int l = qd * 4 - 65 + e;
            const int hi = (int)__bfloat16_as_ushort(__float2bfloat16_rn((float)l)) - 17024;
            k[e] = __uint_as_float(lds32(sK + (c * 648 + (l < 0 ? 644 : (l < 128 ? l : hi))) * 4));
        }
        asm volatile("st.shared.v4.b32 [%0], {%1,%2,%3,%4};" ::"r"(sW + (c * WTAB + qd * 4) * 4), "r"(pack_bf16(k[1], k[0])),
                     "r"(pack_bf16(k[2], k[1])), "r"(pack_bf16(k[3], k[2])), "r"(pack_bf16(k[4], k[3])) : "memory");
    }
}

__global__ void __cluster_dims__(2, 1, 1) __launch_bounds__(512, 1)
outproj_kernel(const __grid_constant__ CUtensorMap tm_ctx, const __grid_constant__ CUtensorMap tm_wo,
               const __grid_constant__ CUtensorMap tm_out, const __grid_constant__ CUtensorMap tm_u, SsmParams sp, bf16* __restrict__ out) {
    extern __shared__ uint8_t smem_raw[];
    const uint32_t sb = (smem_u32(smem_raw) + 1023) & ~1023u;
    const uint32_t sX = sb + OP_NS * 32768, sW = sX + 32768, sU = sW + 4 * WTAB * 4, sK = sU + 4 * OP_UCH, bars = sK + 4 * 648 * 4;
    const uint32_t full = bars, empty = bars + 64, xfull = bars + 128, wfull = bars + 136, xfree = bars + 144;
    const int tid = threadIdx.x, warp = tid >> 5, lane = tid & 31, wg = tid >> 7;
    const uint32_t rank = cluster_rank();
    const uint32_t kr = rank;
    const int cl = blockIdx.x >> 1;
    const int m0 = (cl >> 2) * 128, n0 = (cl & 3) * 128, k0 = kr * 2048;
    STAMP(blockIdx.x == 10 && tid == 0, 1000);
    if (tid == 0) {
        for (int i = 0; i < OP_NS; i++) { mbar_init(full + 8 * i, 1); mbar_init(empty + 8 * i, 8); }
        mbar_init(xfull, 1);
        mbar_init(wfull, 1);
        mbar_init(xfree, 1);
        fence_barrier_init();
        mbar_expect_tx(wfull, 32768);
        for (int i = 0; i < 8; i++) tma_load_2d(sX + i * 4096, &tm_u, cl * 8, i * 256, wfull);
    }
    for (int i = tid; i < 648; i += 512) asm volatile("st.shared.v4.b32 [%0], {%1,%1,%1,%1};" ::"r"(sK + i * 16), "r"(0) : "memory");
    __syncthreads();
    cluster_arrive();
    if (wg == 3) {
        reg_dec<40>();
        cluster_wait();
        if (tid == 384) {
            mbar_expect_tx(xfull, 32768);
            for (int it = 0; it < OP_NS; it++) {
                const uint32_t dst = sb + it * 32768, fb = full + 8 * it;
                mbar_expect_tx(fb, 32768);
                tma_load_2d(dst + 16384, &tm_wo, n0, k0 + it * 64, fb);
                tma_load_2d(dst + 24576, &tm_wo, n0 + 64, k0 + it * 64, fb);
            }
            pdl_wait();
            STAMP(blockIdx.x == 10, 1005);
            for (int it = 0; it < 32; it++) {
                const int st = it & (OP_NS - 1);
                const uint32_t dst = sb + st * 32768, fb = full + 8 * st;
                if (it >= OP_NS) {
                    mbar_wait(empty + 8 * st, ((it / OP_NS) & 1) ^ 1);
                    mbar_expect_tx(fb, 32768);
                    tma_load_2d(dst + 16384, &tm_wo, n0, k0 + it * 64, fb);
                    tma_load_2d(dst + 24576, &tm_wo, n0 + 64, k0 + it * 64, fb);
                }
                tma_load_2d(dst, &tm_ctx, k0 + it * 64, m0, fb);
                tma_load_2d(dst + 8192, &tm_ctx, k0 + it * 64, m0 + 64, fb);
            }
        }
        __syncwarp();
    } else {
      const int ct = tid & 127, wq = warp & 3;
      if (wg == 2) {
        for (int i = ct; i < 8 * 32; i += 128) {
            const uint32_t a = sU + (i >> 5) * OP_ULD + (128 + (i & 31)) * 16;
            asm volatile("st.shared.v4.b32 [%0], {%1,%1,%1,%1};" ::"r"(a), "r"(0) : "memory");
        }
        const bool mine = ((lane >> 2) & 1) == (int)rank;
        const uint32_t ub = sU + (lane & 3) * OP_UCH + ((lane >> 3) & 1) * OP_ULD + (127 - 2 * wq - (lane >> 4)) * 16;
        mbar_wait(wfull, 0);
#pragma unroll 4
        for (int i = 0; i < 16; i++) {
            uint32_t r0, r1, r2, r3;
            asm volatile("ldmatrix.sync.aligned.m8n8.x4.trans.shared.b16 {%0,%1,%2,%3}, [%4];"
                         : "=r"(r0), "=r"(r1), "=r"(r2), "=r"(r3) : "r"(sX + (i * 128 + ct) * 16) : "memory");
            asm volatile("stmatrix.sync.aligned.m8n8.x4.shared.b16 [%0], {%1,%2,%3,%4};"
                         ::"r"(mine ? ub - i * 128 : sW + lane * 16), "r"(r0), "r"(r1), "r"(r2), "r"(r3) : "memory");
        }
        fence_proxy_async();
        STAMP(blockIdx.x == 10 && ct == 0, 1001);
      } else {
        ssm_kgen_warp(sp, blockIdx.x * 4 + wq, wg, lane, sK + wq * 648 * 4);
      }
      cluster_wait();
      named_sync(3, 384);
      if (tid == 256) mbar_arrive_cluster(xfree, rank ^ 1);
      STAMP(blockIdx.x == 10 && tid == 257, 1002);
      expand_table(tid, sW, sK);
      if (wg == 2) {
        reg_inc<208>();
        const int g = lane >> 2, t = lane & 3;
        const int d0 = blockIdx.x * 4;
        const uint2 dsk = __ldg(reinterpret_cast<const uint2*>(sp.dskip + d0));
        named_sync(4, 384);
        uint32_t res[16][2];
        STAMP(blockIdx.x == 10 && ct == 0, 1003);
#pragma unroll 1
        for (int c = 0; c < 4; c++) {
            float acc[64];
            uint32_t fa[32], fb[32];
#pragma unroll
            for (int i = 0; i < 64; i++) acc[i] = 0.f;
            const uint32_t wa = sW + (c * WTAB + 64 + 16 * wq + g - 2 * t) * 4;
            const uint64_t du = make_desc(sU + c * OP_UCH, OP_ULD, 128, 0);
            conv_group<0>(acc, fa, wa, du);
            conv_group<1>(acc, fb, wa, du);
            wg_wait<1>();
            conv_group<2>(acc, fa, wa, du);
            wg_wait<1>();
            conv_group<3>(acc, fb, wa, du);
            named_sync(5, 128);
            wg_wait<0>();
            const uint32_t yb = (wq & 1) ? sW + c * WTAB * 4 : sK;
            if (wq >= 2) named_sync(6, 128);
#pragma unroll
            for (int i = 0; i < 64; i++) {
                const int a = 127 - (8 * (i >> 2) + 2 * t + (i & 1)) + wq;
                const uint32_t p = yb + ypos(a & 127, g + 8 * ((i >> 1) & 1));
                float v = (i < 4 && a > 127) ? 0.f : acc[i];
                if (wq >= 2) v += __uint_as_float(lds32(p));
                sts32(p, v);
            }
            if (wq < 2) named_arrive(6, 128);
            named_sync(5, 128);
            const uint32_t dw = (c & 2) ? dsk.y : dsk.x;
            const float D = (c & 1) ? bhi(dw) : blo(dw);
#pragma unroll
            for (int i = 0; i < 16; i++) {
                const int a = 4 * (31 - (8 * (i >> 2) + 2 * t + (i & 1))) + wq, rh = (i >> 1) & 1;
                const uint32_t p = ypos(a, g + 8 * rh);
                const float y = __uint_as_float(lds32(sK + p)) + __uint_as_float(lds32(sW + c * WTAB * 4 + p));
                const float u = __uint_as_float(lds16(sU + c * OP_UCH + rh * OP_ULD + (127 - a) * 16 + g * 2) << 16);
                const uint32_t o = __bfloat16_as_ushort(__float2bfloat16_rn(rbf(y) + rbf(u * D)));
                res[i][0] = __byte_perm(res[i][0], res[i][1], 0x5432); res[i][1] = __byte_perm(res[i][1], o, 0x5432);
            }
        }
        STAMP(blockIdx.x == 10 && ct == 0, 1004);
        const int grp = blockIdx.x >> 2, me = blockIdx.x & 3;
#pragma unroll
        for (int i = 0; i < 8; i++)
            __stcg(g_y + (((grp * 4 + (i >> 1)) * 4 + me) * 2 + (i & 1)) * 128 + ct,
                   make_uint4(res[2 * i][0], res[2 * i][1], res[2 * i + 1][0], res[2 * i + 1][1]));
        named_sync(5, 128);
        if (ct == 0) {
            __threadfence();
            const unsigned int target = (atomicAdd(g_ycnt + grp, 1u) & ~3u) + 4u;
            uint32_t t0, t1, v;
            asm volatile("mov.u32 %0, %%globaltimer_lo;" : "=r"(t0));
            do {
                asm volatile("ld.acquire.gpu.global.u32 %0, [%1];" : "=r"(v) : "l"(g_ycnt + grp) : "memory");
                asm volatile("mov.u32 %0, %%globaltimer_lo;" : "=r"(t1));
            } while ((int)(v - target) < 0 && t1 - t0 < 4000000u);
        }
        named_sync(5, 128);
        uint4 y[8];
#pragma unroll
        for (int i = 0; i < 8; i++)
            y[i] = __ldcg(g_y + ((blockIdx.x * 4 + 2 * (t & 1) + ((i >> 1) & 1)) * 2 + (i & 1)) * 128 + (ct & ~1) + (i >> 2));
#pragma unroll
        for (int i = 0; i < 8; i++) {
            const int a = 31 - (8 * me + 2 * ((t & 2) + (i >> 2)) + (i & 1)), b = 16 * wq + g + 8 * ((i >> 1) & 1);
            const uint4 p = y[(i & 4) + ((i >> 1) & 1)], q = y[(i & 4) + 2 + ((i >> 1) & 1)];
            *reinterpret_cast<uint4*>(out + (size_t)(64 * a + b) * 1024 + 512 + grp * 16 + (t & 1) * 8) =
                (i & 1) ? make_uint4(p.z, p.w, q.z, q.w) : make_uint4(p.x, p.y, q.x, q.y);
        }
      } else {
        named_arrive(4, 384);
        float acc[64];
#pragma unroll 1
        for (int it = 0; it < 32; it++) {
            const int st = it & (OP_NS - 1);
            mbar_wait(full + 8 * st, (it / OP_NS) & 1);
            STAMP(blockIdx.x == 10 && tid == 0, 1009 + it);
            wg_fence();
            const uint32_t base = sb + st * 32768;
            const uint64_t da = desc_kmajor(base + wg * 8192), db = desc_mnmajor(base + 16384, 8192);
#pragma unroll
            for (int k = 0; k < 4; k++) wgmma_ss128<1>(acc, da + k * 2, db + k * 128, (it | k) != 0);
            wg_commit();
            if (it > 0 && it + OP_NS - 1 < 32) {
                wg_wait<1>();
                if (lane == 0) mbar_arrive(empty + 8 * ((it - 1) & (OP_NS - 1)));
            }
        }
        wg_wait<0>();
        mbar_wait(xfree, 0);
        uint32_t peer, pbar;
        asm volatile("mapa.shared::cluster.u32 %0, %1, %2;" : "=r"(peer) : "r"(sX + tid * 16), "r"(rank ^ 1));
        asm volatile("mapa.shared::cluster.u32 %0, %1, %2;" : "=r"(pbar) : "r"(xfull), "r"(rank ^ 1));
#pragma unroll
        for (int i = 0; i < 8; i++) {
            const float* s = acc + 4 * i;
            const float a = kr ? s[0] : s[32], b = kr ? s[1] : s[33], c = kr ? s[2] : s[34], d = kr ? s[3] : s[35];
            asm volatile("st.async.weak.shared::cluster.mbarrier::complete_tx::bytes.v4.f32 [%0], {%1,%2,%3,%4}, [%5];"
                         ::"r"(peer + i * 4096), "f"(a), "f"(b), "f"(c), "f"(d), "r"(pbar) : "memory");
        }
        STAMP(blockIdx.x == 10 && tid == 0, 1006);
        mbar_wait(xfull, 0);
        STAMP(blockIdx.x == 10 && tid == 0, 1007);
        float r[32];
#pragma unroll
        for (int i = 0; i < 8; i++) {
            float a, b, c, d;
            asm volatile("ld.shared.v4.f32 {%0,%1,%2,%3}, [%4];" : "=f"(a), "=f"(b), "=f"(c), "=f"(d) : "r"(sX + tid * 16 + i * 4096));
            const float* s = acc + 4 * i;
            r[4 * i] = a + (kr ? s[32] : s[0]); r[4 * i + 1] = b + (kr ? s[33] : s[1]);
            r[4 * i + 2] = c + (kr ? s[34] : s[2]); r[4 * i + 3] = d + (kr ? s[35] : s[3]);
        }
        const uint32_t stg = sb + wg * 8192;
        store_slab64(stg, (warp & 3) * 16, r, 1.f, 1.f, lane);
        fence_proxy_async();
        named_sync(1 + wg, 128);
        if ((tid & 127) == 0) {
            tma_store_2d(&tm_out, stg, n0 + kr * 64, m0 + wg * 64);
            bulk_commit();
            bulk_wait<0>();
            STAMP(blockIdx.x == 10 && tid == 0, 1008);
        }
      }
    }
}

typedef CUresult (*EncodeFn)(CUtensorMap*, CUtensorMapDataType, cuuint32_t, void*, const cuuint64_t*, const cuuint64_t*,
                             const cuuint32_t*, const cuuint32_t*, CUtensorMapInterleave, CUtensorMapSwizzle,
                             CUtensorMapL2promotion, CUtensorMapFloatOOBfill);

static void make_map(EncodeFn fn, CUtensorMap* m, const void* p, uint64_t cols, uint64_t rows, uint32_t box_rows) {
    cuuint64_t dims[2] = {cols, rows};
    cuuint64_t strides[1] = {cols * 2};
    cuuint32_t box[2] = {64, box_rows};
    cuuint32_t es[2] = {1, 1};
    fn(m, CU_TENSOR_MAP_DATA_TYPE_BFLOAT16, 2, const_cast<void*>(p), dims, strides, box, es, CU_TENSOR_MAP_INTERLEAVE_NONE,
       CU_TENSOR_MAP_SWIZZLE_128B, CU_TENSOR_MAP_L2_PROMOTION_L2_256B, CU_TENSOR_MAP_FLOAT_OOB_FILL_NONE);
}

extern "C" void kernel_launch(void* const* d_in, const int* in_sizes, int n_in, void* d_out, int out_size) {
    void* fp = nullptr;
    cudaDriverEntryPointQueryResult qr;
    cudaGetDriverEntryPoint("cuTensorMapEncodeTiled", &fp, cudaEnableDefault, &qr);
    EncodeFn fn = (EncodeFn)fp;
    void *p_kv, *p_ctx;
    cudaGetSymbolAddress(&p_kv, g_kv);
    cudaGetSymbolAddress(&p_ctx, g_ctx);
    CUtensorMap tm_kv_st, tm_x, tm_c, tm_wq, tm_wk, tm_wv, tm_wo, tm_kv, tm_ctx, tm_out;
    make_map(fn, &tm_x, d_in[0], DM, SEQ, 128);
    make_map(fn, &tm_c, d_in[1], DM, SEQ, 128);
    make_map(fn, &tm_wq, d_in[2], HDALL, DM, 64);
    make_map(fn, &tm_wk, d_in[3], HDALL, DM, 64);
    make_map(fn, &tm_wv, d_in[4], HDALL, DM, 64);
    make_map(fn, &tm_wo, d_in[5], DM, HDALL, 64);
    make_map(fn, &tm_kv, p_kv, 2 * HDALL, SEQ, 128);
    make_map(fn, &tm_kv_st, p_kv, 2 * HDALL, SEQ, 64);
    make_map(fn, &tm_ctx, p_ctx, HDALL, SEQ, 64);
    make_map(fn, &tm_out, d_out, 1024, SEQ, 64);
    CUtensorMap tm_u;
    {
        cuuint64_t dims[2] = {512, 2048}, strides[1] = {1024};
        cuuint32_t box[2] = {8, 256}, es[2] = {1, 1};
        fn(&tm_u, CU_TENSOR_MAP_DATA_TYPE_BFLOAT16, 2, d_in[6], dims, strides, box, es, CU_TENSOR_MAP_INTERLEAVE_NONE,
           CU_TENSOR_MAP_SWIZZLE_NONE, CU_TENSOR_MAP_L2_PROMOTION_NONE, CU_TENSOR_MAP_FLOAT_OOB_FILL_NONE);
    }
    SsmParams sp;
    sp.u = (const bf16*)d_in[6]; sp.lar = (const bf16*)d_in[7]; sp.aim = (const bf16*)d_in[8];
    sp.cre = (const bf16*)d_in[9]; sp.cim = (const bf16*)d_in[10]; sp.ldt = (const bf16*)d_in[11]; sp.dskip = (const bf16*)d_in[12];
    cudaFuncSetAttribute(gemm_kv_kernel, cudaFuncAttributeMaxDynamicSharedMemorySize, G1_SMEM);
    cudaFuncSetAttribute(attn_kernel, cudaFuncAttributeMaxDynamicSharedMemorySize, AT_SMEM);
    cudaFuncSetAttribute(outproj_kernel, cudaFuncAttributeMaxDynamicSharedMemorySize, OP_SMEM);
    cudaStream_t st = cudaStreamPerThread;
    gemm_kv_kernel<<<128, G1_THREADS, G1_SMEM, st>>>(tm_c, tm_wk, tm_wv, tm_kv_st, (const bf16*)d_in[0], (const bf16*)d_in[2]);
    cudaLaunchAttribute at[1];
    at[0].id = cudaLaunchAttributeProgrammaticStreamSerialization;
    at[0].val.programmaticStreamSerializationAllowed = 1;
    cudaLaunchConfig_t cfg = {};
    cfg.stream = st; cfg.attrs = at; cfg.numAttrs = 1;
    cfg.gridDim = dim3(132); cfg.blockDim = dim3(384); cfg.dynamicSmemBytes = AT_SMEM;
    cudaLaunchKernelEx(&cfg, attn_kernel, tm_x, tm_wq, tm_kv, tm_ctx, sp.u, (const bf16*)d_in[5]);
    cfg.gridDim = dim3(128); cfg.blockDim = dim3(512); cfg.dynamicSmemBytes = OP_SMEM;
    cudaLaunchKernelEx(&cfg, outproj_kernel, tm_ctx, tm_wo, tm_out, tm_u, sp, (bf16*)d_out);
}
```

```cpp
#include <cuda_runtime.h>
#include <cuda_bf16.h>
#include <cuda.h>
#include <stdint.h>

typedef __nv_bfloat16 bf16;

#define DEVI __device__ __forceinline__

constexpr int SEQ = 2048, DM = 512, NH = 32, HD = 128, HDALL = NH * HD;
constexpr int SSM_D = 512, SSM_N = 128;
constexpr int WTAB = 2112;

__device__ bf16 g_kv[(size_t)SEQ * 2 * HDALL];
__device__ bf16 g_ctx[(size_t)SEQ * HDALL];
__device__ uint4 g_y[32 * 4 * 4 * 2 * 128];
__device__ unsigned int g_ycnt[32];
__device__ unsigned int g_sched;

#define STAMP(cond, i)
DEVI uint32_t smem_u32(const void* p) { return (uint32_t)__cvta_generic_to_shared(p); }
DEVI void mbar_init(uint32_t a, uint32_t cnt) { asm volatile("mbarrier.init.shared::cta.b64 [%0], %1;" ::"r"(a), "r"(cnt)); }
DEVI void mbar_expect_tx(uint32_t a, uint32_t bytes) {
    asm volatile("mbarrier.arrive.expect_tx.shared::cta.b64 _, [%0], %1;" ::"r"(a), "r"(bytes) : "memory");
}
DEVI void mbar_arrive(uint32_t a) { asm volatile("mbarrier.arrive.shared::cta.b64 _, [%0];" ::"r"(a) : "memory"); }
DEVI void mbar_arrive_cluster(uint32_t a, uint32_t cta) {
    asm volatile("{\n.reg .b32 r;\nmapa.shared::cluster.u32 r, %0, %1;\n"
                 "mbarrier.arrive.shared::cluster.b64 _, [r];\n}" ::"r"(a), "r"(cta) : "memory");
}
#define MBAR_WAIT_ASM(OP)                                                                              \
    asm volatile("{\n.reg .pred p, q;\n.reg .u32 t0, t1;\n" OP " p, [%0], %1;\n@p bra D_%=;\n"         \
                 "mov.u32 t0, %%globaltimer_lo;\nW_%=:\n" OP " p, [%0], %1;\n"                         \
                 "mov.u32 t1, %%globaltimer_lo;\nsub.u32 t1, t1, t0;\n"                                \
                 "setp.gt.or.u32 q, t1, 4000000, p;\n@!q bra W_%=;\nD_%=:\n}" ::"r"(a), "r"(parity) : "memory")
DEVI void mbar_wait(uint32_t a, uint32_t parity) { MBAR_WAIT_ASM("mbarrier.try_wait.parity.shared::cta.b64"); }
DEVI void mbar_wait_cluster(uint32_t a, uint32_t parity) { MBAR_WAIT_ASM("mbarrier.try_wait.parity.acquire.cluster.shared::cta.b64"); }
DEVI void fence_barrier_init() { asm volatile("fence.mbarrier_init.release.cluster;" ::: "memory"); }
DEVI void fence_proxy_async() { asm volatile("fence.proxy.async.shared::cta;" ::: "memory"); }
DEVI void cluster_sync_all() {
    asm volatile("barrier.cluster.arrive.relaxed.aligned;\nbarrier.cluster.wait.aligned;" ::: "memory");
}
DEVI void cluster_arrive() { asm volatile("barrier.cluster.arrive.relaxed.aligned;" ::: "memory"); }
DEVI void cluster_wait() { asm volatile("barrier.cluster.wait.aligned;" ::: "memory"); }
DEVI uint32_t cluster_rank() { uint32_t r; asm volatile("mov.u32 %0, %%cluster_ctarank;" : "=r"(r)); return r; }
DEVI void tma_load_2d(uint32_t dst, const CUtensorMap* m, int c0, int c1, uint32_t bar) {
    asm volatile("cp.async.bulk.tensor.2d.shared::cluster.global.mbarrier::complete_tx::bytes [%0], [%1, {%3, %4}], [%2];"
                 ::"r"(dst), "l"(m), "r"(bar), "r"(c0), "r"(c1) : "memory");
}
DEVI void tma_load_2d_mc(uint32_t dst, const CUtensorMap* m, int c0, int c1, uint32_t bar, uint16_t mask) {
    asm volatile("cp.async.bulk.tensor.2d.shared::cluster.global.mbarrier::complete_tx::bytes.multicast::cluster [%0], [%1, {%3, %4}], [%2], %5;"
                 ::"r"(dst), "l"(m), "r"(bar), "r"(c0), "r"(c1), "h"(mask) : "memory");
}
DEVI void tma_prefetch_2d(const CUtensorMap* m, int c0, int c1) {
    asm volatile("cp.async.bulk.prefetch.tensor.2d.L2.global [%0, {%1, %2}];" ::"l"(m), "r"(c0), "r"(c1) : "memory");
}
DEVI void tma_store_2d(const CUtensorMap* m, uint32_t src, int c0, int c1) {
    asm volatile("cp.async.bulk.tensor.2d.global.shared::cta.bulk_group [%0, {%2, %3}], [%1];"
                 ::"l"(m), "r"(src), "r"(c0), "r"(c1) : "memory");
}
DEVI void bulk_load(uint32_t dst, const void* src, uint32_t bytes, uint32_t bar) {
    asm volatile("cp.async.bulk.shared::cluster.global.mbarrier::complete_tx::bytes [%0], [%1], %2, [%3];"
                 ::"r"(dst), "l"(src), "r"(bytes), "r"(bar) : "memory");
}
DEVI void bulk_prefetch(const void* src, uint32_t bytes) {
    asm volatile("cp.async.bulk.prefetch.L2.global [%0], %1;" ::"l"(src), "r"(bytes) : "memory");
}
DEVI void bulk_commit() { asm volatile("cp.async.bulk.commit_group;" ::: "memory"); }
template <int N> DEVI void bulk_wait_read() { asm volatile("cp.async.bulk.wait_group.read %0;" ::"n"(N) : "memory"); }
template <int N> DEVI void bulk_wait() { asm volatile("cp.async.bulk.wait_group %0;" ::"n"(N) : "memory"); }
DEVI void prefetch_tmap(const CUtensorMap* m) { asm volatile("prefetch.tensormap [%0];" ::"l"(m) : "memory"); }
DEVI void named_sync(int id, int n) { asm volatile("bar.sync %0, %1;" ::"r"(id), "r"(n) : "memory"); }
DEVI void named_arrive(int id, int n) { asm volatile("bar.arrive %0, %1;" ::"r"(id), "r"(n) : "memory"); }
DEVI void pdl_wait() { asm volatile("griddepcontrol.wait;" ::: "memory"); }
DEVI void pdl_launch() { asm volatile("griddepcontrol.launch_dependents;" ::: "memory"); }
template <int R> DEVI void reg_inc() { asm volatile("setmaxnreg.inc.sync.aligned.u32 %0;" ::"n"(R)); }
template <int R> DEVI void reg_dec() { asm volatile("setmaxnreg.dec.sync.aligned.u32 %0;" ::"n"(R)); }

DEVI void wg_fence() { asm volatile("wgmma.fence.sync.aligned;" ::: "memory"); }
DEVI void wg_commit() { asm volatile("wgmma.commit_group.sync.aligned;" ::: "memory"); }
template <int N> DEVI void wg_wait() { asm volatile("wgmma.wait_group.sync.aligned %0;" ::"n"(N) : "memory"); }

DEVI uint64_t make_desc(uint32_t addr, uint32_t lbo, uint32_t sbo, uint32_t swz) {
    return (uint64_t)((addr & 0x3FFFF) >> 4) | ((uint64_t)(lbo >> 4) << 16) | ((uint64_t)(sbo >> 4) << 32) | ((uint64_t)swz << 62);
}
DEVI uint64_t desc_kmajor(uint32_t addr) { return make_desc(addr, 16, 1024, 1); }
DEVI uint64_t desc_mnmajor(uint32_t addr, uint32_t lbo) { return make_desc(addr, lbo, 1024, 1); }

#define ACC8(d, o) "+f"(d[o + 0]), "+f"(d[o + 1]), "+f"(d[o + 2]), "+f"(d[o + 3]), "+f"(d[o + 4]), "+f"(d[o + 5]), "+f"(d[o + 6]), "+f"(d[o + 7])
#define ACC64(d) ACC8(d, 0), ACC8(d, 8), ACC8(d, 16), ACC8(d, 24), ACC8(d, 32), ACC8(d, 40), ACC8(d, 48), ACC8(d, 56)
#define R64 "{%0,%1,%2,%3,%4,%5,%6,%7,%8,%9,%10,%11,%12,%13,%14,%15,%16,%17,%18,%19,%20,%21,%22,%23,%24,%25,%26,%27,%28,%29,%30,%31," \
            "%32,%33,%34,%35,%36,%37,%38,%39,%40,%41,%42,%43,%44,%45,%46,%47,%48,%49,%50,%51,%52,%53,%54,%55,%56,%57,%58,%59,%60,%61,%62,%63}"

template <int TB> DEVI void wgmma_ss128(float* d, uint64_t da, uint64_t db, int acc) {
    asm volatile("{\n.reg .pred p;\nsetp.ne.b32 p, %66, 0;\n"
                 "wgmma.mma_async.sync.aligned.m64n128k16.f32.bf16.bf16 " R64 ", %64, %65, p, 1, 1, 0, %67;\n}"
                 : ACC64(d) : "l"(da), "l"(db), "r"(acc), "n"(TB));
}
template <int TB> DEVI void wgmma_rs128(float* d, const uint32_t* a, uint64_t db, int acc) {
    asm volatile("{\n.reg .pred p;\nsetp.ne.b32 p, %69, 0;\n"
                 "wgmma.mma_async.sync.aligned.m64n128k16.f32.bf16.bf16 " R64 ", {%64,%65,%66,%67}, %68, p, 1, 1, %70;\n}"
                 : ACC64(d) : "r"(a[0]), "r"(a[1]), "r"(a[2]), "r"(a[3]), "l"(db), "r"(acc), "n"(TB));
}
DEVI uint32_t pack_bf16(float lo, float hi) {
    uint32_t r;
    asm("cvt.rn.bf16x2.f32 %0, %1, %2;" : "=r"(r) : "f"(hi), "f"(lo));
    return r;
}
DEVI void stmatrix_x4(uint32_t addr, uint32_t r0, uint32_t r1, uint32_t r2, uint32_t r3) {
    asm volatile("stmatrix.sync.aligned.m8n8.x4.shared.b16 [%0], {%1,%2,%3,%4};" ::"r"(addr), "r"(r0), "r"(r1), "r"(r2), "r"(r3) : "memory");
}
DEVI float ex2(float x) { float y; asm("ex2.approx.ftz.f32 %0, %1;" : "=f"(y) : "f"(x)); return y; }

DEVI void store_slab64(uint32_t base, int row0, const float* d, float s0, float s1, int lane) {
    int mi = lane >> 3, r = lane & 7;
    int row = row0 + (mi & 1) * 8 + r;
#pragma unroll
    for (int j = 0; j < 8; j += 2) {
        uint32_t r0 = pack_bf16(d[4 * j + 0] * s0, d[4 * j + 1] * s0);
        uint32_t r1 = pack_bf16(d[4 * j + 2] * s1, d[4 * j + 3] * s1);
        uint32_t r2 = pack_bf16(d[4 * j + 4] * s0, d[4 * j + 5] * s0);
        uint32_t r3 = pack_bf16(d[4 * j + 6] * s1, d[4 * j + 7] * s1);
        int chunk = j + (mi >> 1);
        stmatrix_x4(base + row * 128 + ((chunk ^ (row & 7)) << 4), r0, r1, r2, r3);
    }
}
struct cf { float x, y; };
DEVI cf cmul(cf a, cf b) { cf r; r.x = fmaf(a.x, b.x, -a.y * b.y); r.y = fmaf(a.x, b.y, a.y * b.x); return r; }
DEVI cf csq(cf a) { cf r; r.x = fmaf(a.x, a.x, -a.y * a.y); r.y = (a.x + a.x) * a.y; return r; }
DEVI cf cexp_(float re, float im) {
    float m = __expf(re), s, c;
    __sincosf(im, &s, &c);
    cf r; r.x = m * c; r.y = m * s; return r;
}
DEVI uint32_t h2(cf v) { uint32_t r; asm("cvt.rn.f16x2.f32 %0, %1, %2;" : "=r"(r) : "f"(v.y), "f"(v.x)); return r; }
DEVI uint32_t h2c(cf v) { uint32_t r; asm("cvt.rn.f16x2.f32 %0, %1, %2;" : "=r"(r) : "f"(-v.y), "f"(v.x)); return r; }
DEVI void mma_group(float (*c)[4], const uint32_t (*a)[4], const uint32_t (*b)[2]) {
    asm volatile(
        "mma.sync.aligned.m16n8k16.row.col.f32.f16.f16.f32 {%0,%1,%2,%3}, {%20,%21,%22,%23}, {%40,%41}, {%0,%1,%2,%3};\n"
        "mma.sync.aligned.m16n8k16.row.col.f32.f16.f16.f32 {%4,%5,%6,%7}, {%24,%25,%26,%27}, {%40,%41}, {%4,%5,%6,%7};\n"
        "mma.sync.aligned.m16n8k16.row.col.f32.f16.f16.f32 {%8,%9,%10,%11}, {%28,%29,%30,%31}, {%42,%43}, {%8,%9,%10,%11};\n"
        "mma.sync.aligned.m16n8k16.row.col.f32.f16.f16.f32 {%12,%13,%14,%15}, {%32,%33,%34,%35}, {%44,%45}, {%12,%13,%14,%15};\n"
        "mma.sync.aligned.m16n8k16.row.col.f32.f16.f16.f32 {%16,%17,%18,%19}, {%36,%37,%38,%39}, {%46,%47}, {%16,%17,%18,%19};\n"
        : "+f"(c[0][0]), "+f"(c[0][1]), "+f"(c[0][2]), "+f"(c[0][3]), "+f"(c[1][0]), "+f"(c[1][1]), "+f"(c[1][2]), "+f"(c[1][3]),
          "+f"(c[2][0]), "+f"(c[2][1]), "+f"(c[2][2]), "+f"(c[2][3]), "+f"(c[3][0]), "+f"(c[3][1]), "+f"(c[3][2]), "+f"(c[3][3]),
          "+f"(c[4][0]), "+f"(c[4][1]), "+f"(c[4][2]), "+f"(c[4][3])
        : "r"(a[0][0]), "r"(a[0][1]), "r"(a[0][2]), "r"(a[0][3]), "r"(a[1][0]), "r"(a[1][1]), "r"(a[1][2]), "r"(a[1][3]),
          "r"(a[2][0]), "r"(a[2][1]), "r"(a[2][2]), "r"(a[2][3]), "r"(a[3][0]), "r"(a[3][1]), "r"(a[3][2]), "r"(a[3][3]),
          "r"(a[4][0]), "r"(a[4][1]), "r"(a[4][2]), "r"(a[4][3]),
          "r"(b[0][0]), "r"(b[0][1]), "r"(b[1][0]), "r"(b[1][1]), "r"(b[2][0]), "r"(b[2][1]), "r"(b[3][0]), "r"(b[3][1]));
}
DEVI float bf2f(bf16 v) { return __bfloat162float(v); }
DEVI float rbf(float v) { return __bfloat162float(__float2bfloat16_rn(v)); }

struct SsmParams { const bf16 *lar, *aim, *cre, *cim, *ldt, *dskip, *u; };

DEVI int kp_index(int l) {
    int p = (int)rbf((float)l);
    return p < 256 ? p : (p < 512 ? 128 + (p >> 1) : (p < 1024 ? 256 + (p >> 2) : 384 + (p >> 3)));
}

DEVI void reds(uint32_t a, float v) { asm volatile("red.shared.add.f32 [%0], %1;" ::"r"(a), "f"(v) : "memory"); }
DEVI void ssm_kgen_warp(const SsmParams& P, int d, int half, int lane, uint32_t kp) {
    const int g = lane >> 2, t = lane & 3;
    float ar[2], ai[2], cr[2], ci[2], gr[2], gi[2];
    bf16 raw[2][4];
    const bf16 rdt = P.ldt[d];
#pragma unroll
    for (int q = 0; q < 2; q++) {
        const int n = d * SSM_N + 64 * half + 32 * q + lane;
        raw[q][0] = P.lar[n]; raw[q][1] = P.aim[n]; raw[q][2] = P.cre[n]; raw[q][3] = P.cim[n];
    }
    const float dt = rbf(expf(bf2f(rdt)));
#pragma unroll
    for (int q = 0; q < 2; q++) {
        ar[q] = -rbf(expf(bf2f(raw[q][0]))) * dt;
        ai[q] = bf2f(raw[q][1]) * dt;
        cr[q] = 2.f * (bf2f(raw[q][2]) * dt);
        ci[q] = 2.f * (bf2f(raw[q][3]) * dt);
        float m = expf(ar[q] * 64.f), sn, cs;
        sincosf(ai[q] * 64.f, &sn, &cs);
        gr[q] = m * cs; gi[q] = m * sn;
    }
    float cm = 0.f;
#pragma unroll
    for (int q = 0; q < 2; q++) cm = fmaxf(cm, fmaxf(fabsf(cr[q]), fabsf(ci[q])));
#pragma unroll
    for (int o = 16; o; o >>= 1) cm = fmaxf(cm, __shfl_xor_sync(~0u, cm, o));
    const int ex = min(max((int)(__float_as_uint(cm) >> 23), 1), 253);
    const float cs_dn = __uint_as_float((uint32_t)(254 - ex) << 23), cs_up = __uint_as_float((uint32_t)ex << 23);
    float acc[5][4];
#pragma unroll
    for (int s = 0; s < 5; s++) { acc[s][0] = acc[s][1] = acc[s][2] = acc[s][3] = 0.f; }
    float klast = 0.f;
    const float gf = (float)g;
#pragma unroll
    for (int q = 0; q < 2; q++) {
#pragma unroll 1
        for (int g0 = 0; g0 < 8; g0 += 2) {
            uint32_t fa[5][4], fb[4][2];
#pragma unroll
            for (int h = 0; h < 2; h++) {
                const int src = ((g0 + h) << 2) | t;
                const float a_r = __shfl_sync(~0u, ar[q], src), a_i = __shfl_sync(~0u, ai[q], src);
                cf C, G;
                C.x = __shfl_sync(~0u, cr[q], src) * cs_dn; C.y = __shfl_sync(~0u, ci[q], src) * cs_dn;
                G.x = __shfl_sync(~0u, gr[q], src); G.y = __shfl_sync(~0u, gi[q], src);
                cf E = cexp_(a_r * gf, a_i * gf);
                cf B = csq(csq(csq(E)));
                fb[0][h] = h2c(cmul(C, B));
                cf EG = cmul(E, G);
                fa[0][2 * h] = h2(E); fa[0][2 * h + 1] = h2(EG);
                cf G2 = csq(G);
                cf X = cmul(E, G2), Xh = cmul(EG, G2);
                fa[1][2 * h] = h2(X); fa[1][2 * h + 1] = h2(Xh);
#pragma unroll
                for (int s = 2; s < 5; s++) {
                    B = csq(B); X = csq(X); Xh = csq(Xh);
                    fb[s - 1][h] = h2c(cmul(C, B));
                    fa[s][2 * h] = h2(X); fa[s][2 * h + 1] = h2(Xh);
                }
                X = csq(X);
                klast += fmaf(C.x, X.x, -C.y * X.y);
            }
            mma_group(acc, fa, fb);
        }
    }
    klast += __shfl_xor_sync(~0u, klast, 1);
    klast += __shfl_xor_sync(~0u, klast, 2);
#pragma unroll
    for (int s = 0; s < 5; s++) {
        const uint32_t b = kp + (128 * s + g + 16 * t) * 4;
        reds(b, acc[s][0] * cs_up); reds(b + 32, acc[s][1] * cs_up); reds(b + 256, acc[s][2] * cs_up); reds(b + 288, acc[s][3] * cs_up);
    }
    if (lane == 0) reds(kp + 2560, klast * cs_up);
}

constexpr int G1_THREADS = 384;
constexpr int G1_NS = 11;
constexpr int G1_SMEM = G1_NS * 16384 + 32768 + 256 + 1024;

__global__ void __cluster_dims__(2, 1, 1) __launch_bounds__(G1_THREADS, 1)
gemm_kv_kernel(const __grid_constant__ CUtensorMap tm_c, const __grid_constant__ CUtensorMap tm_wk,
               const __grid_constant__ CUtensorMap tm_wv, const __grid_constant__ CUtensorMap tm_kv_st,
               const bf16* __restrict__ px, const bf16* __restrict__ pwq) {
    extern __shared__ uint8_t smem_raw[];
    const uint32_t sb = (smem_u32(smem_raw) + 1023) & ~1023u;
    const uint32_t sC = sb + G1_NS * 16384, bars = sC + 32768;
    const uint32_t full = bars, empty = bars + 128;
    const int tid = threadIdx.x, warp = tid >> 5, lane = tid & 31, wg = tid >> 7;
    const uint32_t rank = cluster_rank();
    const int cl = blockIdx.x >> 1;
    const int m0 = ((cl & 7) * 2 + rank) * 128;
    const int ng = cl >> 3;
    STAMP(blockIdx.x == 10 && tid == 0, 0);
    if (tid == 0) {
        for (int i = 0; i < G1_NS; i++) { mbar_init(full + 8 * i, 1); mbar_init(empty + 8 * i, 16); }
        fence_barrier_init();
        for (int it = 0; it < 8; it++) {
            mbar_expect_tx(full + 8 * it, 16384);
            tma_load_2d(sb + it * 16384, &tm_c, it * 64, m0, full + 8 * it);
        }
    }
    __syncthreads();
    cluster_sync_all();
    pdl_launch();
    if (wg == 2) {
        reg_dec<40>();
        if (tid == 256) {
            const CUtensorMap* tw = ng < 4 ? &tm_wk : &tm_wv;
            const int n0 = (ng & 3) * 1024 + rank * 64;
            int st = 8; uint32_t ph = 1;
            for (int it = 0; it < 64; it++) {
                mbar_wait(empty + 8 * st, ph);
                mbar_expect_tx(full + 8 * st, 16384);
                tma_load_2d_mc(sb + st * 16384 + rank * 8192, tw, n0 + (it >> 3) * 128, (it & 7) * 64, full + 8 * st, 3);
                if (it < 2) {
                    for (int j = 3 + it * 8 + (cl & 7); j < 19; j += 16) tma_prefetch_2d(tw, n0 + (j >> 3) * 128, (j & 7) * 64);
                }
                if (it >= 3 && it + 16 < 64 && (it & 7) == (cl & 7)) tma_prefetch_2d(tw, n0 + ((it + 16) >> 3) * 128, (it & 7) * 64);
                if (it == 24) bulk_prefetch(px + blockIdx.x * 8192, 16384);
                if (it == 32) bulk_prefetch(pwq + blockIdx.x * 16384, 32768);
                if (++st == G1_NS) { st = 0; ph ^= 1; }
            }
        }
        __syncwarp();
    } else {
        reg_inc<232>();
        uint32_t af[128];
        float acc[64];
        const int wq = warp & 3;
        const int row = wg * 64 + wq * 16 + (lane & 15);
        const uint32_t stg = sC + wg * 16384;
        int st = 8, pst = 0; uint32_t ph = 0;
#pragma unroll
        for (int kc = 0; kc < 8; kc++) {
            mbar_wait(full + 8 * kc, 0);
#pragma unroll
            for (int k = 0; k < 4; k++) {
                const uint32_t a = sb + kc * 16384 + row * 128 + (((2 * k + (lane >> 4)) ^ (row & 7)) << 4);
                uint32_t* f = af + kc * 16 + k * 4;
                asm volatile("ldmatrix.sync.aligned.m8n8.x4.shared.b16 {%0,%1,%2,%3}, [%4];"
                             : "=r"(f[0]), "=r"(f[1]), "=r"(f[2]), "=r"(f[3]) : "r"(a) : "memory");
            }
            __syncwarp();
            if (lane < 2) mbar_arrive_cluster(empty + 8 * kc, lane);
        }
#pragma unroll 1
        for (int t = 0; t < 8; t++) {
            if (wg == 1 || t > 0) named_sync(3 + wg, 256);
#pragma unroll
            for (int kc = 0; kc < 8; kc++) {
                mbar_wait(full + 8 * st, ph);
                STAMP(blockIdx.x == 10 && (tid & 127) == 0, 1 + wg * 96 + t * 12 + kc);
                wg_fence();
                const uint64_t db = desc_mnmajor(sb + st * 16384, 8192);
#pragma unroll
                for (int k = 0; k < 4; k++) wgmma_rs128<1>(acc, af + kc * 16 + k * 4, db + k * 128, (kc | k) != 0);
                wg_commit();
                if (kc == 3 && (wg == 0 || t < 7)) named_arrive(3 + (wg ^ 1), 256);
                if (kc > 0) {
                    wg_wait<1>();
                    if (lane < 2) mbar_arrive_cluster(empty + 8 * pst, lane);
                }
                pst = st;
                if (++st == G1_NS) { st = 0; ph ^= 1; }
            }
            if ((tid & 127) == 0) bulk_wait_read<0>();
            named_sync(1 + wg, 128);
            wg_wait<0>();
            STAMP(blockIdx.x == 10 && (tid & 127) == 0, 9 + wg * 96 + t * 12);
            if (lane < 2) mbar_arrive_cluster(empty + 8 * pst, lane);
            store_slab64(stg, wq * 16, acc, 1.f, 1.f, lane);
            store_slab64(stg + 8192, wq * 16, acc + 32, 1.f, 1.f, lane);
            fence_proxy_async();
            named_sync(1 + wg, 128);
            if ((tid & 127) == 0) {
                tma_store_2d(&tm_kv_st, stg, ng * 1024 + t * 128, m0 + wg * 64);
                tma_store_2d(&tm_kv_st, stg + 8192, ng * 1024 + t * 128 + 64, m0 + wg * 64);
                bulk_commit();
            }
            STAMP(blockIdx.x == 10 && (tid & 127) == 0, 10 + wg * 96 + t * 12);
        }
        if ((tid & 127) == 0) bulk_wait<0>();
        __syncwarp();
    }
    asm volatile("barrier.cluster.arrive.relaxed.aligned;\nbarrier.cluster.wait.aligned;" ::: "memory");
}
constexpr int AT_NS = 6;
constexpr int AT_SMEM = AT_NS * 32768 + 32768 + 256 + 1024;
constexpr int AT_ITEMS = 512;

DEVI uint32_t hmax2(uint32_t a, uint32_t b) { uint32_t r; asm("max.bf16x2 %0, %1, %2;" : "=r"(r) : "r"(a), "r"(b)); return r; }
DEVI uint32_t hmul2(uint32_t a, uint32_t b) { uint32_t r; asm("mul.rn.bf16x2 %0, %1, %2;" : "=r"(r) : "r"(a), "r"(b)); return r; }
DEVI uint32_t hfma2(uint32_t a, uint32_t b, uint32_t c) { uint32_t r; asm("fma.rn.bf16x2 %0, %1, %2, %3;" : "=r"(r) : "r"(a), "r"(b), "r"(c)); return r; }
DEVI float blo(uint32_t v) { return __uint_as_float(v << 16); }
DEVI float bhi(uint32_t v) { return __uint_as_float(v & 0xffff0000u); }

template <bool FIRST>
DEVI void softmax_tile(float* s, float& m0, float& m1, float& l0, float& l1, float& al0, float& al1) {
    const uint32_t HI = 0x3DB53DB5u;
    const uint32_t LO = 0x371E371Eu;
    const float L2E = 1.4426950408889634f;
    uint32_t x0 = 0xFF80FF80u, x1 = 0xFF80FF80u;
#pragma unroll
    for (int j = 0; j < 16; j++) {
        uint32_t a = pack_bf16(s[4 * j], s[4 * j + 1]), b = pack_bf16(s[4 * j + 2], s[4 * j + 3]);
        a = hfma2(a, HI, hmul2(a, LO));
        b = hfma2(b, HI, hmul2(b, LO));
        s[4 * j] = __uint_as_float(a); s[4 * j + 2] = __uint_as_float(b);
        x0 = hmax2(x0, a); x1 = hmax2(x1, b);
    }
    uint32_t x = hmax2(__byte_perm(x0, x1, 0x5410), __byte_perm(x0, x1, 0x7632));
    x = hmax2(x, __shfl_xor_sync(~0u, x, 1));
    x = hmax2(x, __shfl_xor_sync(~0u, x, 2));
    float n0 = blo(x), n1 = bhi(x);
    if (!FIRST) {
        n0 = fmaxf(n0, m0); n1 = fmaxf(n1, m1);
        al0 = ex2((m0 - n0) * L2E); al1 = ex2((m1 - n1) * L2E);
    }
    m0 = n0; m1 = n1;
    const float c0 = -n0 * L2E, c1 = -n1 * L2E;
    float s0 = 0.f, s1 = 0.f;
#pragma unroll
    for (int j = 0; j < 16; j++) {
        uint32_t a = __float_as_uint(s[4 * j]), b = __float_as_uint(s[4 * j + 2]);
        float e0 = ex2(fmaf(blo(a), L2E, c0)), e1 = ex2(fmaf(bhi(a), L2E, c0));
        float e2 = ex2(fmaf(blo(b), L2E, c1)), e3 = ex2(fmaf(bhi(b), L2E, c1));
        s0 += e0 + e1; s1 += e2 + e3;
        s[4 * j] = e0; s[4 * j + 1] = e1; s[4 * j + 2] = e2; s[4 * j + 3] = e3;
    }
    if (FIRST) { l0 = s0; l1 = s1; }
    else { l0 = fmaf(l0, al0, s0); l1 = fmaf(l1, al1, s1); }
}

struct Ring {
    int st; uint32_t ph;
    DEVI void next() { if (++st == AT_NS) { st = 0; ph ^= 1; } }
};

__global__ void __launch_bounds__(384, 1)
attn_kernel(const __grid_constant__ CUtensorMap tm_x, const __grid_constant__ CUtensorMap tm_wq,
            const __grid_constant__ CUtensorMap tm_kv, const __grid_constant__ CUtensorMap tm_ctx_st,
            const bf16* __restrict__ pu, const bf16* __restrict__ pwo) {
    extern __shared__ uint8_t smem_raw[];
    const uint32_t sb = (smem_u32(smem_raw) + 1023) & ~1023u;
    const uint32_t sO = sb + AT_NS * 32768, bars = sO + 32768;
    const uint32_t full = bars, empty = bars + 64;
    volatile int* slots = reinterpret_cast<volatile int*>(smem_raw + (bars + 128 - smem_u32(smem_raw)));
    const int tid = threadIdx.x, warp = tid >> 5, lane = tid & 31, wg = tid >> 7;
    if (tid == 0) {
        for (int i = 0; i < AT_NS; i++) { mbar_init(full + 8 * i, 1); mbar_init(empty + 8 * i, 8); }
        fence_barrier_init();
    }
    __syncthreads();
    if (wg == 2) {
        reg_dec<24>();
        if (warp == 8 && lane == 0) {
            Ring r{0, 1};
            int n = 0;
            while (true) {
                int idx = (int)atomicInc(&g_sched, AT_ITEMS + gridDim.x - 1);
                if (idx >= AT_ITEMS - 128 && idx < AT_ITEMS) {
                    bulk_prefetch(pu + (idx - (AT_ITEMS - 128)) * 8192, 16384);
                    bulk_prefetch(pwo + (idx - (AT_ITEMS - 128)) * 16384, 32768);
                }
                mbar_wait(empty + 8 * r.st, r.ph);
                if (idx >= AT_ITEMS) {
                    slots[n & 3] = -1;
                    mbar_arrive(full + 8 * r.st);
                    break;
                }
                slots[n & 3] = idx;
                const int qi = 15 - (idx >> 5), h = idx & 31;
                for (int kc = 0; kc < 8; kc++) {
                    if (kc) mbar_wait(empty + 8 * r.st, r.ph);
                    const uint32_t fb = full + 8 * r.st, dst = sb + r.st * 32768;
                    mbar_expect_tx(fb, 32768);
                    tma_load_2d(dst, &tm_x, kc * 64, qi * 128, fb);
                    tma_load_2d(dst + 16384, &tm_wq, h * 128, kc * 64, fb);
                    tma_load_2d(dst + 24576, &tm_wq, h * 128 + 64, kc * 64, fb);
                    r.next();
                }
                if (n == 0) { pdl_wait(); pdl_launch(); }
                for (int j = qi; j >= -1; j--) {
#pragma unroll
                    for (int v = 0; v < 2; v++) {
                        const int jj = j + v;
                        if (jj < 0 || jj > qi || (v == 0 && j < 0)) continue;
                        mbar_wait(empty + 8 * r.st, r.ph);
                        const uint32_t fb = full + 8 * r.st, dst = sb + r.st * 32768;
                        mbar_expect_tx(fb, 32768);
                        tma_load_2d(dst, &tm_kv, v * HDALL + h * 128, jj * 128, fb);
                        tma_load_2d(dst + 16384, &tm_kv, v * HDALL + h * 128 + 64, jj * 128, fb);
                        r.next();
                    }
                }
                n++;
            }
            if (n == 0) { pdl_wait(); pdl_launch(); }
        }
    } else {
        reg_inc<240>();
        Ring r{0, 0};
        float o[64], s[64];
        uint32_t qf[32], pa[32];
        const int g = lane >> 2, t = lane & 3, wq = warp & 3;
        const uint32_t stg = sO + wg * 16384;
        if (wg == 1) named_arrive(3, 256);
        for (int n = 0;; n++) {
            mbar_wait(full + 8 * r.st, r.ph);
            const int idx = slots[n & 3];
            if (idx < 0) break;
            const int qi = 15 - (idx >> 5), h = idx & 31;
#pragma unroll 1
            for (int kc = 0; kc < 8; kc++) {
                if (kc) mbar_wait(full + 8 * r.st, r.ph);
                wg_fence();
                const uint32_t base = sb + r.st * 32768;
                const uint64_t da = desc_kmajor(base + wg * 8192), db = desc_mnmajor(base + 16384, 8192);
#pragma unroll
                for (int k = 0; k < 4; k++) wgmma_ss128<1>(s, da + k * 2, db + k * 128, (kc | k) != 0);
                wg_commit();
                if (kc) {
                    wg_wait<1>();
                    if (lane == 0) mbar_arrive(empty + 8 * (r.st == 0 ? AT_NS - 1 : r.st - 1));
                }
                r.next();
            }
            wg_wait<0>();
            if (lane == 0) mbar_arrive(empty + 8 * (r.st == 0 ? AT_NS - 1 : r.st - 1));
#pragma unroll
            for (int i = 0; i < 32; i++) qf[i] = pack_bf16(s[2 * i], s[2 * i + 1]);
            float m0, m1, l0, l1, al0, al1;
            auto issue_qk = [&]() {
                mbar_wait(full + 8 * r.st, r.ph);
                wg_fence();
                const uint64_t db = desc_kmajor(sb + r.st * 32768);
#pragma unroll
                for (int k = 0; k < 8; k++) wgmma_rs128<0>(s, qf + 4 * k, db + (k >> 2) * 1024 + (k & 3) * 2, k != 0);
                wg_commit();
            };
            auto issue_pv = [&](const uint32_t* p, int st, uint32_t ph, int acc) {
                mbar_wait(full + 8 * st, ph);
                wg_fence();
                const uint64_t db = desc_mnmajor(sb + st * 32768, 16384);
#pragma unroll
                for (int k = 0; k < 8; k++) wgmma_rs128<1>(o, p + 4 * k, db + k * 128, acc | k);
                wg_commit();
            };
            issue_qk();
            wg_wait<0>();
            if (lane == 0) mbar_arrive(empty + 8 * r.st);
            r.next();
            {
                const int row = wg * 64 + wq * 16 + g;
#pragma unroll
                for (int j = 0; j < 16; j++) {
                    const int c = 8 * j + 2 * t;
                    if (c > row) s[4 * j] = -INFINITY;
                    if (c + 1 > row) s[4 * j + 1] = -INFINITY;
                    if (c > row + 8) s[4 * j + 2] = -INFINITY;
                    if (c + 1 > row + 8) s[4 * j + 3] = -INFINITY;
                }
            }
            softmax_tile<true>(s, m0, m1, l0, l1, al0, al1);
#pragma unroll
            for (int i = 0; i < 32; i++) pa[i] = pack_bf16(s[2 * i], s[2 * i + 1]);
            int first = 0;
#pragma unroll 1
            for (int j = qi; j >= 1; j--) {
                named_sync(3 + wg, 256);
                issue_qk();
                const int kst = r.st;
                r.next();
                issue_pv(pa, r.st, r.ph, first);
                named_arrive(3 + (wg ^ 1), 256);
                wg_wait<1>();
                if (lane == 0) mbar_arrive(empty + 8 * kst);
                softmax_tile<false>(s, m0, m1, l0, l1, al0, al1);
                wg_wait<0>();
                if (lane == 0) mbar_arrive(empty + 8 * r.st);
                r.next();
#pragma unroll
                for (int i = 0; i < 32; i++) pa[i] = pack_bf16(s[2 * i], s[2 * i + 1]);
#pragma unroll
                for (int i = 0; i < 16; i++) {
                    o[4 * i] *= al0; o[4 * i + 1] *= al0; o[4 * i + 2] *= al1; o[4 * i + 3] *= al1;
                }
                first = 1;
            }
            issue_pv(pa, r.st, r.ph, first);
            l0 += __shfl_xor_sync(~0u, l0, 1); l0 += __shfl_xor_sync(~0u, l0, 2);
            l1 += __shfl_xor_sync(~0u, l1, 1); l1 += __shfl_xor_sync(~0u, l1, 2);
            const float i0 = 1.f / l0, i1 = 1.f / l1;
            if ((tid & 127) == 0) bulk_wait_read<0>();
            named_sync(1 + wg, 128);
            wg_wait<0>();
            if (lane == 0) mbar_arrive(empty + 8 * r.st);
            r.next();
            store_slab64(stg, wq * 16, o, i0, i1, lane);
            store_slab64(stg + 8192, wq * 16, o + 32, i0, i1, lane);
            fence_proxy_async();
            named_sync(1 + wg, 128);
            if ((tid & 127) == 0) {
                tma_store_2d(&tm_ctx_st, stg, h * 128, qi * 128 + wg * 64);
                tma_store_2d(&tm_ctx_st, stg + 8192, h * 128 + 64, qi * 128 + wg * 64);
                bulk_commit();
            }
        }
        if ((tid & 127) == 0) bulk_wait<0>();
    }
}
constexpr int OP_NS = 4;
constexpr int OP_ULD = 164 * 16;
constexpr int OP_UCH = 2 * OP_ULD;
constexpr int OP_SMEM = OP_NS * 32768 + 32768 + 4 * WTAB * 4 + 4 * OP_UCH + 4 * 648 * 4 + 256 + 1024;

template <int N> DEVI void wgmma_conv(float* d, const uint32_t* a, uint64_t db);
template <> DEVI void wgmma_conv<128>(float* d, const uint32_t* a, uint64_t db) {
    asm volatile("wgmma.mma_async.sync.aligned.m64n128k16.f32.bf16.bf16 {%0,%1,%2,%3,%4,%5,%6,%7,%8,%9,%10,%11,%12,%13,%14,%15,%16,%17,%18,%19,%20,%21,%22,%23,%24,%25,%26,%27,%28,%29,%30,%31,%32,%33,%34,%35,%36,%37,%38,%39,%40,%41,%42,%43,%44,%45,%46,%47,%48,%49,%50,%51,%52,%53,%54,%55,%56,%57,%58,%59,%60,%61,%62,%63}, "
                 "{%64,%65,%66,%67}, %68, 1, 1, 1, 0;"
                 : ACC8(d, 0), ACC8(d, 8), ACC8(d, 16), ACC8(d, 24), ACC8(d, 32), ACC8(d, 40), ACC8(d, 48), ACC8(d, 56) : "r"(a[0]), "r"(a[1]), "r"(a[2]), "r"(a[3]), "l"(db));
}
template <> DEVI void wgmma_conv<96>(float* d, const uint32_t* a, uint64_t db) {
    asm volatile("wgmma.mma_async.sync.aligned.m64n96k16.f32.bf16.bf16 {%0,%1,%2,%3,%4,%5,%6,%7,%8,%9,%10,%11,%12,%13,%14,%15,%16,%17,%18,%19,%20,%21,%22,%23,%24,%25,%26,%27,%28,%29,%30,%31,%32,%33,%34,%35,%36,%37,%38,%39,%40,%41,%42,%43,%44,%45,%46,%47}, "
                 "{%48,%49,%50,%51}, %52, 1, 1, 1, 0;"
                 : ACC8(d, 0), ACC8(d, 8), ACC8(d, 16), ACC8(d, 24), ACC8(d, 32), ACC8(d, 40) : "r"(a[0]), "r"(a[1]), "r"(a[2]), "r"(a[3]), "l"(db));
}
template <> DEVI void wgmma_conv<64>(float* d, const uint32_t* a, uint64_t db) {
    asm volatile("wgmma.mma_async.sync.aligned.m64n64k16.f32.bf16.bf16 {%0,%1,%2,%3,%4,%5,%6,%7,%8,%9,%10,%11,%12,%13,%14,%15,%16,%17,%18,%19,%20,%21,%22,%23,%24,%25,%26,%27,%28,%29,%30,%31}, "
                 "{%32,%33,%34,%35}, %36, 1, 1, 1, 0;"
                 : ACC8(d, 0), ACC8(d, 8), ACC8(d, 16), ACC8(d, 24) : "r"(a[0]), "r"(a[1]), "r"(a[2]), "r"(a[3]), "l"(db));
}
template <> DEVI void wgmma_conv<32>(float* d, const uint32_t* a, uint64_t db) {
    asm volatile("wgmma.mma_async.sync.aligned.m64n32k16.f32.bf16.bf16 {%0,%1,%2,%3,%4,%5,%6,%7,%8,%9,%10,%11,%12,%13,%14,%15}, "
                 "{%16,%17,%18,%19}, %20, 1, 1, 1, 0;"
                 : ACC8(d, 0), ACC8(d, 8) : "r"(a[0]), "r"(a[1]), "r"(a[2]), "r"(a[3]), "l"(db));
}
DEVI uint32_t lds32(uint32_t a) { uint32_t v; asm volatile("ld.shared.b32 %0, [%1];" : "=r"(v) : "r"(a)); return v; }
DEVI uint32_t lds16(uint32_t a) { uint16_t v; asm volatile("ld.shared.b16 %0, [%1];" : "=h"(v) : "r"(a)); return v; }

DEVI void sts32(uint32_t a, float v) { asm volatile("st.shared.f32 [%0], %1;" ::"r"(a), "f"(v) : "memory"); }
template <int J> DEVI void conv_group(float* acc, uint32_t* f, uint32_t wa, uint64_t du) {
#pragma unroll
    for (int i = 0; i < 8; i++) {
        const uint32_t w = wa + (8 * J + i) * 256;
        f[4 * i] = lds32(w); f[4 * i + 1] = lds32(w + 32); f[4 * i + 2] = lds32(w - 32); f[4 * i + 3] = f[4 * i];
    }
    wg_fence();
#pragma unroll
    for (int i = 0; i < 8; i++) wgmma_conv<128 - 32 * J>(acc, f + 4 * i, du + (uint64_t)(4 * (8 * J + i)));
    wg_commit();
}
DEVI uint32_t ypos(int a, int b) { return (uint32_t)(b * 128 + (a ^ ((b & 3) << 3))) * 4; }

DEVI void expand_table(int ct, uint32_t sW, uint32_t sK) {
#pragma unroll 1
    for (int i = ct; i < WTAB; i += 384) {
        const int c = (i >> 3) & 3, qd = (i & 7) | ((i >> 5) << 3);
        float k[5];
#pragma unroll
        for (int e = 0; e < 5; e++) {
            const int l = qd * 4 - 65 + e;
            const int hi = (int)__bfloat16_as_ushort(__float2bfloat16_rn((float)l)) - 17024;
            k[e] = __uint_as_float(lds32(sK + (c * 648 + (l < 0 ? 644 : (l < 128 ? l : hi))) * 4));
        }
        asm volatile("st.shared.v4.b32 [%0], {%1,%2,%3,%4};" ::"r"(sW + (c * WTAB + qd * 4) * 4), "r"(pack_bf16(k[1], k[0])),
                     "r"(pack_bf16(k[2], k[1])), "r"(pack_bf16(k[3], k[2])), "r"(pack_bf16(k[4], k[3])) : "memory");
    }
}

__global__ void __cluster_dims__(2, 1, 1) __launch_bounds__(512, 1)
outproj_kernel(const __grid_constant__ CUtensorMap tm_ctx, const __grid_constant__ CUtensorMap tm_wo,
               const __grid_constant__ CUtensorMap tm_out, const __grid_constant__ CUtensorMap tm_u, SsmParams sp, bf16* __restrict__ out) {
    extern __shared__ uint8_t smem_raw[];
    const uint32_t sb = (smem_u32(smem_raw) + 1023) & ~1023u;
    const uint32_t sX = sb + OP_NS * 32768, sW = sX + 32768, sU = sW + 4 * WTAB * 4, sK = sU + 4 * OP_UCH, bars = sK + 4 * 648 * 4;
    const uint32_t full = bars, empty = bars + 64, xfull = bars + 128, wfull = bars + 136, xfree = bars + 144;
    const int tid = threadIdx.x, warp = tid >> 5, lane = tid & 31, wg = tid >> 7;
    const uint32_t rank = cluster_rank();
    const uint32_t kr = rank;
    const int cl = blockIdx.x >> 1;
    const int m0 = (cl >> 2) * 128, n0 = (cl & 3) * 128, k0 = kr * 2048;
    STAMP(blockIdx.x == 10 && tid == 0, 1000);
    if (tid == 0) {
        for (int i = 0; i < OP_NS; i++) { mbar_init(full + 8 * i, 1); mbar_init(empty + 8 * i, 8); }
        mbar_init(xfull, 1);
        mbar_init(wfull, 1);
        mbar_init(xfree, 1);
        fence_barrier_init();
        mbar_expect_tx(wfull, 32768);
        for (int i = 0; i < 8; i++) tma_load_2d(sX + i * 4096, &tm_u, cl * 8, i * 256, wfull);
    }
    for (int i = tid; i < 648; i += 512) asm volatile("st.shared.v4.b32 [%0], {%1,%1,%1,%1};" ::"r"(sK + i * 16), "r"(0) : "memory");
    __syncthreads();
    cluster_arrive();
    if (wg == 3) {
        reg_dec<40>();
        cluster_wait();
        if (tid == 384) {
            mbar_expect_tx(xfull, 32768);
            for (int it = 0; it < OP_NS; it++) {
                const uint32_t dst = sb + it * 32768, fb = full + 8 * it;
                mbar_expect_tx(fb, 32768);
                tma_load_2d(dst + 16384, &tm_wo, n0, k0 + it * 64, fb);
                tma_load_2d(dst + 24576, &tm_wo, n0 + 64, k0 + it * 64, fb);
            }
            pdl_wait();
            STAMP(blockIdx.x == 10, 1005);
            for (int it = 0; it < 32; it++) {
                const int st = it & (OP_NS - 1);
                const uint32_t dst = sb + st * 32768, fb = full + 8 * st;
                if (it >= OP_NS) {
                    mbar_wait(empty + 8 * st, ((it / OP_NS) & 1) ^ 1);
                    mbar_expect_tx(fb, 32768);
                    tma_load_2d(dst + 16384, &tm_wo, n0, k0 + it * 64, fb);
                    tma_load_2d(dst + 24576, &tm_wo, n0 + 64, k0 + it * 64, fb);
                }
                tma_load_2d(dst, &tm_ctx, k0 + it * 64, m0, fb);
                tma_load_2d(dst + 8192, &tm_ctx, k0 + it * 64, m0 + 64, fb);
            }
        }
        __syncwarp();
    } else {
      const int ct = tid & 127, wq = warp & 3;
      if (wg == 2) {
        for (int i = ct; i < 8 * 32; i += 128) {
            const uint32_t a = sU + (i >> 5) * OP_ULD + (128 + (i & 31)) * 16;
            asm volatile("st.shared.v4.b32 [%0], {%1,%1,%1,%1};" ::"r"(a), "r"(0) : "memory");
        }
        const bool mine = ((lane >> 2) & 1) == (int)rank;
        const uint32_t ub = sU + (lane & 3) * OP_UCH + ((lane >> 3) & 1) * OP_ULD + (127 - 2 * wq - (lane >> 4)) * 16;
        mbar_wait(wfull, 0);
#pragma unroll 4
        for (int i = 0; i < 16; i++) {
            uint32_t r0, r1, r2, r3;
            asm volatile("ldmatrix.sync.aligned.m8n8.x4.trans.shared.b16 {%0,%1,%2,%3}, [%4];"
                         : "=r"(r0), "=r"(r1), "=r"(r2), "=r"(r3) : "r"(sX + (i * 128 + ct) * 16) : "memory");
            asm volatile("stmatrix.sync.aligned.m8n8.x4.shared.b16 [%0], {%1,%2,%3,%4};"
                         ::"r"(mine ? ub - i * 128 : sW + lane * 16), "r"(r0), "r"(r1), "r"(r2), "r"(r3) : "memory");
        }
        fence_proxy_async();
        STAMP(blockIdx.x == 10 && ct == 0, 1001);
      } else {
        ssm_kgen_warp(sp, blockIdx.x * 4 + wq, wg, lane, sK + wq * 648 * 4);
      }
      cluster_wait();
      named_sync(3, 384);
      if (tid == 256) mbar_arrive_cluster(xfree, rank ^ 1);
      STAMP(blockIdx.x == 10 && tid == 257, 1002);
      expand_table(tid, sW, sK);
      if (wg == 2) {
        reg_inc<208>();
        const int g = lane >> 2, t = lane & 3;
        const int d0 = blockIdx.x * 4;
        const uint2 dsk = __ldg(reinterpret_cast<const uint2*>(sp.dskip + d0));
        named_sync(4, 384);
        uint32_t res[16][2];
        STAMP(blockIdx.x == 10 && ct == 0, 1003);
#pragma unroll 1
        for (int c = 0; c < 4; c++) {
            float acc[64];
            uint32_t fa[32], fb[32];
#pragma unroll
            for (int i = 0; i < 64; i++) acc[i] = 0.f;
            const uint32_t wa = sW + (c * WTAB + 64 + 16 * wq + g - 2 * t) * 4;
            const uint64_t du = make_desc(sU + c * OP_UCH, OP_ULD, 128, 0);
            conv_group<0>(acc, fa, wa, du);
            conv_group<1>(acc, fb, wa, du);
            wg_wait<1>();
            conv_group<2>(acc, fa, wa, du);
            wg_wait<1>();
            conv_group<3>(acc, fb, wa, du);
            named_sync(5, 128);
            wg_wait<0>();
            const uint32_t yb = (wq & 1) ? sW + c * WTAB * 4 : sK;
            const bool skip0 = wq >= 2 && t == 0;
            if (wq >= 2) {
                named_sync(6, 128);
#pragma unroll
                for (int hf = 0; hf < 2; hf++) {
                    float2 v[16];
#pragma unroll
                    for (int i = 0; i < 16; i++)
                        asm volatile("ld.shared.v2.f32 {%0,%1}, [%2];" : "=f"(v[i].x), "=f"(v[i].y)
                                     : "r"(yb + ypos((128 - 8 * (8 * hf + (i >> 1)) - 2 * t) & 127, g + 8 * (i & 1))));
#pragma unroll
                    for (int i = 0; i < 16; i++) { acc[32 * hf + 2 * i] += v[i].y; acc[32 * hf + 2 * i + 1] += v[i].x; }
                }
            }
#pragma unroll
            for (int i = 0; i < 32; i++) {
                const uint32_t p = yb + ypos(126 - 8 * (i >> 1) - 2 * t + (wq & 2), g + 8 * (i & 1));
                if (i >= 2 || !skip0) asm volatile("st.shared.v2.f32 [%0], {%1,%2};" ::"r"(p), "f"(acc[2 * i + 1]), "f"(acc[2 * i]) : "memory");
            }
            if (wq < 2) named_arrive(6, 128);
            named_sync(5, 128);
            const uint32_t dw = (c & 2) ? dsk.y : dsk.x;
            const float D = (c & 1) ? bhi(dw) : blo(dw);
            const int yb2 = (lane >> 3) + 4 * wq;
#pragma unroll
            for (int i = 0; i < 16; i++) {
                const int a = 8 * i + (lane & 7);
                float y = __uint_as_float(lds32(sW + c * WTAB * 4 + ypos((a - 1) & 127, yb2)));
                y = __uint_as_float(lds32(sK + ypos(a, yb2))) + (a == 0 ? 0.f : y);
                const float u = __uint_as_float(lds16(sU + c * OP_UCH + (wq >> 1) * OP_ULD + (127 - a) * 16 + (yb2 & 7) * 2) << 16);
                const uint32_t o = __bfloat16_as_ushort(__float2bfloat16_rn(rbf(y) + rbf(u * D)));
                res[i][0] = __byte_perm(res[i][0], res[i][1], 0x5432); res[i][1] = __byte_perm(res[i][1], o, 0x5432);
            }
        }
        STAMP(blockIdx.x == 10 && ct == 0, 1004);
        const int grp = blockIdx.x >> 2, me = blockIdx.x & 3;
#pragma unroll
        for (int i = 0; i < 8; i++)
            __stcg(g_y + (((grp * 4 + (i >> 1)) * 4 + me) * 2 + (i & 1)) * 128 + ct,
                   make_uint4(res[2 * i][0], res[2 * i][1], res[2 * i + 1][0], res[2 * i + 1][1]));
        named_sync(5, 128);
        if (ct == 0) {
            __threadfence();
            const unsigned int target = (atomicAdd(g_ycnt + grp, 1u) & ~3u) + 4u;
            uint32_t t0, t1, v;
            asm volatile("mov.u32 %0, %%globaltimer_lo;" : "=r"(t0));
            do {
                asm volatile("ld.acquire.gpu.global.u32 %0, [%1];" : "=r"(v) : "l"(g_ycnt + grp) : "memory");
                asm volatile("mov.u32 %0, %%globaltimer_lo;" : "=r"(t1));
            } while ((int)(v - target) < 0 && t1 - t0 < 4000000u);
        }
        named_sync(5, 128);
        uint4 y[8];
#pragma unroll
        for (int i = 0; i < 8; i++)
            y[i] = __ldcg(g_y + ((blockIdx.x * 4 + 2 * (t & 1) + ((i >> 1) & 1)) * 2 + (i & 1)) * 128 + (ct & ~1) + (i >> 2));
#pragma unroll
        for (int i = 0; i < 8; i++) {
            const int row = 128 * (4 * me + (i & 3)) + 16 * ((lane & 6) + (i >> 2)) + 4 * wq + (lane >> 3);
            const uint4 p = y[(i & 4) + ((i >> 1) & 1)], q = y[(i & 4) + 2 + ((i >> 1) & 1)];
            *reinterpret_cast<uint4*>(out + (size_t)row * 1024 + 512 + grp * 16 + (t & 1) * 8) =
                (i & 1) ? make_uint4(p.z, p.w, q.z, q.w) : make_uint4(p.x, p.y, q.x, q.y);
        }
      } else {
        named_arrive(4, 384);
        float acc[64];
#pragma unroll 1
        for (int it = 0; it < 32; it++) {
            const int st = it & (OP_NS - 1);
            mbar_wait(full + 8 * st, (it / OP_NS) & 1);
            STAMP(blockIdx.x == 10 && tid == 0, 1009 + it);
            wg_fence();
            const uint32_t base = sb + st * 32768;
            const uint64_t da = desc_kmajor(base + wg * 8192), db = desc_mnmajor(base + 16384, 8192);
#pragma unroll
            for (int k = 0; k < 4; k++) wgmma_ss128<1>(acc, da + k * 2, db + k * 128, (it | k) != 0);
            wg_commit();
            if (it > 0 && it + OP_NS - 1 < 32) {
                wg_wait<1>();
                if (lane == 0) mbar_arrive(empty + 8 * ((it - 1) & (OP_NS - 1)));
            }
        }
        wg_wait<0>();
        mbar_wait(xfree, 0);
        uint32_t peer, pbar;
        asm volatile("mapa.shared::cluster.u32 %0, %1, %2;" : "=r"(peer) : "r"(sX + tid * 16), "r"(rank ^ 1));
        asm volatile("mapa.shared::cluster.u32 %0, %1, %2;" : "=r"(pbar) : "r"(xfull), "r"(rank ^ 1));
#pragma unroll
        for (int i = 0; i < 8; i++) {
            const float* s = acc + 4 * i;
            const float a = kr ? s[0] : s[32], b = kr ? s[1] : s[33], c = kr ? s[2] : s[34], d = kr ? s[3] : s[35];
            asm volatile("st.async.weak.shared::cluster.mbarrier::complete_tx::bytes.v4.f32 [%0], {%1,%2,%3,%4}, [%5];"
                         ::"r"(peer + i * 4096), "f"(a), "f"(b), "f"(c), "f"(d), "r"(pbar) : "memory");
        }
        STAMP(blockIdx.x == 10 && tid == 0, 1006);
        mbar_wait(xfull, 0);
        STAMP(blockIdx.x == 10 && tid == 0, 1007);
        float r[32];
#pragma unroll
        for (int i = 0; i < 8; i++) {
            float a, b, c, d;
            asm volatile("ld.shared.v4.f32 {%0,%1,%2,%3}, [%4];" : "=f"(a), "=f"(b), "=f"(c), "=f"(d) : "r"(sX + tid * 16 + i * 4096));
            const float* s = acc + 4 * i;
            r[4 * i] = a + (kr ? s[32] : s[0]); r[4 * i + 1] = b + (kr ? s[33] : s[1]);
            r[4 * i + 2] = c + (kr ? s[34] : s[2]); r[4 * i + 3] = d + (kr ? s[35] : s[3]);
        }
        const uint32_t stg = sb + wg * 8192;
        store_slab64(stg, (warp & 3) * 16, r, 1.f, 1.f, lane);
        fence_proxy_async();
        named_sync(1 + wg, 128);
        if ((tid & 127) == 0) {
            tma_store_2d(&tm_out, stg, n0 + kr * 64, m0 + wg * 64);
            bulk_commit();
            bulk_wait<0>();
            STAMP(blockIdx.x == 10 && tid == 0, 1008);
        }
      }
    }
}

typedef CUresult (*EncodeFn)(CUtensorMap*, CUtensorMapDataType, cuuint32_t, void*, const cuuint64_t*, const cuuint64_t*,
                             const cuuint32_t*, const cuuint32_t*, CUtensorMapInterleave, CUtensorMapSwizzle,
                             CUtensorMapL2promotion, CUtensorMapFloatOOBfill);

static void make_map(EncodeFn fn, CUtensorMap* m, const void* p, uint64_t cols, uint64_t rows, uint32_t box_rows) {
    cuuint64_t dims[2] = {cols, rows};
    cuuint64_t strides[1] = {cols * 2};
    cuuint32_t box[2] = {64, box_rows};
    cuuint32_t es[2] = {1, 1};
    fn(m, CU_TENSOR_MAP_DATA_TYPE_BFLOAT16, 2, const_cast<void*>(p), dims, strides, box, es, CU_TENSOR_MAP_INTERLEAVE_NONE,
       CU_TENSOR_MAP_SWIZZLE_128B, CU_TENSOR_MAP_L2_PROMOTION_L2_256B, CU_TENSOR_MAP_FLOAT_OOB_FILL_NONE);
}

extern "C" void kernel_launch(void* const* d_in, const int* in_sizes, int n_in, void* d_out, int out_size) {
    void* fp = nullptr;
    cudaDriverEntryPointQueryResult qr;
    cudaGetDriverEntryPoint("cuTensorMapEncodeTiled", &fp, cudaEnableDefault, &qr);
    EncodeFn fn = (EncodeFn)fp;
    void *p_kv, *p_ctx;
    cudaGetSymbolAddress(&p_kv, g_kv);
    cudaGetSymbolAddress(&p_ctx, g_ctx);
    CUtensorMap tm_kv_st, tm_x, tm_c, tm_wq, tm_wk, tm_wv, tm_wo, tm_kv, tm_ctx, tm_out;
    make_map(fn, &tm_x, d_in[0], DM, SEQ, 128);
    make_map(fn, &tm_c, d_in[1], DM, SEQ, 128);
    make_map(fn, &tm_wq, d_in[2], HDALL, DM, 64);
    make_map(fn, &tm_wk, d_in[3], HDALL, DM, 64);
    make_map(fn, &tm_wv, d_in[4], HDALL, DM, 64);
    make_map(fn, &tm_wo, d_in[5], DM, HDALL, 64);
    make_map(fn, &tm_kv, p_kv, 2 * HDALL, SEQ, 128);
    make_map(fn, &tm_kv_st, p_kv, 2 * HDALL, SEQ, 64);
    make_map(fn, &tm_ctx, p_ctx, HDALL, SEQ, 64);
    make_map(fn, &tm_out, d_out, 1024, SEQ, 64);
    CUtensorMap tm_u;
    {
        cuuint64_t dims[2] = {512, 2048}, strides[1] = {1024};
        cuuint32_t box[2] = {8, 256}, es[2] = {1, 1};
        fn(&tm_u, CU_TENSOR_MAP_DATA_TYPE_BFLOAT16, 2, d_in[6], dims, strides, box, es, CU_TENSOR_MAP_INTERLEAVE_NONE,
           CU_TENSOR_MAP_SWIZZLE_NONE, CU_TENSOR_MAP_L2_PROMOTION_NONE, CU_TENSOR_MAP_FLOAT_OOB_FILL_NONE);
    }
    SsmParams sp;
    sp.u = (const bf16*)d_in[6]; sp.lar = (const bf16*)d_in[7]; sp.aim = (const bf16*)d_in[8];
    sp.cre = (const bf16*)d_in[9]; sp.cim = (const bf16*)d_in[10]; sp.ldt = (const bf16*)d_in[11]; sp.dskip = (const bf16*)d_in[12];
    cudaFuncSetAttribute(gemm_kv_kernel, cudaFuncAttributeMaxDynamicSharedMemorySize, G1_SMEM);
    cudaFuncSetAttribute(attn_kernel, cudaFuncAttributeMaxDynamicSharedMemorySize, AT_SMEM);
    cudaFuncSetAttribute(outproj_kernel, cudaFuncAttributeMaxDynamicSharedMemorySize, OP_SMEM);
    cudaStream_t st = cudaStreamPerThread;
    gemm_kv_kernel<<<128, G1_THREADS, G1_SMEM, st>>>(tm_c, tm_wk, tm_wv, tm_kv_st, (const bf16*)d_in[0], (const bf16*)d_in[2]);
    cudaLaunchAttribute at[1];
    at[0].id = cudaLaunchAttributeProgrammaticStreamSerialization;
    at[0].val.programmaticStreamSerializationAllowed = 1;
    cudaLaunchConfig_t cfg = {};
    cfg.stream = st; cfg.attrs = at; cfg.numAttrs = 1;
    cfg.gridDim = dim3(132); cfg.blockDim = dim3(384); cfg.dynamicSmemBytes = AT_SMEM;
    cudaLaunchKernelEx(&cfg, attn_kernel, tm_x, tm_wq, tm_kv, tm_ctx, sp.u, (const bf16*)d_in[5]);
    cfg.gridDim = dim3(128); cfg.blockDim = dim3(512); cfg.dynamicSmemBytes = OP_SMEM;
    cudaLaunchKernelEx(&cfg, outproj_kernel, tm_ctx, tm_wo, tm_out, tm_u, sp, (bf16*)d_out);
}
```

```cpp
#include <cuda_runtime.h>
#include <cuda_bf16.h>
#include <cuda.h>
#include <stdint.h>

typedef __nv_bfloat16 bf16;

#define DEVI __device__ __forceinline__

constexpr int SEQ = 2048, DM = 512, NH = 32, HD = 128, HDALL = NH * HD;
constexpr int SSM_D = 512, SSM_N = 128;
constexpr int WTAB = 2112;

__device__ bf16 g_kv[(size_t)SEQ * 2 * HDALL];
__device__ bf16 g_ctx[(size_t)SEQ * HDALL];
__device__ uint4 g_y[32 * 4 * 4 * 2 * 128];
__device__ unsigned int g_ycnt[32];
__device__ unsigned int g_sched;

#define STAMP(cond, i)
DEVI uint32_t smem_u32(const void* p) { return (uint32_t)__cvta_generic_to_shared(p); }
DEVI void mbar_init(uint32_t a, uint32_t cnt) { asm volatile("mbarrier.init.shared::cta.b64 [%0], %1;" ::"r"(a), "r"(cnt)); }
DEVI void mbar_expect_tx(uint32_t a, uint32_t bytes) {
    asm volatile("mbarrier.arrive.expect_tx.shared::cta.b64 _, [%0], %1;" ::"r"(a), "r"(bytes) : "memory");
}
DEVI void mbar_arrive(uint32_t a) { asm volatile("mbarrier.arrive.shared::cta.b64 _, [%0];" ::"r"(a) : "memory"); }
DEVI void mbar_arrive_cluster(uint32_t a, uint32_t cta) {
    asm volatile("{\n.reg .b32 r;\nmapa.shared::cluster.u32 r, %0, %1;\n"
                 "mbarrier.arrive.shared::cluster.b64 _, [r];\n}" ::"r"(a), "r"(cta) : "memory");
}
#define MBAR_WAIT_ASM(OP)                                                                              \
    asm volatile("{\n.reg .pred p, q;\n.reg .u32 t0, t1;\n" OP " p, [%0], %1;\n@p bra D_%=;\n"         \
                 "mov.u32 t0, %%globaltimer_lo;\nW_%=:\n" OP " p, [%0], %1;\n"                         \
                 "mov.u32 t1, %%globaltimer_lo;\nsub.u32 t1, t1, t0;\n"                                \
                 "setp.gt.or.u32 q, t1, 4000000, p;\n@!q bra W_%=;\nD_%=:\n}" ::"r"(a), "r"(parity) : "memory")
DEVI void mbar_wait(uint32_t a, uint32_t parity) { MBAR_WAIT_ASM("mbarrier.try_wait.parity.shared::cta.b64"); }
DEVI void mbar_wait_cluster(uint32_t a, uint32_t parity) { MBAR_WAIT_ASM("mbarrier.try_wait.parity.acquire.cluster.shared::cta.b64"); }
DEVI void fence_barrier_init() { asm volatile("fence.mbarrier_init.release.cluster;" ::: "memory"); }
DEVI void fence_proxy_async() { asm volatile("fence.proxy.async.shared::cta;" ::: "memory"); }
DEVI void cluster_sync_all() {
    asm volatile("barrier.cluster.arrive.relaxed.aligned;\nbarrier.cluster.wait.aligned;" ::: "memory");
}
DEVI void cluster_arrive() { asm volatile("barrier.cluster.arrive.relaxed.aligned;" ::: "memory"); }
DEVI void cluster_wait() { asm volatile("barrier.cluster.wait.aligned;" ::: "memory"); }
DEVI uint32_t cluster_rank() { uint32_t r; asm volatile("mov.u32 %0, %%cluster_ctarank;" : "=r"(r)); return r; }
DEVI void tma_load_2d(uint32_t dst, const CUtensorMap* m, int c0, int c1, uint32_t bar) {
    asm volatile("cp.async.bulk.tensor.2d.shared::cluster.global.mbarrier::complete_tx::bytes [%0], [%1, {%3, %4}], [%2];"
                 ::"r"(dst), "l"(m), "r"(bar), "r"(c0), "r"(c1) : "memory");
}
DEVI void tma_load_2d_mc(uint32_t dst, const CUtensorMap* m, int c0, int c1, uint32_t bar, uint16_t mask) {
    asm volatile("cp.async.bulk.tensor.2d.shared::cluster.global.mbarrier::complete_tx::bytes.multicast::cluster [%0], [%1, {%3, %4}], [%2], %5;"
                 ::"r"(dst), "l"(m), "r"(bar), "r"(c0), "r"(c1), "h"(mask) : "memory");
}
DEVI void tma_prefetch_2d(const CUtensorMap* m, int c0, int c1) {
    asm volatile("cp.async.bulk.prefetch.tensor.2d.L2.global [%0, {%1, %2}];" ::"l"(m), "r"(c0), "r"(c1) : "memory");
}
DEVI void tma_store_2d(const CUtensorMap* m, uint32_t src, int c0, int c1) {
    asm volatile("cp.async.bulk.tensor.2d.global.shared::cta.bulk_group [%0, {%2, %3}], [%1];"
                 ::"l"(m), "r"(src), "r"(c0), "r"(c1) : "memory");
}
DEVI void bulk_load(uint32_t dst, const void* src, uint32_t bytes, uint32_t bar) {
    asm volatile("cp.async.bulk.shared::cluster.global.mbarrier::complete_tx::bytes [%0], [%1], %2, [%3];"
                 ::"r"(dst), "l"(src), "r"(bytes), "r"(bar) : "memory");
}
DEVI void bulk_prefetch(const void* src, uint32_t bytes) {
    asm volatile("cp.async.bulk.prefetch.L2.global [%0], %1;" ::"l"(src), "r"(bytes) : "memory");
}
DEVI void bulk_commit() { asm volatile("cp.async.bulk.commit_group;" ::: "memory"); }
template <int N> DEVI void bulk_wait_read() { asm volatile("cp.async.bulk.wait_group.read %0;" ::"n"(N) : "memory"); }
template <int N> DEVI void bulk_wait() { asm volatile("cp.async.bulk.wait_group %0;" ::"n"(N) : "memory"); }
DEVI void prefetch_tmap(const CUtensorMap* m) { asm volatile("prefetch.tensormap [%0];" ::"l"(m) : "memory"); }
DEVI void named_sync(int id, int n) { asm volatile("bar.sync %0, %1;" ::"r"(id), "r"(n) : "memory"); }
DEVI void named_arrive(int id, int n) { asm volatile("bar.arrive %0, %1;" ::"r"(id), "r"(n) : "memory"); }
DEVI void pdl_wait() { asm volatile("griddepcontrol.wait;" ::: "memory"); }
DEVI void pdl_launch() { asm volatile("griddepcontrol.launch_dependents;" ::: "memory"); }
template <int R> DEVI void reg_inc() { asm volatile("setmaxnreg.inc.sync.aligned.u32 %0;" ::"n"(R)); }
template <int R> DEVI void reg_dec() { asm volatile("setmaxnreg.dec.sync.aligned.u32 %0;" ::"n"(R)); }

DEVI void wg_fence() { asm volatile("wgmma.fence.sync.aligned;" ::: "memory"); }
DEVI void wg_commit() { asm volatile("wgmma.commit_group.sync.aligned;" ::: "memory"); }
template <int N> DEVI void wg_wait() { asm volatile("wgmma.wait_group.sync.aligned %0;" ::"n"(N) : "memory"); }

DEVI uint64_t make_desc(uint32_t addr, uint32_t lbo, uint32_t sbo, uint32_t swz) {
    return (uint64_t)((addr & 0x3FFFF) >> 4) | ((uint64_t)(lbo >> 4) << 16) | ((uint64_t)(sbo >> 4) << 32) | ((uint64_t)swz << 62);
}
DEVI uint64_t desc_kmajor(uint32_t addr) { return make_desc(addr, 16, 1024, 1); }
DEVI uint64_t desc_mnmajor(uint32_t addr, uint32_t lbo) { return make_desc(addr, lbo, 1024, 1); }

#define ACC8(d, o) "+f"(d[o + 0]), "+f"(d[o + 1]), "+f"(d[o + 2]), "+f"(d[o + 3]), "+f"(d[o + 4]), "+f"(d[o + 5]), "+f"(d[o + 6]), "+f"(d[o + 7])
#define ACC64(d) ACC8(d, 0), ACC8(d, 8), ACC8(d, 16), ACC8(d, 24), ACC8(d, 32), ACC8(d, 40), ACC8(d, 48), ACC8(d, 56)
#define R64 "{%0,%1,%2,%3,%4,%5,%6,%7,%8,%9,%10,%11,%12,%13,%14,%15,%16,%17,%18,%19,%20,%21,%22,%23,%24,%25,%26,%27,%28,%29,%30,%31," \
            "%32,%33,%34,%35,%36,%37,%38,%39,%40,%41,%42,%43,%44,%45,%46,%47,%48,%49,%50,%51,%52,%53,%54,%55,%56,%57,%58,%59,%60,%61,%62,%63}"

template <int TB> DEVI void wgmma_ss128(float* d, uint64_t da, uint64_t db, int acc) {
    asm volatile("{\n.reg .pred p;\nsetp.ne.b32 p, %66, 0;\n"
                 "wgmma.mma_async.sync.aligned.m64n128k16.f32.bf16.bf16 " R64 ", %64, %65, p, 1, 1, 0, %67;\n}"
                 : ACC64(d) : "l"(da), "l"(db), "r"(acc), "n"(TB));
}
template <int TB> DEVI void wgmma_rs128(float* d, const uint32_t* a, uint64_t db, int acc) {
    asm volatile("{\n.reg .pred p;\nsetp.ne.b32 p, %69, 0;\n"
                 "wgmma.mma_async.sync.aligned.m64n128k16.f32.bf16.bf16 " R64 ", {%64,%65,%66,%67}, %68, p, 1, 1, %70;\n}"
                 : ACC64(d) : "r"(a[0]), "r"(a[1]), "r"(a[2]), "r"(a[3]), "l"(db), "r"(acc), "n"(TB));
}
DEVI uint32_t pack_bf16(float lo, float hi) {
    uint32_t r;
    asm("cvt.rn.bf16x2.f32 %0, %1, %2;" : "=r"(r) : "f"(hi), "f"(lo));
    return r;
}
DEVI void stmatrix_x4(uint32_t addr, uint32_t r0, uint32_t r1, uint32_t r2, uint32_t r3) {
    asm volatile("stmatrix.sync.aligned.m8n8.x4.shared.b16 [%0], {%1,%2,%3,%4};" ::"r"(addr), "r"(r0), "r"(r1), "r"(r2), "r"(r3) : "memory");
}
DEVI float ex2(float x) { float y; asm("ex2.approx.ftz.f32 %0, %1;" : "=f"(y) : "f"(x)); return y; }

DEVI void store_slab64(uint32_t base, int row0, const float* d, float s0, float s1, int lane) {
    int mi = lane >> 3, r = lane & 7;
    int row = row0 + (mi & 1) * 8 + r;
#pragma unroll
    for (int j = 0; j < 8; j += 2) {
        uint32_t r0 = pack_bf16(d[4 * j + 0] * s0, d[4 * j + 1] * s0);
        uint32_t r1 = pack_bf16(d[4 * j + 2] * s1, d[4 * j + 3] * s1);
        uint32_t r2 = pack_bf16(d[4 * j + 4] * s0, d[4 * j + 5] * s0);
        uint32_t r3 = pack_bf16(d[4 * j + 6] * s1, d[4 * j + 7] * s1);
        int chunk = j + (mi >> 1);
        stmatrix_x4(base + row * 128 + ((chunk ^ (row & 7)) << 4), r0, r1, r2, r3);
    }
}
struct cf { float x, y; };
DEVI cf cmul(cf a, cf b) { cf r; r.x = fmaf(a.x, b.x, -a.y * b.y); r.y = fmaf(a.x, b.y, a.y * b.x); return r; }
DEVI cf csq(cf a) { cf r; r.x = fmaf(a.x, a.x, -a.y * a.y); r.y = (a.x + a.x) * a.y; return r; }
DEVI cf cexp_(float re, float im) {
    float m = __expf(re), s, c;
    __sincosf(im, &s, &c);
    cf r; r.x = m * c; r.y = m * s; return r;
}
DEVI uint32_t h2(cf v) { uint32_t r; asm("cvt.rn.f16x2.f32 %0, %1, %2;" : "=r"(r) : "f"(v.y), "f"(v.x)); return r; }
DEVI uint32_t h2c(cf v) { uint32_t r; asm("cvt.rn.f16x2.f32 %0, %1, %2;" : "=r"(r) : "f"(-v.y), "f"(v.x)); return r; }
DEVI void mma_group(float (*c)[4], const uint32_t (*a)[4], const uint32_t (*b)[2]) {
    asm volatile(
        "mma.sync.aligned.m16n8k16.row.col.f32.f16.f16.f32 {%0,%1,%2,%3}, {%20,%21,%22,%23}, {%40,%41}, {%0,%1,%2,%3};\n"
        "mma.sync.aligned.m16n8k16.row.col.f32.f16.f16.f32 {%4,%5,%6,%7}, {%24,%25,%26,%27}, {%40,%41}, {%4,%5,%6,%7};\n"
        "mma.sync.aligned.m16n8k16.row.col.f32.f16.f16.f32 {%8,%9,%10,%11}, {%28,%29,%30,%31}, {%42,%43}, {%8,%9,%10,%11};\n"
        "mma.sync.aligned.m16n8k16.row.col.f32.f16.f16.f32 {%12,%13,%14,%15}, {%32,%33,%34,%35}, {%44,%45}, {%12,%13,%14,%15};\n"
        "mma.sync.aligned.m16n8k16.row.col.f32.f16.f16.f32 {%16,%17,%18,%19}, {%36,%37,%38,%39}, {%46,%47}, {%16,%17,%18,%19};\n"
        : "+f"(c[0][0]), "+f"(c[0][1]), "+f"(c[0][2]), "+f"(c[0][3]), "+f"(c[1][0]), "+f"(c[1][1]), "+f"(c[1][2]), "+f"(c[1][3]),
          "+f"(c[2][0]), "+f"(c[2][1]), "+f"(c[2][2]), "+f"(c[2][3]), "+f"(c[3][0]), "+f"(c[3][1]), "+f"(c[3][2]), "+f"(c[3][3]),
          "+f"(c[4][0]), "+f"(c[4][1]), "+f"(c[4][2]), "+f"(c[4][3])
        : "r"(a[0][0]), "r"(a[0][1]), "r"(a[0][2]), "r"(a[0][3]), "r"(a[1][0]), "r"(a[1][1]), "r"(a[1][2]), "r"(a[1][3]),
          "r"(a[2][0]), "r"(a[2][1]), "r"(a[2][2]), "r"(a[2][3]), "r"(a[3][0]), "r"(a[3][1]), "r"(a[3][2]), "r"(a[3][3]),
          "r"(a[4][0]), "r"(a[4][1]), "r"(a[4][2]), "r"(a[4][3]),
          "r"(b[0][0]), "r"(b[0][1]), "r"(b[1][0]), "r"(b[1][1]), "r"(b[2][0]), "r"(b[2][1]), "r"(b[3][0]), "r"(b[3][1]));
}
DEVI float bf2f(bf16 v) { return __bfloat162float(v); }
DEVI float rbf(float v) { return __bfloat162float(__float2bfloat16_rn(v)); }

struct SsmParams { const bf16 *lar, *aim, *cre, *cim, *ldt, *dskip, *u; };

DEVI int kp_index(int l) {
    int p = (int)rbf((float)l);
    return p < 256 ? p : (p < 512 ? 128 + (p >> 1) : (p < 1024 ? 256 + (p >> 2) : 384 + (p >> 3)));
}

DEVI void reds(uint32_t a, float v) { asm volatile("red.shared.add.f32 [%0], %1;" ::"r"(a), "f"(v) : "memory"); }
DEVI uint32_t ldg16(const bf16* p) { uint16_t v; asm volatile("ld.global.nc.u16 %0, [%1];" : "=h"(v) : "l"(p)); return v; }
DEVI void ssm_kgen_load(const SsmParams& P, int d, int half, int lane, uint32_t* r) {
#pragma unroll
    for (int q = 0; q < 2; q++) {
        const int n = d * SSM_N + 64 * half + 32 * q + lane;
        r[4 * q] = ldg16(P.lar + n); r[4 * q + 1] = ldg16(P.aim + n); r[4 * q + 2] = ldg16(P.cre + n); r[4 * q + 3] = ldg16(P.cim + n);
    }
    r[8] = ldg16(P.ldt + d);
}
DEVI void ssm_kgen_warp(const uint32_t* r, int lane, uint32_t kp) {
    float raw[9];
#pragma unroll
    for (int i = 0; i < 9; i++) raw[i] = __uint_as_float(r[i] << 16);
    const int g = lane >> 2, t = lane & 3;
    float ar[2], ai[2], cr[2], ci[2], gr[2], gi[2];
    const float dt = rbf(expf(raw[8]));
#pragma unroll
    for (int q = 0; q < 2; q++) {
        ar[q] = -rbf(expf(raw[4 * q])) * dt;
        ai[q] = raw[4 * q + 1] * dt;
        cr[q] = 2.f * (raw[4 * q + 2] * dt);
        ci[q] = 2.f * (raw[4 * q + 3] * dt);
        float m = expf(ar[q] * 64.f), sn, cs;
        sincosf(ai[q] * 64.f, &sn, &cs);
        gr[q] = m * cs; gi[q] = m * sn;
    }
    float cm = 0.f;
#pragma unroll
    for (int q = 0; q < 2; q++) cm = fmaxf(cm, fmaxf(fabsf(cr[q]), fabsf(ci[q])));
#pragma unroll
    for (int o = 16; o; o >>= 1) cm = fmaxf(cm, __shfl_xor_sync(~0u, cm, o));
    const int ex = min(max((int)(__float_as_uint(cm) >> 23), 1), 253);
    const float cs_dn = __uint_as_float((uint32_t)(254 - ex) << 23), cs_up = __uint_as_float((uint32_t)ex << 23);
    float acc[5][4];
#pragma unroll
    for (int s = 0; s < 5; s++) { acc[s][0] = acc[s][1] = acc[s][2] = acc[s][3] = 0.f; }
    float klast = 0.f;
    const float gf = (float)g;
#pragma unroll
    for (int q = 0; q < 2; q++) {
#pragma unroll 1
        for (int g0 = 0; g0 < 8; g0 += 2) {
            uint32_t fa[5][4], fb[4][2];
#pragma unroll
            for (int h = 0; h < 2; h++) {
                const int src = ((g0 + h) << 2) | t;
                const float a_r = __shfl_sync(~0u, ar[q], src), a_i = __shfl_sync(~0u, ai[q], src);
                cf C, G;
                C.x = __shfl_sync(~0u, cr[q], src) * cs_dn; C.y = __shfl_sync(~0u, ci[q], src) * cs_dn;
                G.x = __shfl_sync(~0u, gr[q], src); G.y = __shfl_sync(~0u, gi[q], src);
                cf E = cexp_(a_r * gf, a_i * gf);
                cf B = csq(csq(csq(E)));
                fb[0][h] = h2c(cmul(C, B));
                cf EG = cmul(E, G);
                fa[0][2 * h] = h2(E); fa[0][2 * h + 1] = h2(EG);
                cf G2 = csq(G);
                cf X = cmul(E, G2), Xh = cmul(EG, G2);
                fa[1][2 * h] = h2(X); fa[1][2 * h + 1] = h2(Xh);
#pragma unroll
                for (int s = 2; s < 5; s++) {
                    B = csq(B); X = csq(X); Xh = csq(Xh);
                    fb[s - 1][h] = h2c(cmul(C, B));
                    fa[s][2 * h] = h2(X); fa[s][2 * h + 1] = h2(Xh);
                }
                X = csq(X);
                klast += fmaf(C.x, X.x, -C.y * X.y);
            }
            mma_group(acc, fa, fb);
        }
    }
    klast += __shfl_xor_sync(~0u, klast, 1);
    klast += __shfl_xor_sync(~0u, klast, 2);
#pragma unroll
    for (int s = 0; s < 5; s++) {
        const uint32_t b = kp + (128 * s + g + 16 * t) * 4;
        reds(b, acc[s][0] * cs_up); reds(b + 32, acc[s][1] * cs_up); reds(b + 256, acc[s][2] * cs_up); reds(b + 288, acc[s][3] * cs_up);
    }
    if (lane == 0) reds(kp + 2560, klast * cs_up);
}

constexpr int G1_THREADS = 384;
constexpr int G1_NS = 11;
constexpr int G1_SMEM = G1_NS * 16384 + 32768 + 256 + 1024;

__global__ void __cluster_dims__(2, 1, 1) __launch_bounds__(G1_THREADS, 1)
gemm_kv_kernel(const __grid_constant__ CUtensorMap tm_c, const __grid_constant__ CUtensorMap tm_wk,
               const __grid_constant__ CUtensorMap tm_wv, const __grid_constant__ CUtensorMap tm_kv_st,
               const bf16* __restrict__ px, const bf16* __restrict__ pwq) {
    extern __shared__ uint8_t smem_raw[];
    const uint32_t sb = (smem_u32(smem_raw) + 1023) & ~1023u;
    const uint32_t sC = sb + G1_NS * 16384, bars = sC + 32768;
    const uint32_t full = bars, empty = bars + 128;
    const int tid = threadIdx.x, warp = tid >> 5, lane = tid & 31, wg = tid >> 7;
    const uint32_t rank = cluster_rank();
    const int cl = blockIdx.x >> 1;
    const int m0 = ((cl & 7) * 2 + rank) * 128;
    const int ng = cl >> 3;
    STAMP(blockIdx.x == 10 && tid == 0, 0);
    if (tid == 0) {
        for (int i = 0; i < G1_NS; i++) { mbar_init(full + 8 * i, 1); mbar_init(empty + 8 * i, 16); }
        fence_barrier_init();
        for (int it = 0; it < 8; it++) {
            mbar_expect_tx(full + 8 * it, 16384);
            tma_load_2d(sb + it * 16384, &tm_c, it * 64, m0, full + 8 * it);
        }
    }
    __syncthreads();
    cluster_sync_all();
    pdl_launch();
    if (wg == 2) {
        reg_dec<40>();
        if (tid == 256) {
            const CUtensorMap* tw = ng < 4 ? &tm_wk : &tm_wv;
            const int n0 = (ng & 3) * 1024 + rank * 64;
            int st = 8; uint32_t ph = 1;
            for (int it = 0; it < 64; it++) {
                mbar_wait(empty + 8 * st, ph);
                mbar_expect_tx(full + 8 * st, 16384);
                tma_load_2d_mc(sb + st * 16384 + rank * 8192, tw, n0 + (it >> 3) * 128, (it & 7) * 64, full + 8 * st, 3);
                if (it < 2) {
                    for (int j = 3 + it * 8 + (cl & 7); j < 19; j += 16) tma_prefetch_2d(tw, n0 + (j >> 3) * 128, (j & 7) * 64);
                }
                if (it >= 3 && it + 16 < 64 && (it & 7) == (cl & 7)) tma_prefetch_2d(tw, n0 + ((it + 16) >> 3) * 128, (it & 7) * 64);
                if (it == 24) bulk_prefetch(px + blockIdx.x * 8192, 16384);
                if (it == 32) bulk_prefetch(pwq + blockIdx.x * 16384, 32768);
                if (++st == G1_NS) { st = 0; ph ^= 1; }
            }
        }
        __syncwarp();
    } else {
        reg_inc<232>();
        uint32_t af[128];
        float acc[64];
        const int wq = warp & 3;
        const int row = wg * 64 + wq * 16 + (lane & 15);
        const uint32_t stg = sC + wg * 16384;
        int st = 8, pst = 0; uint32_t ph = 0;
#pragma unroll
        for (int kc = 0; kc < 8; kc++) {
            mbar_wait(full + 8 * kc, 0);
#pragma unroll
            for (int k = 0; k < 4; k++) {
                const uint32_t a = sb + kc * 16384 + row * 128 + (((2 * k + (lane >> 4)) ^ (row & 7)) << 4);
                uint32_t* f = af + kc * 16 + k * 4;
                asm volatile("ldmatrix.sync.aligned.m8n8.x4.shared.b16 {%0,%1,%2,%3}, [%4];"
                             : "=r"(f[0]), "=r"(f[1]), "=r"(f[2]), "=r"(f[3]) : "r"(a) : "memory");
            }
            __syncwarp();
            if (lane < 2) mbar_arrive_cluster(empty + 8 * kc, lane);
        }
#pragma unroll 1
        for (int t = 0; t < 8; t++) {
            if (wg == 1 || t > 0) named_sync(3 + wg, 256);
#pragma unroll
            for (int kc = 0; kc < 8; kc++) {
                mbar_wait(full + 8 * st, ph);
                STAMP(blockIdx.x == 10 && (tid & 127) == 0, 1 + wg * 96 + t * 12 + kc);
                wg_fence();
                const uint64_t db = desc_mnmajor(sb + st * 16384, 8192);
#pragma unroll
                for (int k = 0; k < 4; k++) wgmma_rs128<1>(acc, af + kc * 16 + k * 4, db + k * 128, (kc | k) != 0);
                wg_commit();
                if (kc == 3 && (wg == 0 || t < 7)) named_arrive(3 + (wg ^ 1), 256);
                if (kc > 0) {
                    wg_wait<1>();
                    if (lane < 2) mbar_arrive_cluster(empty + 8 * pst, lane);
                }
                pst = st;
                if (++st == G1_NS) { st = 0; ph ^= 1; }
            }
            if ((tid & 127) == 0) bulk_wait_read<0>();
            named_sync(1 + wg, 128);
            wg_wait<0>();
            STAMP(blockIdx.x == 10 && (tid & 127) == 0, 9 + wg * 96 + t * 12);
            if (lane < 2) mbar_arrive_cluster(empty + 8 * pst, lane);
            store_slab64(stg, wq * 16, acc, 1.f, 1.f, lane);
            store_slab64(stg + 8192, wq * 16, acc + 32, 1.f, 1.f, lane);
            fence_proxy_async();
            named_sync(1 + wg, 128);
            if ((tid & 127) == 0) {
                tma_store_2d(&tm_kv_st, stg, ng * 1024 + t * 128, m0 + wg * 64);
                tma_store_2d(&tm_kv_st, stg + 8192, ng * 1024 + t * 128 + 64, m0 + wg * 64);
                bulk_commit();
            }
            STAMP(blockIdx.x == 10 && (tid & 127) == 0, 10 + wg * 96 + t * 12);
        }
        if ((tid & 127) == 0) bulk_wait<0>();
        __syncwarp();
    }
    asm volatile("barrier.cluster.arrive.relaxed.aligned;\nbarrier.cluster.wait.aligned;" ::: "memory");
}
constexpr int AT_NS = 6;
constexpr int AT_SMEM = AT_NS * 32768 + 32768 + 256 + 1024;
constexpr int AT_ITEMS = 512;

DEVI uint32_t hmax2(uint32_t a, uint32_t b) { uint32_t r; asm("max.bf16x2 %0, %1, %2;" : "=r"(r) : "r"(a), "r"(b)); return r; }
DEVI uint32_t hmul2(uint32_t a, uint32_t b) { uint32_t r; asm("mul.rn.bf16x2 %0, %1, %2;" : "=r"(r) : "r"(a), "r"(b)); return r; }
DEVI uint32_t hfma2(uint32_t a, uint32_t b, uint32_t c) { uint32_t r; asm("fma.rn.bf16x2 %0, %1, %2, %3;" : "=r"(r) : "r"(a), "r"(b), "r"(c)); return r; }
DEVI float blo(uint32_t v) { return __uint_as_float(v << 16); }
DEVI float bhi(uint32_t v) { return __uint_as_float(v & 0xffff0000u); }

template <bool FIRST>
DEVI void softmax_tile(float* s, float& m0, float& m1, float& l0, float& l1, float& al0, float& al1) {
    const uint32_t HI = 0x3DB53DB5u;
    const uint32_t LO = 0x371E371Eu;
    const float L2E = 1.4426950408889634f;
    uint32_t x0 = 0xFF80FF80u, x1 = 0xFF80FF80u;
#pragma unroll
    for (int j = 0; j < 16; j++) {
        uint32_t a = pack_bf16(s[4 * j], s[4 * j + 1]), b = pack_bf16(s[4 * j + 2], s[4 * j + 3]);
        a = hfma2(a, HI, hmul2(a, LO));
        b = hfma2(b, HI, hmul2(b, LO));
        s[4 * j] = __uint_as_float(a); s[4 * j + 2] = __uint_as_float(b);
        x0 = hmax2(x0, a); x1 = hmax2(x1, b);
    }
    uint32_t x = hmax2(__byte_perm(x0, x1, 0x5410), __byte_perm(x0, x1, 0x7632));
    x = hmax2(x, __shfl_xor_sync(~0u, x, 1));
    x = hmax2(x, __shfl_xor_sync(~0u, x, 2));
    float n0 = blo(x), n1 = bhi(x);
    if (!FIRST) {
        n0 = fmaxf(n0, m0); n1 = fmaxf(n1, m1);
        al0 = ex2((m0 - n0) * L2E); al1 = ex2((m1 - n1) * L2E);
    }
    m0 = n0; m1 = n1;
    const float c0 = -n0 * L2E, c1 = -n1 * L2E;
    float s0 = 0.f, s1 = 0.f;
#pragma unroll
    for (int j = 0; j < 16; j++) {
        uint32_t a = __float_as_uint(s[4 * j]), b = __float_as_uint(s[4 * j + 2]);
        float e0 = ex2(fmaf(blo(a), L2E, c0)), e1 = ex2(fmaf(bhi(a), L2E, c0));
        float e2 = ex2(fmaf(blo(b), L2E, c1)), e3 = ex2(fmaf(bhi(b), L2E, c1));
        s0 += e0 + e1; s1 += e2 + e3;
        s[4 * j] = e0; s[4 * j + 1] = e1; s[4 * j + 2] = e2; s[4 * j + 3] = e3;
    }
    if (FIRST) { l0 = s0; l1 = s1; }
    else { l0 = fmaf(l0, al0, s0); l1 = fmaf(l1, al1, s1); }
}

struct Ring {
    int st; uint32_t ph;
    DEVI void next() { if (++st == AT_NS) { st = 0; ph ^= 1; } }
};

__global__ void __launch_bounds__(384, 1)
attn_kernel(const __grid_constant__ CUtensorMap tm_x, const __grid_constant__ CUtensorMap tm_wq,
            const __grid_constant__ CUtensorMap tm_kv, const __grid_constant__ CUtensorMap tm_ctx_st,
            const SsmParams sp, const bf16* __restrict__ pwo) {
    extern __shared__ uint8_t smem_raw[];
    const uint32_t sb = (smem_u32(smem_raw) + 1023) & ~1023u;
    const uint32_t sO = sb + AT_NS * 32768, bars = sO + 32768;
    const uint32_t full = bars, empty = bars + 64;
    volatile int* slots = reinterpret_cast<volatile int*>(smem_raw + (bars + 128 - smem_u32(smem_raw)));
    const int tid = threadIdx.x, warp = tid >> 5, lane = tid & 31, wg = tid >> 7;
    if (tid == 0) {
        for (int i = 0; i < AT_NS; i++) { mbar_init(full + 8 * i, 1); mbar_init(empty + 8 * i, 8); }
        fence_barrier_init();
    }
    __syncthreads();
    if (wg == 2) {
        reg_dec<24>();
        if (warp == 8 && lane == 0) {
            Ring r{0, 1};
            int n = 0;
            while (true) {
                int idx = (int)atomicInc(&g_sched, AT_ITEMS + gridDim.x - 1);
                if (idx >= AT_ITEMS - 128 && idx < AT_ITEMS) {
                    bulk_prefetch(sp.u + (idx - (AT_ITEMS - 128)) * 8192, 16384);
                    const int po = (idx - (AT_ITEMS - 128)) * 512;
                    bulk_prefetch(sp.lar + po, 1024); bulk_prefetch(sp.aim + po, 1024);
                    bulk_prefetch(sp.cre + po, 1024); bulk_prefetch(sp.cim + po, 1024);
                    if (po == 0) { bulk_prefetch(sp.ldt, 1024); bulk_prefetch(sp.dskip, 1024); }
                    bulk_prefetch(pwo + (idx - (AT_ITEMS - 128)) * 16384, 32768);
                }
                mbar_wait(empty + 8 * r.st, r.ph);
                if (idx >= AT_ITEMS) {
                    slots[n & 3] = -1;
                    mbar_arrive(full + 8 * r.st);
                    break;
                }
                slots[n & 3] = idx;
                const int qi = 15 - (idx >> 5), h = idx & 31;
                for (int kc = 0; kc < 8; kc++) {
                    if (kc) mbar_wait(empty + 8 * r.st, r.ph);
                    const uint32_t fb = full + 8 * r.st, dst = sb + r.st * 32768;
                    mbar_expect_tx(fb, 32768);
                    tma_load_2d(dst, &tm_x, kc * 64, qi * 128, fb);
                    tma_load_2d(dst + 16384, &tm_wq, h * 128, kc * 64, fb);
                    tma_load_2d(dst + 24576, &tm_wq, h * 128 + 64, kc * 64, fb);
                    r.next();
                }
                if (n == 0) { pdl_wait(); pdl_launch(); }
                for (int j = qi; j >= -1; j--) {
#pragma unroll
                    for (int v = 0; v < 2; v++) {
                        const int jj = j + v;
                        if (jj < 0 || jj > qi || (v == 0 && j < 0)) continue;
                        mbar_wait(empty + 8 * r.st, r.ph);
                        const uint32_t fb = full + 8 * r.st, dst = sb + r.st * 32768;
                        mbar_expect_tx(fb, 32768);
                        tma_load_2d(dst, &tm_kv, v * HDALL + h * 128, jj * 128, fb);
                        tma_load_2d(dst + 16384, &tm_kv, v * HDALL + h * 128 + 64, jj * 128, fb);
                        r.next();
                    }
                }
                n++;
            }
            if (n == 0) { pdl_wait(); pdl_launch(); }
        }
    } else {
        reg_inc<240>();
        Ring r{0, 0};
        float o[64], s[64];
        uint32_t qf[32], pa[32];
        const int g = lane >> 2, t = lane & 3, wq = warp & 3;
        const uint32_t stg = sO + wg * 16384;
        if (wg == 1) named_arrive(3, 256);
        for (int n = 0;; n++) {
            mbar_wait(full + 8 * r.st, r.ph);
            const int idx = slots[n & 3];
            if (idx < 0) break;
            const int qi = 15 - (idx >> 5), h = idx & 31;
#pragma unroll 1
            for (int kc = 0; kc < 8; kc++) {
                if (kc) mbar_wait(full + 8 * r.st, r.ph);
                wg_fence();
                const uint32_t base = sb + r.st * 32768;
                const uint64_t da = desc_kmajor(base + wg * 8192), db = desc_mnmajor(base + 16384, 8192);
#pragma unroll
                for (int k = 0; k < 4; k++) wgmma_ss128<1>(s, da + k * 2, db + k * 128, (kc | k) != 0);
                wg_commit();
                if (kc) {
                    wg_wait<1>();
                    if (lane == 0) mbar_arrive(empty + 8 * (r.st == 0 ? AT_NS - 1 : r.st - 1));
                }
                r.next();
            }
            wg_wait<0>();
            if (lane == 0) mbar_arrive(empty + 8 * (r.st == 0 ? AT_NS - 1 : r.st - 1));
#pragma unroll
            for (int i = 0; i < 32; i++) qf[i] = pack_bf16(s[2 * i], s[2 * i + 1]);
            float m0, m1, l0, l1, al0, al1;
            auto issue_qk = [&]() {
                mbar_wait(full + 8 * r.st, r.ph);
                wg_fence();
                const uint64_t db = desc_kmajor(sb + r.st * 32768);
#pragma unroll
                for (int k = 0; k < 8; k++) wgmma_rs128<0>(s, qf + 4 * k, db + (k >> 2) * 1024 + (k & 3) * 2, k != 0);
                wg_commit();
            };
            auto issue_pv = [&](const uint32_t* p, int st, uint32_t ph, int acc) {
                mbar_wait(full + 8 * st, ph);
                wg_fence();
                const uint64_t db = desc_mnmajor(sb + st * 32768, 16384);
#pragma unroll
                for (int k = 0; k < 8; k++) wgmma_rs128<1>(o, p + 4 * k, db + k * 128, acc | k);
                wg_commit();
            };
            issue_qk();
            wg_wait<0>();
            if (lane == 0) mbar_arrive(empty + 8 * r.st);
            r.next();
            {
                const int row = wg * 64 + wq * 16 + g;
#pragma unroll
                for (int j = 0; j < 16; j++) {
                    const int c = 8 * j + 2 * t;
                    if (c > row) s[4 * j] = -INFINITY;
                    if (c + 1 > row) s[4 * j + 1] = -INFINITY;
                    if (c > row + 8) s[4 * j + 2] = -INFINITY;
                    if (c + 1 > row + 8) s[4 * j + 3] = -INFINITY;
                }
            }
            softmax_tile<true>(s, m0, m1, l0, l1, al0, al1);
#pragma unroll
            for (int i = 0; i < 32; i++) pa[i] = pack_bf16(s[2 * i], s[2 * i + 1]);
            int first = 0;
#pragma unroll 1
            for (int j = qi; j >= 1; j--) {
                named_sync(3 + wg, 256);
                issue_qk();
                const int kst = r.st;
                r.next();
                issue_pv(pa, r.st, r.ph, first);
                named_arrive(3 + (wg ^ 1), 256);
                wg_wait<1>();
                if (lane == 0) mbar_arrive(empty + 8 * kst);
                softmax_tile<false>(s, m0, m1, l0, l1, al0, al1);
                wg_wait<0>();
                if (lane == 0) mbar_arrive(empty + 8 * r.st);
                r.next();
#pragma unroll
                for (int i = 0; i < 32; i++) pa[i] = pack_bf16(s[2 * i], s[2 * i + 1]);
#pragma unroll
                for (int i = 0; i < 16; i++) {
                    o[4 * i] *= al0; o[4 * i + 1] *= al0; o[4 * i + 2] *= al1; o[4 * i + 3] *= al1;
                }
                first = 1;
            }
            issue_pv(pa, r.st, r.ph, first);
            l0 += __shfl_xor_sync(~0u, l0, 1); l0 += __shfl_xor_sync(~0u, l0, 2);
            l1 += __shfl_xor_sync(~0u, l1, 1); l1 += __shfl_xor_sync(~0u, l1, 2);
            const float i0 = 1.f / l0, i1 = 1.f / l1;
            if ((tid & 127) == 0) bulk_wait_read<0>();
            named_sync(1 + wg, 128);
            wg_wait<0>();
            if (lane == 0) mbar_arrive(empty + 8 * r.st);
            r.next();
            store_slab64(stg, wq * 16, o, i0, i1, lane);
            store_slab64(stg + 8192, wq * 16, o + 32, i0, i1, lane);
            fence_proxy_async();
            named_sync(1 + wg, 128);
            if ((tid & 127) == 0) {
                tma_store_2d(&tm_ctx_st, stg, h * 128, qi * 128 + wg * 64);
                tma_store_2d(&tm_ctx_st, stg + 8192, h * 128 + 64, qi * 128 + wg * 64);
                bulk_commit();
            }
        }
        if ((tid & 127) == 0) bulk_wait<0>();
    }
}
constexpr int OP_NS = 4;
constexpr int OP_ULD = 164 * 16;
constexpr int OP_UCH = 2 * OP_ULD;
constexpr int OP_SMEM = OP_NS * 32768 + 32768 + 4 * WTAB * 4 + 4 * OP_UCH + 4 * 648 * 4 + 256 + 1024;

template <int N> DEVI void wgmma_conv(float* d, const uint32_t* a, uint64_t db);
template <> DEVI void wgmma_conv<128>(float* d, const uint32_t* a, uint64_t db) {
    asm volatile("wgmma.mma_async.sync.aligned.m64n128k16.f32.bf16.bf16 {%0,%1,%2,%3,%4,%5,%6,%7,%8,%9,%10,%11,%12,%13,%14,%15,%16,%17,%18,%19,%20,%21,%22,%23,%24,%25,%26,%27,%28,%29,%30,%31,%32,%33,%34,%35,%36,%37,%38,%39,%40,%41,%42,%43,%44,%45,%46,%47,%48,%49,%50,%51,%52,%53,%54,%55,%56,%57,%58,%59,%60,%61,%62,%63}, "
                 "{%64,%65,%66,%67}, %68, 1, 1, 1, 0;"
                 : ACC8(d, 0), ACC8(d, 8), ACC8(d, 16), ACC8(d, 24), ACC8(d, 32), ACC8(d, 40), ACC8(d, 48), ACC8(d, 56) : "r"(a[0]), "r"(a[1]), "r"(a[2]), "r"(a[3]), "l"(db));
}
template <> DEVI void wgmma_conv<96>(float* d, const uint32_t* a, uint64_t db) {
    asm volatile("wgmma.mma_async.sync.aligned.m64n96k16.f32.bf16.bf16 {%0,%1,%2,%3,%4,%5,%6,%7,%8,%9,%10,%11,%12,%13,%14,%15,%16,%17,%18,%19,%20,%21,%22,%23,%24,%25,%26,%27,%28,%29,%30,%31,%32,%33,%34,%35,%36,%37,%38,%39,%40,%41,%42,%43,%44,%45,%46,%47}, "
                 "{%48,%49,%50,%51}, %52, 1, 1, 1, 0;"
                 : ACC8(d, 0), ACC8(d, 8), ACC8(d, 16), ACC8(d, 24), ACC8(d, 32), ACC8(d, 40) : "r"(a[0]), "r"(a[1]), "r"(a[2]), "r"(a[3]), "l"(db));
}
template <> DEVI void wgmma_conv<64>(float* d, const uint32_t* a, uint64_t db) {
    asm volatile("wgmma.mma_async.sync.aligned.m64n64k16.f32.bf16.bf16 {%0,%1,%2,%3,%4,%5,%6,%7,%8,%9,%10,%11,%12,%13,%14,%15,%16,%17,%18,%19,%20,%21,%22,%23,%24,%25,%26,%27,%28,%29,%30,%31}, "
                 "{%32,%33,%34,%35}, %36, 1, 1, 1, 0;"
                 : ACC8(d, 0), ACC8(d, 8), ACC8(d, 16), ACC8(d, 24) : "r"(a[0]), "r"(a[1]), "r"(a[2]), "r"(a[3]), "l"(db));
}
template <> DEVI void wgmma_conv<32>(float* d, const uint32_t* a, uint64_t db) {
    asm volatile("wgmma.mma_async.sync.aligned.m64n32k16.f32.bf16.bf16 {%0,%1,%2,%3,%4,%5,%6,%7,%8,%9,%10,%11,%12,%13,%14,%15}, "
                 "{%16,%17,%18,%19}, %20, 1, 1, 1, 0;"
                 : ACC8(d, 0), ACC8(d, 8) : "r"(a[0]), "r"(a[1]), "r"(a[2]), "r"(a[3]), "l"(db));
}
DEVI uint32_t lds32(uint32_t a) { uint32_t v; asm volatile("ld.shared.b32 %0, [%1];" : "=r"(v) : "r"(a)); return v; }
DEVI uint32_t lds16(uint32_t a) { uint16_t v; asm volatile("ld.shared.b16 %0, [%1];" : "=h"(v) : "r"(a)); return v; }

DEVI void sts32(uint32_t a, float v) { asm volatile("st.shared.f32 [%0], %1;" ::"r"(a), "f"(v) : "memory"); }
template <int J> DEVI void conv_group(float* acc, uint32_t* f, uint32_t wa, uint64_t du) {
#pragma unroll
    for (int i = 0; i < 8; i++) {
        const uint32_t w = wa + (8 * J + i) * 256;
        f[4 * i] = lds32(w); f[4 * i + 1] = lds32(w + 32); f[4 * i + 2] = lds32(w - 32); f[4 * i + 3] = f[4 * i];
    }
    wg_fence();
#pragma unroll
    for (int i = 0; i < 8; i++) wgmma_conv<128 - 32 * J>(acc, f + 4 * i, du + (uint64_t)(4 * (8 * J + i)));
    wg_commit();
}
DEVI uint32_t ypos(int a, int b) { return (uint32_t)(b * 128 + (a ^ ((b & 3) << 3))) * 4; }

DEVI void expand_table(int ct, uint32_t sW, uint32_t sK) {
#pragma unroll 1
    for (int i = ct; i < WTAB; i += 384) {
        const int c = (i >> 3) & 3, qd = (i & 7) | ((i >> 5) << 3);
        float k[5];
#pragma unroll
        for (int e = 0; e < 5; e++) {
            const int l = qd * 4 - 65 + e;
            const int hi = (int)__bfloat16_as_ushort(__float2bfloat16_rn((float)l)) - 17024;
            k[e] = __uint_as_float(lds32(sK + (c * 648 + (l < 0 ? 644 : (l < 128 ? l : hi))) * 4));
        }
        asm volatile("st.shared.v4.b32 [%0], {%1,%2,%3,%4};" ::"r"(sW + (c * WTAB + qd * 4) * 4), "r"(pack_bf16(k[1], k[0])),
                     "r"(pack_bf16(k[2], k[1])), "r"(pack_bf16(k[3], k[2])), "r"(pack_bf16(k[4], k[3])) : "memory");
    }
}

__global__ void __cluster_dims__(2, 1, 1) __launch_bounds__(512, 1)
outproj_kernel(const __grid_constant__ CUtensorMap tm_ctx, const __grid_constant__ CUtensorMap tm_wo,
               const __grid_constant__ CUtensorMap tm_out, const __grid_constant__ CUtensorMap tm_u, SsmParams sp, bf16* __restrict__ out) {
    extern __shared__ uint8_t smem_raw[];
    const uint32_t sb = (smem_u32(smem_raw) + 1023) & ~1023u;
    const uint32_t sX = sb + OP_NS * 32768, sW = sX + 32768, sU = sW + 4 * WTAB * 4, sK = sU + 4 * OP_UCH, bars = sK + 4 * 648 * 4;
    const uint32_t full = bars, empty = bars + 64, xfull = bars + 128, wfull = bars + 136, xfree = bars + 144;
    const int tid = threadIdx.x, warp = tid >> 5, lane = tid & 31, wg = tid >> 7;
    const uint32_t rank = cluster_rank();
    const uint32_t kr = rank;
    const int cl = blockIdx.x >> 1;
    const int m0 = (cl >> 2) * 128, n0 = (cl & 3) * 128, k0 = kr * 2048;
    STAMP(blockIdx.x == 10 && tid == 0, 1000);
    uint32_t praw[9];
    ssm_kgen_load(sp, blockIdx.x * 4 + (warp & 3), wg & 1, lane, praw);
    if (tid == 0) {
        for (int i = 0; i < OP_NS; i++) { mbar_init(full + 8 * i, 1); mbar_init(empty + 8 * i, 8); }
        mbar_init(xfull, 1);
        mbar_init(wfull, 1);
        mbar_init(xfree, 1);
        fence_barrier_init();
        mbar_expect_tx(wfull, 32768);
        for (int i = 0; i < 8; i++) tma_load_2d(sX + i * 4096, &tm_u, cl * 8, i * 256, wfull);
    }
    for (int i = tid; i < 648; i += 512) asm volatile("st.shared.v4.b32 [%0], {%1,%1,%1,%1};" ::"r"(sK + i * 16), "r"(0) : "memory");
    __syncthreads();
    cluster_arrive();
    if (wg == 3) {
        reg_dec<40>();
        cluster_wait();
        if (tid == 384) {
            mbar_expect_tx(xfull, 32768);
            for (int it = 0; it < OP_NS; it++) {
                const uint32_t dst = sb + it * 32768, fb = full + 8 * it;
                mbar_expect_tx(fb, 32768);
                tma_load_2d(dst + 16384, &tm_wo, n0, k0 + it * 64, fb);
                tma_load_2d(dst + 24576, &tm_wo, n0 + 64, k0 + it * 64, fb);
            }
            pdl_wait();
            STAMP(blockIdx.x == 10, 1005);
            for (int it = 0; it < 32; it++) {
                const int st = it & (OP_NS - 1);
                const uint32_t dst = sb + st * 32768, fb = full + 8 * st;
                if (it >= OP_NS) {
                    mbar_wait(empty + 8 * st, ((it / OP_NS) & 1) ^ 1);
                    mbar_expect_tx(fb, 32768);
                    tma_load_2d(dst + 16384, &tm_wo, n0, k0 + it * 64, fb);
                    tma_load_2d(dst + 24576, &tm_wo, n0 + 64, k0 + it * 64, fb);
                }
                tma_load_2d(dst, &tm_ctx, k0 + it * 64, m0, fb);
                tma_load_2d(dst + 8192, &tm_ctx, k0 + it * 64, m0 + 64, fb);
            }
        }
        __syncwarp();
    } else {
      const int ct = tid & 127, wq = warp & 3;
      if (wg == 2) {
        for (int i = ct; i < 8 * 32; i += 128) {
            const uint32_t a = sU + (i >> 5) * OP_ULD + (128 + (i & 31)) * 16;
            asm volatile("st.shared.v4.b32 [%0], {%1,%1,%1,%1};" ::"r"(a), "r"(0) : "memory");
        }
        const bool mine = ((lane >> 2) & 1) == (int)rank;
        const uint32_t ub = sU + (lane & 3) * OP_UCH + ((lane >> 3) & 1) * OP_ULD + (127 - 2 * wq - (lane >> 4)) * 16;
        mbar_wait(wfull, 0);
#pragma unroll 4
        for (int i = 0; i < 16; i++) {
            uint32_t r0, r1, r2, r3;
            asm volatile("ldmatrix.sync.aligned.m8n8.x4.trans.shared.b16 {%0,%1,%2,%3}, [%4];"
                         : "=r"(r0), "=r"(r1), "=r"(r2), "=r"(r3) : "r"(sX + (i * 128 + ct) * 16) : "memory");
            asm volatile("stmatrix.sync.aligned.m8n8.x4.shared.b16 [%0], {%1,%2,%3,%4};"
                         ::"r"(mine ? ub - i * 128 : sW + lane * 16), "r"(r0), "r"(r1), "r"(r2), "r"(r3) : "memory");
        }
        fence_proxy_async();
        STAMP(blockIdx.x == 10 && ct == 0, 1001);
      } else {
        ssm_kgen_warp(praw, lane, sK + wq * 648 * 4);
      }
      cluster_wait();
      named_sync(3, 384);
      if (tid == 256) mbar_arrive_cluster(xfree, rank ^ 1);
      STAMP(blockIdx.x == 10 && tid == 257, 1002);
      expand_table(tid, sW, sK);
      if (wg == 2) {
        reg_inc<208>();
        const int g = lane >> 2, t = lane & 3;
        const int d0 = blockIdx.x * 4;
        const uint2 dsk = __ldg(reinterpret_cast<const uint2*>(sp.dskip + d0));
        named_sync(4, 384);
        uint32_t res[16][2];
        STAMP(blockIdx.x == 10 && ct == 0, 1003);
#pragma unroll 1
        for (int c = 0; c < 4; c++) {
            float acc[64];
            uint32_t fa[32], fb[32];
#pragma unroll
            for (int i = 0; i < 64; i++) acc[i] = 0.f;
            const uint32_t wa = sW + (c * WTAB + 64 + 16 * wq + g - 2 * t) * 4;
            const uint64_t du = make_desc(sU + c * OP_UCH, OP_ULD, 128, 0);
            conv_group<0>(acc, fa, wa, du);
            conv_group<1>(acc, fb, wa, du);
            wg_wait<1>();
            conv_group<2>(acc, fa, wa, du);
            wg_wait<1>();
            conv_group<3>(acc, fb, wa, du);
            named_sync(5, 128);
            wg_wait<0>();
            const uint32_t yb = (wq & 1) ? sW + c * WTAB * 4 : sK;
            const bool skip0 = wq >= 2 && t == 0;
            if (wq >= 2) {
                named_sync(6, 128);
#pragma unroll
                for (int hf = 0; hf < 2; hf++) {
                    float2 v[16];
#pragma unroll
                    for (int i = 0; i < 16; i++)
                        asm volatile("ld.shared.v2.f32 {%0,%1}, [%2];" : "=f"(v[i].x), "=f"(v[i].y)
                                     : "r"(yb + ypos((128 - 8 * (8 * hf + (i >> 1)) - 2 * t) & 127, g + 8 * (i & 1))));
#pragma unroll
                    for (int i = 0; i < 16; i++) { acc[32 * hf + 2 * i] += v[i].y; acc[32 * hf + 2 * i + 1] += v[i].x; }
                }
            }
#pragma unroll
            for (int i = 0; i < 32; i++) {
                const uint32_t p = yb + ypos(126 - 8 * (i >> 1) - 2 * t + (wq & 2), g + 8 * (i & 1));
                if (i >= 2 || !skip0) asm volatile("st.shared.v2.f32 [%0], {%1,%2};" ::"r"(p), "f"(acc[2 * i + 1]), "f"(acc[2 * i]) : "memory");
            }
            if (wq < 2) named_arrive(6, 128);
            named_sync(5, 128);
            const uint32_t dw = (c & 2) ? dsk.y : dsk.x;
            const float D = (c & 1) ? bhi(dw) : blo(dw);
            const int yb2 = (lane >> 3) + 4 * wq;
#pragma unroll
            for (int i = 0; i < 16; i++) {
                const int a = 8 * i + (lane & 7);
                float y = __uint_as_float(lds32(sW + c * WTAB * 4 + ypos((a - 1) & 127, yb2)));
                y = __uint_as_float(lds32(sK + ypos(a, yb2))) + (a == 0 ? 0.f : y);
                const float u = __uint_as_float(lds16(sU + c * OP_UCH + (wq >> 1) * OP_ULD + (127 - a) * 16 + (yb2 & 7) * 2) << 16);
                const uint32_t o = __bfloat16_as_ushort(__float2bfloat16_rn(rbf(y) + rbf(u * D)));
                res[i][0] = __byte_perm(res[i][0], res[i][1], 0x5432); res[i][1] = __byte_perm(res[i][1], o, 0x5432);
            }
        }
        STAMP(blockIdx.x == 10 && ct == 0, 1004);
        const int grp = blockIdx.x >> 2, me = blockIdx.x & 3;
#pragma unroll
        for (int i = 0; i < 8; i++)
            __stcg(g_y + (((grp * 4 + (i >> 1)) * 4 + me) * 2 + (i & 1)) * 128 + ct,
                   make_uint4(res[2 * i][0], res[2 * i][1], res[2 * i + 1][0], res[2 * i + 1][1]));
        named_sync(5, 128);
        if (ct == 0) {
            __threadfence();
            const unsigned int target = (atomicAdd(g_ycnt + grp, 1u) & ~3u) + 4u;
            uint32_t t0, t1, v;
            asm volatile("mov.u32 %0, %%globaltimer_lo;" : "=r"(t0));
            do {
                asm volatile("ld.acquire.gpu.global.u32 %0, [%1];" : "=r"(v) : "l"(g_ycnt + grp) : "memory");
                asm volatile("mov.u32 %0, %%globaltimer_lo;" : "=r"(t1));
            } while ((int)(v - target) < 0 && t1 - t0 < 4000000u);
        }
        named_sync(5, 128);
        uint4 y[8];
#pragma unroll
        for (int i = 0; i < 8; i++)
            y[i] = __ldcg(g_y + ((blockIdx.x * 4 + 2 * (t & 1) + ((i >> 1) & 1)) * 2 + (i & 1)) * 128 + (ct & ~1) + (i >> 2));
#pragma unroll
        for (int i = 0; i < 8; i++) {
            const int row = 128 * (4 * me + (i & 3)) + 16 * ((lane & 6) + (i >> 2)) + 4 * wq + (lane >> 3);
            const uint4 p = y[(i & 4) + ((i >> 1) & 1)], q = y[(i & 4) + 2 + ((i >> 1) & 1)];
            *reinterpret_cast<uint4*>(out + (size_t)row * 1024 + 512 + grp * 16 + (t & 1) * 8) =
                (i & 1) ? make_uint4(p.z, p.w, q.z, q.w) : make_uint4(p.x, p.y, q.x, q.y);
        }
      } else {
        named_arrive(4, 384);
        float acc[64];
#pragma unroll 1
        for (int it = 0; it < 32; it++) {
            const int st = it & (OP_NS - 1);
            mbar_wait(full + 8 * st, (it / OP_NS) & 1);
            STAMP(blockIdx.x == 10 && tid == 0, 1009 + it);
            wg_fence();
            const uint32_t base = sb + st * 32768;
            const uint64_t da = desc_kmajor(base + wg * 8192), db = desc_mnmajor(base + 16384, 8192);
#pragma unroll
            for (int k = 0; k < 4; k++) wgmma_ss128<1>(acc, da + k * 2, db + k * 128, (it | k) != 0);
            wg_commit();
            if (it > 0 && it + OP_NS - 1 < 32) {
                wg_wait<1>();
                if (lane == 0) mbar_arrive(empty + 8 * ((it - 1) & (OP_NS - 1)));
            }
        }
        wg_wait<0>();
        mbar_wait(xfree, 0);
        uint32_t peer, pbar;
        asm volatile("mapa.shared::cluster.u32 %0, %1, %2;" : "=r"(peer) : "r"(sX + tid * 16), "r"(rank ^ 1));
        asm volatile("mapa.shared::cluster.u32 %0, %1, %2;" : "=r"(pbar) : "r"(xfull), "r"(rank ^ 1));
#pragma unroll
        for (int i = 0; i < 8; i++) {
            const float* s = acc + 4 * i;
            const float a = kr ? s[0] : s[32], b = kr ? s[1] : s[33], c = kr ? s[2] : s[34], d = kr ? s[3] : s[35];
            asm volatile("st.async.weak.shared::cluster.mbarrier::complete_tx::bytes.v4.f32 [%0], {%1,%2,%3,%4}, [%5];"
                         ::"r"(peer + i * 4096), "f"(a), "f"(b), "f"(c), "f"(d), "r"(pbar) : "memory");
        }
        STAMP(blockIdx.x == 10 && tid == 0, 1006);
        mbar_wait(xfull, 0);
        STAMP(blockIdx.x == 10 && tid == 0, 1007);
        float r[32];
#pragma unroll
        for (int i = 0; i < 8; i++) {
            float a, b, c, d;
            asm volatile("ld.shared.v4.f32 {%0,%1,%2,%3}, [%4];" : "=f"(a), "=f"(b), "=f"(c), "=f"(d) : "r"(sX + tid * 16 + i * 4096));
            const float* s = acc + 4 * i;
            r[4 * i] = a + (kr ? s[32] : s[0]); r[4 * i + 1] = b + (kr ? s[33] : s[1]);
            r[4 * i + 2] = c + (kr ? s[34] : s[2]); r[4 * i + 3] = d + (kr ? s[35] : s[3]);
        }
        const uint32_t stg = sb + wg * 8192;
        store_slab64(stg, (warp & 3) * 16, r, 1.f, 1.f, lane);
        fence_proxy_async();
        named_sync(1 + wg, 128);
        if ((tid & 127) == 0) {
            tma_store_2d(&tm_out, stg, n0 + kr * 64, m0 + wg * 64);
            bulk_commit();
            bulk_wait<0>();
            STAMP(blockIdx.x == 10 && tid == 0, 1008);
        }
      }
    }
}

typedef CUresult (*EncodeFn)(CUtensorMap*, CUtensorMapDataType, cuuint32_t, void*, const cuuint64_t*, const cuuint64_t*,
                             const cuuint32_t*, const cuuint32_t*, CUtensorMapInterleave, CUtensorMapSwizzle,
                             CUtensorMapL2promotion, CUtensorMapFloatOOBfill);

static void make_map(EncodeFn fn, CUtensorMap* m, const void* p, uint64_t cols, uint64_t rows, uint32_t box_rows) {
    cuuint64_t dims[2] = {cols, rows};
    cuuint64_t strides[1] = {cols * 2};
    cuuint32_t box[2] = {64, box_rows};
    cuuint32_t es[2] = {1, 1};
    fn(m, CU_TENSOR_MAP_DATA_TYPE_BFLOAT16, 2, const_cast<void*>(p), dims, strides, box, es, CU_TENSOR_MAP_INTERLEAVE_NONE,
       CU_TENSOR_MAP_SWIZZLE_128B, CU_TENSOR_MAP_L2_PROMOTION_L2_256B, CU_TENSOR_MAP_FLOAT_OOB_FILL_NONE);
}

extern "C" void kernel_launch(void* const* d_in, const int* in_sizes, int n_in, void* d_out, int out_size) {
    void* fp = nullptr;
    cudaDriverEntryPointQueryResult qr;
    cudaGetDriverEntryPoint("cuTensorMapEncodeTiled", &fp, cudaEnableDefault, &qr);
    EncodeFn fn = (EncodeFn)fp;
    void *p_kv, *p_ctx;
    cudaGetSymbolAddress(&p_kv, g_kv);
    cudaGetSymbolAddress(&p_ctx, g_ctx);
    CUtensorMap tm_kv_st, tm_x, tm_c, tm_wq, tm_wk, tm_wv, tm_wo, tm_kv, tm_ctx, tm_out;
    make_map(fn, &tm_x, d_in[0], DM, SEQ, 128);
    make_map(fn, &tm_c, d_in[1], DM, SEQ, 128);
    make_map(fn, &tm_wq, d_in[2], HDALL, DM, 64);
    make_map(fn, &tm_wk, d_in[3], HDALL, DM, 64);
    make_map(fn, &tm_wv, d_in[4], HDALL, DM, 64);
    make_map(fn, &tm_wo, d_in[5], DM, HDALL, 64);
    make_map(fn, &tm_kv, p_kv, 2 * HDALL, SEQ, 128);
    make_map(fn, &tm_kv_st, p_kv, 2 * HDALL, SEQ, 64);
    make_map(fn, &tm_ctx, p_ctx, HDALL, SEQ, 64);
    make_map(fn, &tm_out, d_out, 1024, SEQ, 64);
    CUtensorMap tm_u;
    {
        cuuint64_t dims[2] = {512, 2048}, strides[1] = {1024};
        cuuint32_t box[2] = {8, 256}, es[2] = {1, 1};
        fn(&tm_u, CU_TENSOR_MAP_DATA_TYPE_BFLOAT16, 2, d_in[6], dims, strides, box, es, CU_TENSOR_MAP_INTERLEAVE_NONE,
           CU_TENSOR_MAP_SWIZZLE_NONE, CU_TENSOR_MAP_L2_PROMOTION_NONE, CU_TENSOR_MAP_FLOAT_OOB_FILL_NONE);
    }
    SsmParams sp;
    sp.u = (const bf16*)d_in[6]; sp.lar = (const bf16*)d_in[7]; sp.aim = (const bf16*)d_in[8];
    sp.cre = (const bf16*)d_in[9]; sp.cim = (const bf16*)d_in[10]; sp.ldt = (const bf16*)d_in[11]; sp.dskip = (const bf16*)d_in[12];
    cudaFuncSetAttribute(gemm_kv_kernel, cudaFuncAttributeMaxDynamicSharedMemorySize, G1_SMEM);
    cudaFuncSetAttribute(attn_kernel, cudaFuncAttributeMaxDynamicSharedMemorySize, AT_SMEM);
    cudaFuncSetAttribute(outproj_kernel, cudaFuncAttributeMaxDynamicSharedMemorySize, OP_SMEM);
    cudaStream_t st = cudaStreamPerThread;
    gemm_kv_kernel<<<128, G1_THREADS, G1_SMEM, st>>>(tm_c, tm_wk, tm_wv, tm_kv_st, (const bf16*)d_in[0], (const bf16*)d_in[2]);
    cudaLaunchAttribute at[1];
    at[0].id = cudaLaunchAttributeProgrammaticStreamSerialization;
    at[0].val.programmaticStreamSerializationAllowed = 1;
    cudaLaunchConfig_t cfg = {};
    cfg.stream = st; cfg.attrs = at; cfg.numAttrs = 1;
    cfg.gridDim = dim3(132); cfg.blockDim = dim3(384); cfg.dynamicSmemBytes = AT_SMEM;
    cudaLaunchKernelEx(&cfg, attn_kernel, tm_x, tm_wq, tm_kv, tm_ctx, sp, (const bf16*)d_in[5]);
    cfg.gridDim = dim3(128); cfg.blockDim = dim3(512); cfg.dynamicSmemBytes = OP_SMEM;
    cudaLaunchKernelEx(&cfg, outproj_kernel, tm_ctx, tm_wo, tm_out, tm_u, sp, (bf16*)d_out);
}
```

```cpp
#include <cuda_runtime.h>
#include <cuda_bf16.h>
#include <cuda.h>
#include <stdint.h>

typedef __nv_bfloat16 bf16;

#define DEVI __device__ __forceinline__

constexpr int SEQ = 2048, DM = 512, NH = 32, HD = 128, HDALL = NH * HD;
constexpr int SSM_D = 512, SSM_N = 128;
constexpr int WTAB = 2112;

__device__ bf16 g_kv[(size_t)SEQ * 2 * HDALL];
__device__ bf16 g_ctx[(size_t)SEQ * HDALL];
__device__ uint4 g_y[32 * 4 * 4 * 2 * 128];
__device__ unsigned int g_ycnt[32];
__device__ unsigned int g_sched;

#define STAMP(cond, i)
DEVI uint32_t smem_u32(const void* p) { return (uint32_t)__cvta_generic_to_shared(p); }
DEVI void mbar_init(uint32_t a, uint32_t cnt) { asm volatile("mbarrier.init.shared::cta.b64 [%0], %1;" ::"r"(a), "r"(cnt)); }
DEVI void mbar_expect_tx(uint32_t a, uint32_t bytes) {
    asm volatile("mbarrier.arrive.expect_tx.shared::cta.b64 _, [%0], %1;" ::"r"(a), "r"(bytes) : "memory");
}
DEVI void mbar_arrive(uint32_t a) { asm volatile("mbarrier.arrive.shared::cta.b64 _, [%0];" ::"r"(a) : "memory"); }
DEVI void mbar_arrive_cluster(uint32_t a, uint32_t cta) {
    asm volatile("{\n.reg .b32 r;\nmapa.shared::cluster.u32 r, %0, %1;\n"
                 "mbarrier.arrive.shared::cluster.b64 _, [r];\n}" ::"r"(a), "r"(cta) : "memory");
}
#define MBAR_WAIT_ASM(OP)                                                                              \
    asm volatile("{\n.reg .pred p, q;\n.reg .u32 t0, t1;\n" OP " p, [%0], %1;\n@p bra D_%=;\n"         \
                 "mov.u32 t0, %%globaltimer_lo;\nW_%=:\n" OP " p, [%0], %1;\n"                         \
                 "mov.u32 t1, %%globaltimer_lo;\nsub.u32 t1, t1, t0;\n"                                \
                 "setp.gt.or.u32 q, t1, 4000000, p;\n@!q bra W_%=;\nD_%=:\n}" ::"r"(a), "r"(parity) : "memory")
DEVI void mbar_wait(uint32_t a, uint32_t parity) { MBAR_WAIT_ASM("mbarrier.try_wait.parity.shared::cta.b64"); }
DEVI void mbar_wait_cluster(uint32_t a, uint32_t parity) { MBAR_WAIT_ASM("mbarrier.try_wait.parity.acquire.cluster.shared::cta.b64"); }
DEVI void fence_barrier_init() { asm volatile("fence.mbarrier_init.release.cluster;" ::: "memory"); }
DEVI void fence_proxy_async() { asm volatile("fence.proxy.async.shared::cta;" ::: "memory"); }
DEVI void cluster_sync_all() {
    asm volatile("barrier.cluster.arrive.relaxed.aligned;\nbarrier.cluster.wait.aligned;" ::: "memory");
}
DEVI void cluster_arrive() { asm volatile("barrier.cluster.arrive.relaxed.aligned;" ::: "memory"); }
DEVI void cluster_wait() { asm volatile("barrier.cluster.wait.aligned;" ::: "memory"); }
DEVI uint32_t cluster_rank() { uint32_t r; asm volatile("mov.u32 %0, %%cluster_ctarank;" : "=r"(r)); return r; }
DEVI void tma_load_2d(uint32_t dst, const CUtensorMap* m, int c0, int c1, uint32_t bar) {
    asm volatile("cp.async.bulk.tensor.2d.shared::cluster.global.mbarrier::complete_tx::bytes [%0], [%1, {%3, %4}], [%2];"
                 ::"r"(dst), "l"(m), "r"(bar), "r"(c0), "r"(c1) : "memory");
}
DEVI void tma_load_2d_mc(uint32_t dst, const CUtensorMap* m, int c0, int c1, uint32_t bar, uint16_t mask) {
    asm volatile("cp.async.bulk.tensor.2d.shared::cluster.global.mbarrier::complete_tx::bytes.multicast::cluster [%0], [%1, {%3, %4}], [%2], %5;"
                 ::"r"(dst), "l"(m), "r"(bar), "r"(c0), "r"(c1), "h"(mask) : "memory");
}
DEVI void tma_prefetch_2d(const CUtensorMap* m, int c0, int c1) {
    asm volatile("cp.async.bulk.prefetch.tensor.2d.L2.global [%0, {%1, %2}];" ::"l"(m), "r"(c0), "r"(c1) : "memory");
}
DEVI void tma_store_2d(const CUtensorMap* m, uint32_t src, int c0, int c1) {
    asm volatile("cp.async.bulk.tensor.2d.global.shared::cta.bulk_group [%0, {%2, %3}], [%1];"
                 ::"l"(m), "r"(src), "r"(c0), "r"(c1) : "memory");
}
DEVI void bulk_load(uint32_t dst, const void* src, uint32_t bytes, uint32_t bar) {
    asm volatile("cp.async.bulk.shared::cluster.global.mbarrier::complete_tx::bytes [%0], [%1], %2, [%3];"
                 ::"r"(dst), "l"(src), "r"(bytes), "r"(bar) : "memory");
}
DEVI void bulk_prefetch(const void* src, uint32_t bytes) {
    asm volatile("cp.async.bulk.prefetch.L2.global [%0], %1;" ::"l"(src), "r"(bytes) : "memory");
}
DEVI void bulk_commit() { asm volatile("cp.async.bulk.commit_group;" ::: "memory"); }
template <int N> DEVI void bulk_wait_read() { asm volatile("cp.async.bulk.wait_group.read %0;" ::"n"(N) : "memory"); }
template <int N> DEVI void bulk_wait() { asm volatile("cp.async.bulk.wait_group %0;" ::"n"(N) : "memory"); }
DEVI void prefetch_tmap(const CUtensorMap* m) { asm volatile("prefetch.tensormap [%0];" ::"l"(m) : "memory"); }
DEVI void named_sync(int id, int n) { asm volatile("bar.sync %0, %1;" ::"r"(id), "r"(n) : "memory"); }
DEVI void named_arrive(int id, int n) { asm volatile("bar.arrive %0, %1;" ::"r"(id), "r"(n) : "memory"); }
DEVI void pdl_wait() { asm volatile("griddepcontrol.wait;" ::: "memory"); }
DEVI void pdl_launch() { asm volatile("griddepcontrol.launch_dependents;" ::: "memory"); }
template <int R> DEVI void reg_inc() { asm volatile("setmaxnreg.inc.sync.aligned.u32 %0;" ::"n"(R)); }
template <int R> DEVI void reg_dec() { asm volatile("setmaxnreg.dec.sync.aligned.u32 %0;" ::"n"(R)); }

DEVI void wg_fence() { asm volatile("wgmma.fence.sync.aligned;" ::: "memory"); }
DEVI void wg_commit() { asm volatile("wgmma.commit_group.sync.aligned;" ::: "memory"); }
template <int N> DEVI void wg_wait() { asm volatile("wgmma.wait_group.sync.aligned %0;" ::"n"(N) : "memory"); }

DEVI uint64_t make_desc(uint32_t addr, uint32_t lbo, uint32_t sbo, uint32_t swz) {
    return (uint64_t)((addr & 0x3FFFF) >> 4) | ((uint64_t)(lbo >> 4) << 16) | ((uint64_t)(sbo >> 4) << 32) | ((uint64_t)swz << 62);
}
DEVI uint64_t desc_kmajor(uint32_t addr) { return make_desc(addr, 16, 1024, 1); }
DEVI uint64_t desc_mnmajor(uint32_t addr, uint32_t lbo) { return make_desc(addr, lbo, 1024, 1); }

#define ACC8(d, o) "+f"(d[o + 0]), "+f"(d[o + 1]), "+f"(d[o + 2]), "+f"(d[o + 3]), "+f"(d[o + 4]), "+f"(d[o + 5]), "+f"(d[o + 6]), "+f"(d[o + 7])
#define ACC64(d) ACC8(d, 0), ACC8(d, 8), ACC8(d, 16), ACC8(d, 24), ACC8(d, 32), ACC8(d, 40), ACC8(d, 48), ACC8(d, 56)
#define R64 "{%0,%1,%2,%3,%4,%5,%6,%7,%8,%9,%10,%11,%12,%13,%14,%15,%16,%17,%18,%19,%20,%21,%22,%23,%24,%25,%26,%27,%28,%29,%30,%31," \
            "%32,%33,%34,%35,%36,%37,%38,%39,%40,%41,%42,%43,%44,%45,%46,%47,%48,%49,%50,%51,%52,%53,%54,%55,%56,%57,%58,%59,%60,%61,%62,%63}"

template <int TB> DEVI void wgmma_ss128(float* d, uint64_t da, uint64_t db, int acc) {
    asm volatile("{\n.reg .pred p;\nsetp.ne.b32 p, %66, 0;\n"
                 "wgmma.mma_async.sync.aligned.m64n128k16.f32.bf16.bf16 " R64 ", %64, %65, p, 1, 1, 0, %67;\n}"
                 : ACC64(d) : "l"(da), "l"(db), "r"(acc), "n"(TB));
}
template <int TB> DEVI void wgmma_rs128(float* d, const uint32_t* a, uint64_t db, int acc) {
    asm volatile("{\n.reg .pred p;\nsetp.ne.b32 p, %69, 0;\n"
                 "wgmma.mma_async.sync.aligned.m64n128k16.f32.bf16.bf16 " R64 ", {%64,%65,%66,%67}, %68, p, 1, 1, %70;\n}"
                 : ACC64(d) : "r"(a[0]), "r"(a[1]), "r"(a[2]), "r"(a[3]), "l"(db), "r"(acc), "n"(TB));
}
DEVI uint32_t pack_bf16(float lo, float hi) {
    uint32_t r;
    asm("cvt.rn.bf16x2.f32 %0, %1, %2;" : "=r"(r) : "f"(hi), "f"(lo));
    return r;
}
DEVI void stmatrix_x4(uint32_t addr, uint32_t r0, uint32_t r1, uint32_t r2, uint32_t r3) {
    asm volatile("stmatrix.sync.aligned.m8n8.x4.shared.b16 [%0], {%1,%2,%3,%4};" ::"r"(addr), "r"(r0), "r"(r1), "r"(r2), "r"(r3) : "memory");
}
DEVI float ex2(float x) { float y; asm("ex2.approx.ftz.f32 %0, %1;" : "=f"(y) : "f"(x)); return y; }

DEVI void store_slab64(uint32_t base, int row0, const float* d, float s0, float s1, int lane) {
    int mi = lane >> 3, r = lane & 7;
    int row = row0 + (mi & 1) * 8 + r;
#pragma unroll
    for (int j = 0; j < 8; j += 2) {
        uint32_t r0 = pack_bf16(d[4 * j + 0] * s0, d[4 * j + 1] * s0);
        uint32_t r1 = pack_bf16(d[4 * j + 2] * s1, d[4 * j + 3] * s1);
        uint32_t r2 = pack_bf16(d[4 * j + 4] * s0, d[4 * j + 5] * s0);
        uint32_t r3 = pack_bf16(d[4 * j + 6] * s1, d[4 * j + 7] * s1);
        int chunk = j + (mi >> 1);
        stmatrix_x4(base + row * 128 + ((chunk ^ (row & 7)) << 4), r0, r1, r2, r3);
    }
}
struct cf { float x, y; };
DEVI cf cmul(cf a, cf b) { cf r; r.x = fmaf(a.x, b.x, -a.y * b.y); r.y = fmaf(a.x, b.y, a.y * b.x); return r; }
DEVI cf csq(cf a) { cf r; r.x = fmaf(a.x, a.x, -a.y * a.y); r.y = (a.x + a.x) * a.y; return r; }
DEVI cf cexp_(float re, float im) {
    float m = __expf(re), s, c;
    __sincosf(im, &s, &c);
    cf r; r.x = m * c; r.y = m * s; return r;
}
DEVI uint32_t h2(cf v) { uint32_t r; asm("cvt.rn.f16x2.f32 %0, %1, %2;" : "=r"(r) : "f"(v.y), "f"(v.x)); return r; }
DEVI uint32_t h2c(cf v) { uint32_t r; asm("cvt.rn.f16x2.f32 %0, %1, %2;" : "=r"(r) : "f"(-v.y), "f"(v.x)); return r; }
DEVI void mma_group(float (*c)[4], const uint32_t (*a)[4], const uint32_t (*b)[2]) {
    asm volatile(
        "mma.sync.aligned.m16n8k16.row.col.f32.f16.f16.f32 {%0,%1,%2,%3}, {%20,%21,%22,%23}, {%40,%41}, {%0,%1,%2,%3};\n"
        "mma.sync.aligned.m16n8k16.row.col.f32.f16.f16.f32 {%4,%5,%6,%7}, {%24,%25,%26,%27}, {%40,%41}, {%4,%5,%6,%7};\n"
        "mma.sync.aligned.m16n8k16.row.col.f32.f16.f16.f32 {%8,%9,%10,%11}, {%28,%29,%30,%31}, {%42,%43}, {%8,%9,%10,%11};\n"
        "mma.sync.aligned.m16n8k16.row.col.f32.f16.f16.f32 {%12,%13,%14,%15}, {%32,%33,%34,%35}, {%44,%45}, {%12,%13,%14,%15};\n"
        "mma.sync.aligned.m16n8k16.row.col.f32.f16.f16.f32 {%16,%17,%18,%19}, {%36,%37,%38,%39}, {%46,%47}, {%16,%17,%18,%19};\n"
        : "+f"(c[0][0]), "+f"(c[0][1]), "+f"(c[0][2]), "+f"(c[0][3]), "+f"(c[1][0]), "+f"(c[1][1]), "+f"(c[1][2]), "+f"(c[1][3]),
          "+f"(c[2][0]), "+f"(c[2][1]), "+f"(c[2][2]), "+f"(c[2][3]), "+f"(c[3][0]), "+f"(c[3][1]), "+f"(c[3][2]), "+f"(c[3][3]),
          "+f"(c[4][0]), "+f"(c[4][1]), "+f"(c[4][2]), "+f"(c[4][3])
        : "r"(a[0][0]), "r"(a[0][1]), "r"(a[0][2]), "r"(a[0][3]), "r"(a[1][0]), "r"(a[1][1]), "r"(a[1][2]), "r"(a[1][3]),
          "r"(a[2][0]), "r"(a[2][1]), "r"(a[2][2]), "r"(a[2][3]), "r"(a[3][0]), "r"(a[3][1]), "r"(a[3][2]), "r"(a[3][3]),
          "r"(a[4][0]), "r"(a[4][1]), "r"(a[4][2]), "r"(a[4][3]),
          "r"(b[0][0]), "r"(b[0][1]), "r"(b[1][0]), "r"(b[1][1]), "r"(b[2][0]), "r"(b[2][1]), "r"(b[3][0]), "r"(b[3][1]));
}
DEVI float bf2f(bf16 v) { return __bfloat162float(v); }
DEVI float rbf(float v) { return __bfloat162float(__float2bfloat16_rn(v)); }

struct SsmParams { const bf16 *lar, *aim, *cre, *cim, *ldt, *dskip, *u; };

DEVI int kp_index(int l) {
    int p = (int)rbf((float)l);
    return p < 256 ? p : (p < 512 ? 128 + (p >> 1) : (p < 1024 ? 256 + (p >> 2) : 384 + (p >> 3)));
}

DEVI void reds(uint32_t a, float v) { asm volatile("red.shared.add.f32 [%0], %1;" ::"r"(a), "f"(v) : "memory"); }
DEVI uint32_t ldg16(const bf16* p) { uint16_t v; asm volatile("ld.global.nc.u16 %0, [%1];" : "=h"(v) : "l"(p)); return v; }
DEVI void ssm_kgen_load(const SsmParams& P, int d, int half, int lane, uint32_t* r) {
#pragma unroll
    for (int q = 0; q < 2; q++) {
        const int n = d * SSM_N + 64 * half + 32 * q + lane;
        r[4 * q] = ldg16(P.lar + n); r[4 * q + 1] = ldg16(P.aim + n); r[4 * q + 2] = ldg16(P.cre + n); r[4 * q + 3] = ldg16(P.cim + n);
    }
    r[8] = ldg16(P.ldt + d);
}
DEVI void ssm_kgen_warp(const uint32_t* r, int lane, uint32_t kp) {
    float raw[9];
#pragma unroll
    for (int i = 0; i < 9; i++) raw[i] = __uint_as_float(r[i] << 16);
    const int g = lane >> 2, t = lane & 3;
    float ar[2], ai[2], cr[2], ci[2], gr[2], gi[2];
    const float dt = rbf(expf(raw[8]));
#pragma unroll
    for (int q = 0; q < 2; q++) {
        ar[q] = -rbf(expf(raw[4 * q])) * dt;
        ai[q] = raw[4 * q + 1] * dt;
        cr[q] = 2.f * (raw[4 * q + 2] * dt);
        ci[q] = 2.f * (raw[4 * q + 3] * dt);
        float m = expf(ar[q] * 64.f), sn, cs;
        sincosf(ai[q] * 64.f, &sn, &cs);
        gr[q] = m * cs; gi[q] = m * sn;
    }
    float cm = 0.f;
#pragma unroll
    for (int q = 0; q < 2; q++) cm = fmaxf(cm, fmaxf(fabsf(cr[q]), fabsf(ci[q])));
#pragma unroll
    for (int o = 16; o; o >>= 1) cm = fmaxf(cm, __shfl_xor_sync(~0u, cm, o));
    const int ex = min(max((int)(__float_as_uint(cm) >> 23), 1), 253);
    const float cs_dn = __uint_as_float((uint32_t)(254 - ex) << 23), cs_up = __uint_as_float((uint32_t)ex << 23);
    float acc[5][4];
#pragma unroll
    for (int s = 0; s < 5; s++) { acc[s][0] = acc[s][1] = acc[s][2] = acc[s][3] = 0.f; }
    float klast = 0.f;
    const float gf = (float)g;
#pragma unroll
    for (int q = 0; q < 2; q++) {
#pragma unroll 1
        for (int g0 = 0; g0 < 8; g0 += 2) {
            uint32_t fa[5][4], fb[4][2];
#pragma unroll
            for (int h = 0; h < 2; h++) {
                const int src = ((g0 + h) << 2) | t;
                const float a_r = __shfl_sync(~0u, ar[q], src), a_i = __shfl_sync(~0u, ai[q], src);
                cf C, G;
                C.x = __shfl_sync(~0u, cr[q], src) * cs_dn; C.y = __shfl_sync(~0u, ci[q], src) * cs_dn;
                G.x = __shfl_sync(~0u, gr[q], src); G.y = __shfl_sync(~0u, gi[q], src);
                cf E = cexp_(a_r * gf, a_i * gf);
                cf B = csq(csq(csq(E)));
                fb[0][h] = h2c(cmul(C, B));
                cf EG = cmul(E, G);
                fa[0][2 * h] = h2(E); fa[0][2 * h + 1] = h2(EG);
                cf G2 = csq(G);
                cf X = cmul(E, G2), Xh = cmul(EG, G2);
                fa[1][2 * h] = h2(X); fa[1][2 * h + 1] = h2(Xh);
#pragma unroll
                for (int s = 2; s < 5; s++) {
                    B = csq(B); X = csq(X); Xh = csq(Xh);
                    fb[s - 1][h] = h2c(cmul(C, B));
                    fa[s][2 * h] = h2(X); fa[s][2 * h + 1] = h2(Xh);
                }
                X = csq(X);
                klast += fmaf(C.x, X.x, -C.y * X.y);
            }
            mma_group(acc, fa, fb);
        }
    }
    klast += __shfl_xor_sync(~0u, klast, 1);
    klast += __shfl_xor_sync(~0u, klast, 2);
#pragma unroll
    for (int s = 0; s < 5; s++) {
        const uint32_t b = kp + (128 * s + g + 16 * t) * 4;
        reds(b, acc[s][0] * cs_up); reds(b + 32, acc[s][1] * cs_up); reds(b + 256, acc[s][2] * cs_up); reds(b + 288, acc[s][3] * cs_up);
    }
    if (lane == 0) reds(kp + 2560, klast * cs_up);
}

constexpr int G1_THREADS = 384;
constexpr int G1_NS = 11;
constexpr int G1_SMEM = G1_NS * 16384 + 32768 + 256 + 1024;

__global__ void __cluster_dims__(2, 1, 1) __launch_bounds__(G1_THREADS, 1)
gemm_kv_kernel(const __grid_constant__ CUtensorMap tm_c, const __grid_constant__ CUtensorMap tm_wk,
               const __grid_constant__ CUtensorMap tm_wv, const __grid_constant__ CUtensorMap tm_kv_st,
               const bf16* __restrict__ px, const bf16* __restrict__ pwq) {
    extern __shared__ uint8_t smem_raw[];
    const uint32_t sb = (smem_u32(smem_raw) + 1023) & ~1023u;
    const uint32_t sC = sb + G1_NS * 16384, bars = sC + 32768;
    const uint32_t full = bars, empty = bars + 128;
    const int tid = threadIdx.x, warp = tid >> 5, lane = tid & 31, wg = tid >> 7;
    const uint32_t rank = cluster_rank();
    const int cl = blockIdx.x >> 1;
    const int m0 = ((cl & 7) * 2 + rank) * 128;
    const int ng = cl >> 3;
    STAMP(blockIdx.x == 10 && tid == 0, 0);
    if (tid == 0) {
        for (int i = 0; i < G1_NS; i++) { mbar_init(full + 8 * i, 1); mbar_init(empty + 8 * i, 16); }
        fence_barrier_init();
        for (int it = 0; it < 8; it++) {
            mbar_expect_tx(full + 8 * it, 16384);
            tma_load_2d(sb + it * 16384, &tm_c, it * 64, m0, full + 8 * it);
        }
    }
    __syncthreads();
    cluster_sync_all();
    pdl_launch();
    if (wg == 2) {
        reg_dec<40>();
        if (tid == 256) {
            const CUtensorMap* tw = ng < 4 ? &tm_wk : &tm_wv;
            const int n0 = (ng & 3) * 1024 + rank * 64;
            int st = 8; uint32_t ph = 1;
            for (int it = 0; it < 64; it++) {
                mbar_wait(empty + 8 * st, ph);
                mbar_expect_tx(full + 8 * st, 16384);
                tma_load_2d_mc(sb + st * 16384 + rank * 8192, tw, n0 + (it >> 3) * 128, (it & 7) * 64, full + 8 * st, 3);
                if (it < 2) {
                    for (int j = 3 + it * 8 + (cl & 7); j < 19; j += 16) tma_prefetch_2d(tw, n0 + (j >> 3) * 128, (j & 7) * 64);
                }
                if (it >= 3 && it + 16 < 64 && (it & 7) == (cl & 7)) tma_prefetch_2d(tw, n0 + ((it + 16) >> 3) * 128, (it & 7) * 64);
                if (it == 24) bulk_prefetch(px + blockIdx.x * 8192, 16384);
                if (it == 32) bulk_prefetch(pwq + blockIdx.x * 16384, 32768);
                if (++st == G1_NS) { st = 0; ph ^= 1; }
            }
        }
        __syncwarp();
    } else {
        reg_inc<232>();
        uint32_t af[128];
        float acc[64];
        const int wq = warp & 3;
        const int row = wg * 64 + wq * 16 + (lane & 15);
        const uint32_t stg = sC + wg * 16384;
        int st = 8, pst = 0; uint32_t ph = 0;
#pragma unroll
        for (int kc = 0; kc < 8; kc++) {
            mbar_wait(full + 8 * kc, 0);
#pragma unroll
            for (int k = 0; k < 4; k++) {
                const uint32_t a = sb + kc * 16384 + row * 128 + (((2 * k + (lane >> 4)) ^ (row & 7)) << 4);
                uint32_t* f = af + kc * 16 + k * 4;
                asm volatile("ldmatrix.sync.aligned.m8n8.x4.shared.b16 {%0,%1,%2,%3}, [%4];"
                             : "=r"(f[0]), "=r"(f[1]), "=r"(f[2]), "=r"(f[3]) : "r"(a) : "memory");
            }
            __syncwarp();
            if (lane < 2) mbar_arrive_cluster(empty + 8 * kc, lane);
        }
#pragma unroll 1
        for (int t = 0; t < 8; t++) {
            if (wg == 1 || t > 0) named_sync(3 + wg, 256);
#pragma unroll
            for (int kc = 0; kc < 8; kc++) {
                mbar_wait(full + 8 * st, ph);
                STAMP(blockIdx.x == 10 && (tid & 127) == 0, 1 + wg * 96 + t * 12 + kc);
                wg_fence();
                const uint64_t db = desc_mnmajor(sb + st * 16384, 8192);
#pragma unroll
                for (int k = 0; k < 4; k++) wgmma_rs128<1>(acc, af + kc * 16 + k * 4, db + k * 128, (kc | k) != 0);
                wg_commit();
                if (kc == 3 && (wg == 0 || t < 7)) named_arrive(3 + (wg ^ 1), 256);
                if (kc > 0) {
                    wg_wait<1>();
                    if (lane < 2) mbar_arrive_cluster(empty + 8 * pst, lane);
                }
                pst = st;
                if (++st == G1_NS) { st = 0; ph ^= 1; }
            }
            if ((tid & 127) == 0) bulk_wait_read<0>();
            named_sync(1 + wg, 128);
            wg_wait<0>();
            STAMP(blockIdx.x == 10 && (tid & 127) == 0, 9 + wg * 96 + t * 12);
            if (lane < 2) mbar_arrive_cluster(empty + 8 * pst, lane);
            store_slab64(stg, wq * 16, acc, 1.f, 1.f, lane);
            store_slab64(stg + 8192, wq * 16, acc + 32, 1.f, 1.f, lane);
            fence_proxy_async();
            named_sync(1 + wg, 128);
            if ((tid & 127) == 0) {
                tma_store_2d(&tm_kv_st, stg, ng * 1024 + t * 128, m0 + wg * 64);
                tma_store_2d(&tm_kv_st, stg + 8192, ng * 1024 + t * 128 + 64, m0 + wg * 64);
                bulk_commit();
            }
            STAMP(blockIdx.x == 10 && (tid & 127) == 0, 10 + wg * 96 + t * 12);
        }
        if ((tid & 127) == 0) bulk_wait<0>();
        __syncwarp();
    }
    asm volatile("barrier.cluster.arrive.relaxed.aligned;\nbarrier.cluster.wait.aligned;" ::: "memory");
}
constexpr int AT_NS = 6;
constexpr int AT_SMEM = AT_NS * 32768 + 32768 + 256 + 1024;
constexpr int AT_ITEMS = 512;

DEVI uint32_t hmax2(uint32_t a, uint32_t b) { uint32_t r; asm("max.bf16x2 %0, %1, %2;" : "=r"(r) : "r"(a), "r"(b)); return r; }
DEVI uint32_t hmul2(uint32_t a, uint32_t b) { uint32_t r; asm("mul.rn.bf16x2 %0, %1, %2;" : "=r"(r) : "r"(a), "r"(b)); return r; }
DEVI uint32_t hfma2(uint32_t a, uint32_t b, uint32_t c) { uint32_t r; asm("fma.rn.bf16x2 %0, %1, %2, %3;" : "=r"(r) : "r"(a), "r"(b), "r"(c)); return r; }
DEVI float blo(uint32_t v) { return __uint_as_float(v << 16); }
DEVI float bhi(uint32_t v) { return __uint_as_float(v & 0xffff0000u); }

template <bool FIRST>
DEVI void softmax_tile(float* s, float& m0, float& m1, float& l0, float& l1, float& al0, float& al1) {
    const uint32_t HI = 0x3DB53DB5u;
    const uint32_t LO = 0x371E371Eu;
    const float L2E = 1.4426950408889634f;
    uint32_t x0 = 0xFF80FF80u, x1 = 0xFF80FF80u;
#pragma unroll
    for (int j = 0; j < 16; j++) {
        uint32_t a = pack_bf16(s[4 * j], s[4 * j + 1]), b = pack_bf16(s[4 * j + 2], s[4 * j + 3]);
        a = hfma2(a, HI, hmul2(a, LO));
        b = hfma2(b, HI, hmul2(b, LO));
        s[4 * j] = __uint_as_float(a); s[4 * j + 2] = __uint_as_float(b);
        x0 = hmax2(x0, a); x1 = hmax2(x1, b);
    }
    uint32_t x = hmax2(__byte_perm(x0, x1, 0x5410), __byte_perm(x0, x1, 0x7632));
    x = hmax2(x, __shfl_xor_sync(~0u, x, 1));
    x = hmax2(x, __shfl_xor_sync(~0u, x, 2));
    float n0 = blo(x), n1 = bhi(x);
    if (!FIRST) {
        n0 = fmaxf(n0, m0); n1 = fmaxf(n1, m1);
        al0 = ex2((m0 - n0) * L2E); al1 = ex2((m1 - n1) * L2E);
    }
    m0 = n0; m1 = n1;
    const float c0 = -n0 * L2E, c1 = -n1 * L2E;
    float s0 = 0.f, s1 = 0.f;
#pragma unroll
    for (int j = 0; j < 16; j++) {
        uint32_t a = __float_as_uint(s[4 * j]), b = __float_as_uint(s[4 * j + 2]);
        float e0 = ex2(fmaf(blo(a), L2E, c0)), e1 = ex2(fmaf(bhi(a), L2E, c0));
        float e2 = ex2(fmaf(blo(b), L2E, c1)), e3 = ex2(fmaf(bhi(b), L2E, c1));
        s0 += e0 + e1; s1 += e2 + e3;
        s[4 * j] = e0; s[4 * j + 1] = e1; s[4 * j + 2] = e2; s[4 * j + 3] = e3;
    }
    if (FIRST) { l0 = s0; l1 = s1; }
    else { l0 = fmaf(l0, al0, s0); l1 = fmaf(l1, al1, s1); }
}

struct Ring {
    int st; uint32_t ph;
    DEVI void next() { if (++st == AT_NS) { st = 0; ph ^= 1; } }
};

__global__ void __launch_bounds__(384, 1)
attn_kernel(const __grid_constant__ CUtensorMap tm_x, const __grid_constant__ CUtensorMap tm_wq,
            const __grid_constant__ CUtensorMap tm_kv, const __grid_constant__ CUtensorMap tm_ctx_st,
            const SsmParams sp, const bf16* __restrict__ pwo) {
    extern __shared__ uint8_t smem_raw[];
    const uint32_t sb = (smem_u32(smem_raw) + 1023) & ~1023u;
    const uint32_t sO = sb + AT_NS * 32768, bars = sO + 32768;
    const uint32_t full = bars, empty = bars + 64;
    volatile int* slots = reinterpret_cast<volatile int*>(smem_raw + (bars + 128 - smem_u32(smem_raw)));
    const int tid = threadIdx.x, warp = tid >> 5, lane = tid & 31, wg = tid >> 7;
    if (tid == 0) {
        for (int i = 0; i < AT_NS; i++) { mbar_init(full + 8 * i, 1); mbar_init(empty + 8 * i, 8); }
        fence_barrier_init();
    }
    __syncthreads();
    if (wg == 2) {
        reg_dec<24>();
        if (warp == 8 && lane == 0) {
            Ring r{0, 1};
            int n = 0;
            while (true) {
                int idx = (int)atomicInc(&g_sched, AT_ITEMS + gridDim.x - 1);
                if (idx >= AT_ITEMS - 128 && idx < AT_ITEMS) {
                    bulk_prefetch(sp.u + (idx - (AT_ITEMS - 128)) * 8192, 16384);
                    const int po = (idx - (AT_ITEMS - 128)) * 512;
                    bulk_prefetch(sp.lar + po, 1024); bulk_prefetch(sp.aim + po, 1024);
                    bulk_prefetch(sp.cre + po, 1024); bulk_prefetch(sp.cim + po, 1024);
                    if (po == 0) { bulk_prefetch(sp.ldt, 1024); bulk_prefetch(sp.dskip, 1024); }
                    bulk_prefetch(pwo + (idx - (AT_ITEMS - 128)) * 16384, 32768);
                }
                mbar_wait(empty + 8 * r.st, r.ph);
                if (idx >= AT_ITEMS) {
                    slots[n & 3] = -1;
                    mbar_arrive(full + 8 * r.st);
                    break;
                }
                slots[n & 3] = idx;
                const int qi = 15 - (idx >> 5), h = idx & 31;
                for (int kc = 0; kc < 8; kc++) {
                    if (kc) mbar_wait(empty + 8 * r.st, r.ph);
                    const uint32_t fb = full + 8 * r.st, dst = sb + r.st * 32768;
                    mbar_expect_tx(fb, 32768);
                    tma_load_2d(dst, &tm_x, kc * 64, qi * 128, fb);
                    tma_load_2d(dst + 16384, &tm_wq, h * 128, kc * 64, fb);
                    tma_load_2d(dst + 24576, &tm_wq, h * 128 + 64, kc * 64, fb);
                    r.next();
                }
                if (n == 0) { pdl_wait(); pdl_launch(); }
                for (int j = qi; j >= -1; j--) {
#pragma unroll
                    for (int v = 0; v < 2; v++) {
                        const int jj = j + v;
                        if (jj < 0 || jj > qi || (v == 0 && j < 0)) continue;
                        mbar_wait(empty + 8 * r.st, r.ph);
                        const uint32_t fb = full + 8 * r.st, dst = sb + r.st * 32768;
                        mbar_expect_tx(fb, 32768);
                        tma_load_2d(dst, &tm_kv, v * HDALL + h * 128, jj * 128, fb);
                        tma_load_2d(dst + 16384, &tm_kv, v * HDALL + h * 128 + 64, jj * 128, fb);
                        r.next();
                    }
                }
                n++;
            }
            if (n == 0) { pdl_wait(); pdl_launch(); }
        }
    } else {
        reg_inc<240>();
        Ring r{0, 0};
        float o[64], s[64];
        uint32_t qf[32], pa[32];
        const int g = lane >> 2, t = lane & 3, wq = warp & 3;
        const uint32_t stg = sO + wg * 16384;
        if (wg == 1) named_arrive(3, 256);
        for (int n = 0;; n++) {
            mbar_wait(full + 8 * r.st, r.ph);
            const int idx = slots[n & 3];
            if (idx < 0) break;
            const int qi = 15 - (idx >> 5), h = idx & 31;
#pragma unroll 1
            for (int kc = 0; kc < 8; kc++) {
                if (kc) mbar_wait(full + 8 * r.st, r.ph);
                wg_fence();
                const uint32_t base = sb + r.st * 32768;
                const uint64_t da = desc_kmajor(base + wg * 8192), db = desc_mnmajor(base + 16384, 8192);
#pragma unroll
                for (int k = 0; k < 4; k++) wgmma_ss128<1>(s, da + k * 2, db + k * 128, (kc | k) != 0);
                wg_commit();
                if (kc) {
                    wg_wait<1>();
                    if (lane == 0) mbar_arrive(empty + 8 * (r.st == 0 ? AT_NS - 1 : r.st - 1));
                }
                r.next();
            }
            wg_wait<0>();
            if (lane == 0) mbar_arrive(empty + 8 * (r.st == 0 ? AT_NS - 1 : r.st - 1));
#pragma unroll
            for (int i = 0; i < 32; i++) qf[i] = pack_bf16(s[2 * i], s[2 * i + 1]);
            float m0, m1, l0, l1, al0, al1;
            auto issue_qk = [&]() {
                mbar_wait(full + 8 * r.st, r.ph);
                wg_fence();
                const uint64_t db = desc_kmajor(sb + r.st * 32768);
#pragma unroll
                for (int k = 0; k < 8; k++) wgmma_rs128<0>(s, qf + 4 * k, db + (k >> 2) * 1024 + (k & 3) * 2, k != 0);
                wg_commit();
            };
            auto issue_pv = [&](const uint32_t* p, int st, uint32_t ph, int acc) {
                mbar_wait(full + 8 * st, ph);
                wg_fence();
                const uint64_t db = desc_mnmajor(sb + st * 32768, 16384);
#pragma unroll
                for (int k = 0; k < 8; k++) wgmma_rs128<1>(o, p + 4 * k, db + k * 128, acc | k);
                wg_commit();
            };
            issue_qk();
            wg_wait<0>();
            if (lane == 0) mbar_arrive(empty + 8 * r.st);
            r.next();
            {
                const int row = wg * 64 + wq * 16 + g;
#pragma unroll
                for (int j = 0; j < 16; j++) {
                    const int c = 8 * j + 2 * t;
                    if (c > row) s[4 * j] = -INFINITY;
                    if (c + 1 > row) s[4 * j + 1] = -INFINITY;
                    if (c > row + 8) s[4 * j + 2] = -INFINITY;
                    if (c + 1 > row + 8) s[4 * j + 3] = -INFINITY;
                }
            }
            softmax_tile<true>(s, m0, m1, l0, l1, al0, al1);
#pragma unroll
            for (int i = 0; i < 32; i++) pa[i] = pack_bf16(s[2 * i], s[2 * i + 1]);
            int first = 0;
#pragma unroll 1
            for (int j = qi; j >= 1; j--) {
                named_sync(3 + wg, 256);
                issue_qk();
                const int kst = r.st;
                r.next();
                issue_pv(pa, r.st, r.ph, first);
                named_arrive(3 + (wg ^ 1), 256);
                wg_wait<1>();
                if (lane == 0) mbar_arrive(empty + 8 * kst);
                softmax_tile<false>(s, m0, m1, l0, l1, al0, al1);
                wg_wait<0>();
                if (lane == 0) mbar_arrive(empty + 8 * r.st);
                r.next();
#pragma unroll
                for (int i = 0; i < 32; i++) pa[i] = pack_bf16(s[2 * i], s[2 * i + 1]);
#pragma unroll
                for (int i = 0; i < 16; i++) {
                    o[4 * i] *= al0; o[4 * i + 1] *= al0; o[4 * i + 2] *= al1; o[4 * i + 3] *= al1;
                }
                first = 1;
            }
            issue_pv(pa, r.st, r.ph, first);
            l0 += __shfl_xor_sync(~0u, l0, 1); l0 += __shfl_xor_sync(~0u, l0, 2);
            l1 += __shfl_xor_sync(~0u, l1, 1); l1 += __shfl_xor_sync(~0u, l1, 2);
            const float i0 = 1.f / l0, i1 = 1.f / l1;
            if ((tid & 127) == 0) bulk_wait_read<0>();
            named_sync(1 + wg, 128);
            wg_wait<0>();
            if (lane == 0) mbar_arrive(empty + 8 * r.st);
            r.next();
            store_slab64(stg, wq * 16, o, i0, i1, lane);
            store_slab64(stg + 8192, wq * 16, o + 32, i0, i1, lane);
            fence_proxy_async();
            named_sync(1 + wg, 128);
            if ((tid & 127) == 0) {
                tma_store_2d(&tm_ctx_st, stg, h * 128, qi * 128 + wg * 64);
                tma_store_2d(&tm_ctx_st, stg + 8192, h * 128 + 64, qi * 128 + wg * 64);
                bulk_commit();
            }
        }
        if ((tid & 127) == 0) bulk_wait<0>();
    }
}
constexpr int OP_NS = 4;
constexpr int OP_ULD = 164 * 16;
constexpr int OP_UCH = 2 * OP_ULD;
constexpr int OP_SMEM = OP_NS * 32768 + 32768 + 4 * WTAB * 4 + 4 * OP_UCH + 4 * 648 * 4 + 256 + 1024;

template <int N> DEVI void wgmma_conv(float* d, const uint32_t* a, uint64_t db);
template <> DEVI void wgmma_conv<128>(float* d, const uint32_t* a, uint64_t db) {
    asm volatile("wgmma.mma_async.sync.aligned.m64n128k16.f32.bf16.bf16 {%0,%1,%2,%3,%4,%5,%6,%7,%8,%9,%10,%11,%12,%13,%14,%15,%16,%17,%18,%19,%20,%21,%22,%23,%24,%25,%26,%27,%28,%29,%30,%31,%32,%33,%34,%35,%36,%37,%38,%39,%40,%41,%42,%43,%44,%45,%46,%47,%48,%49,%50,%51,%52,%53,%54,%55,%56,%57,%58,%59,%60,%61,%62,%63}, "
                 "{%64,%65,%66,%67}, %68, 1, 1, 1, 0;"
                 : ACC8(d, 0), ACC8(d, 8), ACC8(d, 16), ACC8(d, 24), ACC8(d, 32), ACC8(d, 40), ACC8(d, 48), ACC8(d, 56) : "r"(a[0]), "r"(a[1]), "r"(a[2]), "r"(a[3]), "l"(db));
}
template <> DEVI void wgmma_conv<96>(float* d, const uint32_t* a, uint64_t db) {
    asm volatile("wgmma.mma_async.sync.aligned.m64n96k16.f32.bf16.bf16 {%0,%1,%2,%3,%4,%5,%6,%7,%8,%9,%10,%11,%12,%13,%14,%15,%16,%17,%18,%19,%20,%21,%22,%23,%24,%25,%26,%27,%28,%29,%30,%31,%32,%33,%34,%35,%36,%37,%38,%39,%40,%41,%42,%43,%44,%45,%46,%47}, "
                 "{%48,%49,%50,%51}, %52, 1, 1, 1, 0;"
                 : ACC8(d, 0), ACC8(d, 8), ACC8(d, 16), ACC8(d, 24), ACC8(d, 32), ACC8(d, 40) : "r"(a[0]), "r"(a[1]), "r"(a[2]), "r"(a[3]), "l"(db));
}
template <> DEVI void wgmma_conv<64>(float* d, const uint32_t* a, uint64_t db) {
    asm volatile("wgmma.mma_async.sync.aligned.m64n64k16.f32.bf16.bf16 {%0,%1,%2,%3,%4,%5,%6,%7,%8,%9,%10,%11,%12,%13,%14,%15,%16,%17,%18,%19,%20,%21,%22,%23,%24,%25,%26,%27,%28,%29,%30,%31}, "
                 "{%32,%33,%34,%35}, %36, 1, 1, 1, 0;"
                 : ACC8(d, 0), ACC8(d, 8), ACC8(d, 16), ACC8(d, 24) : "r"(a[0]), "r"(a[1]), "r"(a[2]), "r"(a[3]), "l"(db));
}
template <> DEVI void wgmma_conv<32>(float* d, const uint32_t* a, uint64_t db) {
    asm volatile("wgmma.mma_async.sync.aligned.m64n32k16.f32.bf16.bf16 {%0,%1,%2,%3,%4,%5,%6,%7,%8,%9,%10,%11,%12,%13,%14,%15}, "
                 "{%16,%17,%18,%19}, %20, 1, 1, 1, 0;"
                 : ACC8(d, 0), ACC8(d, 8) : "r"(a[0]), "r"(a[1]), "r"(a[2]), "r"(a[3]), "l"(db));
}
DEVI uint32_t lds32(uint32_t a) { uint32_t v; asm volatile("ld.shared.b32 %0, [%1];" : "=r"(v) : "r"(a)); return v; }
DEVI uint32_t lds16(uint32_t a) { uint16_t v; asm volatile("ld.shared.b16 %0, [%1];" : "=h"(v) : "r"(a)); return v; }

DEVI void sts32(uint32_t a, float v) { asm volatile("st.shared.f32 [%0], %1;" ::"r"(a), "f"(v) : "memory"); }
template <int J> DEVI void conv_half(float* acc, uint32_t* f, uint32_t wa, uint64_t du) {
#pragma unroll
    for (int i = 0; i < 4; i++) {
        const uint32_t w = wa + (4 * J + i) * 256;
        f[4 * i] = lds32(w); f[4 * i + 1] = lds32(w + 32); f[4 * i + 2] = lds32(w - 32); f[4 * i + 3] = lds32(w);
    }
    wg_fence();
#pragma unroll
    for (int i = 0; i < 4; i++) wgmma_conv<128 - 32 * (J / 2)>(acc, f + 4 * i, du + (uint64_t)(4 * (4 * J + i)));
    wg_commit();
}
template <int J> DEVI void conv_group(float* acc, uint32_t* fa, uint32_t* fb, uint32_t wa, uint64_t du) {
    conv_half<2 * J>(acc, fa, wa, du);
    if (J) wg_wait<1>();
    conv_half<2 * J + 1>(acc, fb, wa, du);
    if (J < 3) wg_wait<1>();
}
DEVI uint32_t ypos(int a, int b) { return (uint32_t)(b * 128 + (a ^ ((b & 3) << 3))) * 4; }

DEVI void expand_table(int ct, uint32_t sW, uint32_t sK) {
#pragma unroll 1
    for (int i = ct; i < WTAB; i += 384) {
        const int c = (i >> 3) & 3, qd = (i & 7) | ((i >> 5) << 3);
        float k[5];
#pragma unroll
        for (int e = 0; e < 5; e++) {
            const int l = qd * 4 - 65 + e;
            const int hi = (int)__bfloat16_as_ushort(__float2bfloat16_rn((float)l)) - 17024;
            k[e] = __uint_as_float(lds32(sK + (c * 648 + (l < 0 ? 644 : (l < 128 ? l : hi))) * 4));
        }
        asm volatile("st.shared.v4.b32 [%0], {%1,%2,%3,%4};" ::"r"(sW + (c * WTAB + qd * 4) * 4), "r"(pack_bf16(k[1], k[0])),
                     "r"(pack_bf16(k[2], k[1])), "r"(pack_bf16(k[3], k[2])), "r"(pack_bf16(k[4], k[3])) : "memory");
    }
}

__global__ void __cluster_dims__(2, 1, 1) __launch_bounds__(512, 1)
outproj_kernel(const __grid_constant__ CUtensorMap tm_ctx, const __grid_constant__ CUtensorMap tm_wo,
               const __grid_constant__ CUtensorMap tm_out, const __grid_constant__ CUtensorMap tm_u, SsmParams sp, bf16* __restrict__ out) {
    extern __shared__ uint8_t smem_raw[];
    const uint32_t sb = (smem_u32(smem_raw) + 1023) & ~1023u;
    const uint32_t sX = sb + OP_NS * 32768, sW = sX + 32768, sU = sW + 4 * WTAB * 4, sK = sU + 4 * OP_UCH, bars = sK + 4 * 648 * 4;
    const uint32_t full = bars, empty = bars + 64, xfull = bars + 128, wfull = bars + 136, xfree = bars + 144;
    const int tid = threadIdx.x, warp = tid >> 5, lane = tid & 31, wg = tid >> 7;
    const uint32_t rank = cluster_rank();
    const uint32_t kr = rank;
    const int cl = blockIdx.x >> 1;
    const int m0 = (cl >> 2) * 128, n0 = (cl & 3) * 128, k0 = kr * 2048;
    STAMP(blockIdx.x == 10 && tid == 0, 1000);
    uint32_t praw[9];
    ssm_kgen_load(sp, blockIdx.x * 4 + (warp & 3), wg & 1, lane, praw);
    if (tid == 0) {
        for (int i = 0; i < OP_NS; i++) { mbar_init(full + 8 * i, 1); mbar_init(empty + 8 * i, 8); }
        mbar_init(xfull, 1);
        mbar_init(wfull, 1);
        mbar_init(xfree, 1);
        fence_barrier_init();
        mbar_expect_tx(wfull, 32768);
        for (int i = 0; i < 8; i++) tma_load_2d(sX + i * 4096, &tm_u, cl * 8, i * 256, wfull);
    }
    for (int i = tid; i < 648; i += 512) asm volatile("st.shared.v4.b32 [%0], {%1,%1,%1,%1};" ::"r"(sK + i * 16), "r"(0) : "memory");
    __syncthreads();
    cluster_arrive();
    if (wg == 3) {
        reg_dec<40>();
        cluster_wait();
        if (tid == 384) {
            mbar_expect_tx(xfull, 32768);
            for (int it = 0; it < OP_NS; it++) {
                const uint32_t dst = sb + it * 32768, fb = full + 8 * it;
                mbar_expect_tx(fb, 32768);
                tma_load_2d(dst + 16384, &tm_wo, n0, k0 + it * 64, fb);
                tma_load_2d(dst + 24576, &tm_wo, n0 + 64, k0 + it * 64, fb);
            }
            pdl_wait();
            STAMP(blockIdx.x == 10, 1005);
            for (int it = 0; it < 32; it++) {
                const int st = it & (OP_NS - 1);
                const uint32_t dst = sb + st * 32768, fb = full + 8 * st;
                if (it >= OP_NS) {
                    mbar_wait(empty + 8 * st, ((it / OP_NS) & 1) ^ 1);
                    mbar_expect_tx(fb, 32768);
                    tma_load_2d(dst + 16384, &tm_wo, n0, k0 + it * 64, fb);
                    tma_load_2d(dst + 24576, &tm_wo, n0 + 64, k0 + it * 64, fb);
                }
                tma_load_2d(dst, &tm_ctx, k0 + it * 64, m0, fb);
                tma_load_2d(dst + 8192, &tm_ctx, k0 + it * 64, m0 + 64, fb);
            }
        }
        __syncwarp();
    } else {
      const int ct = tid & 127, wq = warp & 3;
      if (wg == 2) {
        for (int i = ct; i < 8 * 32; i += 128) {
            const uint32_t a = sU + (i >> 5) * OP_ULD + (128 + (i & 31)) * 16;
            asm volatile("st.shared.v4.b32 [%0], {%1,%1,%1,%1};" ::"r"(a), "r"(0) : "memory");
        }
        const bool mine = ((lane >> 2) & 1) == (int)rank;
        const uint32_t ub = sU + (lane & 3) * OP_UCH + ((lane >> 3) & 1) * OP_ULD + (127 - 2 * wq - (lane >> 4)) * 16;
        mbar_wait(wfull, 0);
#pragma unroll 4
        for (int i = 0; i < 16; i++) {
            uint32_t r0, r1, r2, r3;
            asm volatile("ldmatrix.sync.aligned.m8n8.x4.trans.shared.b16 {%0,%1,%2,%3}, [%4];"
                         : "=r"(r0), "=r"(r1), "=r"(r2), "=r"(r3) : "r"(sX + (i * 128 + ct) * 16) : "memory");
            asm volatile("stmatrix.sync.aligned.m8n8.x4.shared.b16 [%0], {%1,%2,%3,%4};"
                         ::"r"(mine ? ub - i * 128 : sW + lane * 16), "r"(r0), "r"(r1), "r"(r2), "r"(r3) : "memory");
        }
        fence_proxy_async();
        STAMP(blockIdx.x == 10 && ct == 0, 1001);
      } else {
        ssm_kgen_warp(praw, lane, sK + wq * 648 * 4);
      }
      cluster_wait();
      named_sync(3, 384);
      if (tid == 256) mbar_arrive_cluster(xfree, rank ^ 1);
      STAMP(blockIdx.x == 10 && tid == 257, 1002);
      expand_table(tid, sW, sK);
      if (wg == 2) {
        reg_inc<216>();
        const int g = lane >> 2, t = lane & 3;
        const int d0 = blockIdx.x * 4;
        const uint2 dsk = __ldg(reinterpret_cast<const uint2*>(sp.dskip + d0));
        named_sync(4, 384);
        uint32_t res[16][2];
        STAMP(blockIdx.x == 10 && ct == 0, 1003);
#pragma unroll 1
        for (int c = 0; c < 4; c++) {
            float acc[64];
            uint32_t fa[16], fb[16];
#pragma unroll
            for (int i = 0; i < 64; i++) acc[i] = 0.f;
            const uint32_t wa = sW + (c * WTAB + 64 + 16 * wq + g - 2 * t) * 4;
            const uint64_t du = make_desc(sU + c * OP_UCH, OP_ULD, 128, 0);
            conv_group<0>(acc, fa, fb, wa, du);
            conv_group<1>(acc, fa, fb, wa, du);
            conv_group<2>(acc, fa, fb, wa, du);
            conv_group<3>(acc, fa, fb, wa, du);
            named_sync(5, 128);
            wg_wait<0>();
            const uint32_t yb = (wq & 1) ? sW + c * WTAB * 4 : sK;
            const bool skip0 = wq >= 2 && t == 0;
            if (wq >= 2) {
                named_sync(6, 128);
#pragma unroll
                for (int hf = 0; hf < 2; hf++) {
                    float2 v[16];
#pragma unroll
                    for (int i = 0; i < 16; i++)
                        asm volatile("ld.shared.v2.f32 {%0,%1}, [%2];" : "=f"(v[i].x), "=f"(v[i].y)
                                     : "r"(yb + ypos((128 - 8 * (8 * hf + (i >> 1)) - 2 * t) & 127, g + 8 * (i & 1))));
#pragma unroll
                    for (int i = 0; i < 16; i++) { acc[32 * hf + 2 * i] += v[i].y; acc[32 * hf + 2 * i + 1] += v[i].x; }
                }
            }
#pragma unroll
            for (int i = 0; i < 32; i++) {
                const uint32_t p = yb + ypos(126 - 8 * (i >> 1) - 2 * t + (wq & 2), g + 8 * (i & 1));
                if (i >= 2 || !skip0) asm volatile("st.shared.v2.f32 [%0], {%1,%2};" ::"r"(p), "f"(acc[2 * i + 1]), "f"(acc[2 * i]) : "memory");
            }
            if (wq < 2) named_arrive(6, 128);
            named_sync(5, 128);
            const uint32_t dw = (c & 2) ? dsk.y : dsk.x;
            const float D = (c & 1) ? bhi(dw) : blo(dw);
            const int yb2 = (lane >> 3) + 4 * wq;
#pragma unroll
            for (int i = 0; i < 16; i++) {
                const int a = 8 * i + (lane & 7);
                float y = __uint_as_float(lds32(sW + c * WTAB * 4 + ypos((a - 1) & 127, yb2)));
                y = __uint_as_float(lds32(sK + ypos(a, yb2))) + (a == 0 ? 0.f : y);
                const float u = __uint_as_float(lds16(sU + c * OP_UCH + (wq >> 1) * OP_ULD + (127 - a) * 16 + (yb2 & 7) * 2) << 16);
                const uint32_t o = __bfloat16_as_ushort(__float2bfloat16_rn(rbf(y) + rbf(u * D)));
                res[i][0] = __byte_perm(res[i][0], res[i][1], 0x5432); res[i][1] = __byte_perm(res[i][1], o, 0x5432);
            }
        }
        STAMP(blockIdx.x == 10 && ct == 0, 1004);
        const int grp = blockIdx.x >> 2, me = blockIdx.x & 3;
#pragma unroll
        for (int i = 0; i < 8; i++)
            __stcg(g_y + (((grp * 4 + (i >> 1)) * 4 + me) * 2 + (i & 1)) * 128 + ct,
                   make_uint4(res[2 * i][0], res[2 * i][1], res[2 * i + 1][0], res[2 * i + 1][1]));
        named_sync(5, 128);
        if (ct == 0) {
            __threadfence();
            const unsigned int target = (atomicAdd(g_ycnt + grp, 1u) & ~3u) + 4u;
            uint32_t t0, t1, v;
            asm volatile("mov.u32 %0, %%globaltimer_lo;" : "=r"(t0));
            do {
                asm volatile("ld.acquire.gpu.global.u32 %0, [%1];" : "=r"(v) : "l"(g_ycnt + grp) : "memory");
                asm volatile("mov.u32 %0, %%globaltimer_lo;" : "=r"(t1));
            } while ((int)(v - target) < 0 && t1 - t0 < 4000000u);
        }
        named_sync(5, 128);
        uint4 y[8];
#pragma unroll
        for (int i = 0; i < 8; i++)
            y[i] = __ldcg(g_y + ((blockIdx.x * 4 + 2 * (t & 1) + ((i >> 1) & 1)) * 2 + (i & 1)) * 128 + (ct & ~1) + (i >> 2));
#pragma unroll
        for (int i = 0; i < 8; i++) {
            const int row = 128 * (4 * me + (i & 3)) + 16 * ((lane & 6) + (i >> 2)) + 4 * wq + (lane >> 3);
            const uint4 p = y[(i & 4) + ((i >> 1) & 1)], q = y[(i & 4) + 2 + ((i >> 1) & 1)];
            *reinterpret_cast<uint4*>(out + (size_t)row * 1024 + 512 + grp * 16 + (t & 1) * 8) =
                (i & 1) ? make_uint4(p.z, p.w, q.z, q.w) : make_uint4(p.x, p.y, q.x, q.y);
        }
      } else {
        named_arrive(4, 384);
        float acc[64];
#pragma unroll 1
        for (int it = 0; it < 32; it++) {
            const int st = it & (OP_NS - 1);
            mbar_wait(full + 8 * st, (it / OP_NS) & 1);
            STAMP(blockIdx.x == 10 && tid == 0, 1009 + it);
            wg_fence();
            const uint32_t base = sb + st * 32768;
            const uint64_t da = desc_kmajor(base + wg * 8192), db = desc_mnmajor(base + 16384, 8192);
#pragma unroll
            for (int k = 0; k < 4; k++) wgmma_ss128<1>(acc, da + k * 2, db + k * 128, (it | k) != 0);
            wg_commit();
            if (it > 0 && it + OP_NS - 1 < 32) {
                wg_wait<1>();
                if (lane == 0) mbar_arrive(empty + 8 * ((it - 1) & (OP_NS - 1)));
            }
        }
        wg_wait<0>();
        mbar_wait(xfree, 0);
        uint32_t peer, pbar;
        asm volatile("mapa.shared::cluster.u32 %0, %1, %2;" : "=r"(peer) : "r"(sX + tid * 16), "r"(rank ^ 1));
        asm volatile("mapa.shared::cluster.u32 %0, %1, %2;" : "=r"(pbar) : "r"(xfull), "r"(rank ^ 1));
#pragma unroll
        for (int i = 0; i < 8; i++) {
            const float* s = acc + 4 * i;
            const float a = kr ? s[0] : s[32], b = kr ? s[1] : s[33], c = kr ? s[2] : s[34], d = kr ? s[3] : s[35];
            asm volatile("st.async.weak.shared::cluster.mbarrier::complete_tx::bytes.v4.f32 [%0], {%1,%2,%3,%4}, [%5];"
                         ::"r"(peer + i * 4096), "f"(a), "f"(b), "f"(c), "f"(d), "r"(pbar) : "memory");
        }
        STAMP(blockIdx.x == 10 && tid == 0, 1006);
        mbar_wait(xfull, 0);
        STAMP(blockIdx.x == 10 && tid == 0, 1007);
        float r[32];
#pragma unroll
        for (int i = 0; i < 8; i++) {
            float a, b, c, d;
            asm volatile("ld.shared.v4.f32 {%0,%1,%2,%3}, [%4];" : "=f"(a), "=f"(b), "=f"(c), "=f"(d) : "r"(sX + tid * 16 + i * 4096));
            const float* s = acc + 4 * i;
            r[4 * i] = a + (kr ? s[32] : s[0]); r[4 * i + 1] = b + (kr ? s[33] : s[1]);
            r[4 * i + 2] = c + (kr ? s[34] : s[2]); r[4 * i + 3] = d + (kr ? s[35] : s[3]);
        }
        const uint32_t stg = sb + wg * 8192;
        store_slab64(stg, (warp & 3) * 16, r, 1.f, 1.f, lane);
        fence_proxy_async();
        named_sync(1 + wg, 128);
        if ((tid & 127) == 0) {
            tma_store_2d(&tm_out, stg, n0 + kr * 64, m0 + wg * 64);
            bulk_commit();
            bulk_wait<0>();
            STAMP(blockIdx.x == 10 && tid == 0, 1008);
        }
      }
    }
}

typedef CUresult (*EncodeFn)(CUtensorMap*, CUtensorMapDataType, cuuint32_t, void*, const cuuint64_t*, const cuuint64_t*,
                             const cuuint32_t*, const cuuint32_t*, CUtensorMapInterleave, CUtensorMapSwizzle,
                             CUtensorMapL2promotion, CUtensorMapFloatOOBfill);

static void make_map(EncodeFn fn, CUtensorMap* m, const void* p, uint64_t cols, uint64_t rows, uint32_t box_rows) {
    cuuint64_t dims[2] = {cols, rows};
    cuuint64_t strides[1] = {cols * 2};
    cuuint32_t box[2] = {64, box_rows};
    cuuint32_t es[2] = {1, 1};
    fn(m, CU_TENSOR_MAP_DATA_TYPE_BFLOAT16, 2, const_cast<void*>(p), dims, strides, box, es, CU_TENSOR_MAP_INTERLEAVE_NONE,
       CU_TENSOR_MAP_SWIZZLE_128B, CU_TENSOR_MAP_L2_PROMOTION_L2_256B, CU_TENSOR_MAP_FLOAT_OOB_FILL_NONE);
}

extern "C" void kernel_launch(void* const* d_in, const int* in_sizes, int n_in, void* d_out, int out_size) {
    void* fp = nullptr;
    cudaDriverEntryPointQueryResult qr;
    cudaGetDriverEntryPoint("cuTensorMapEncodeTiled", &fp, cudaEnableDefault, &qr);
    EncodeFn fn = (EncodeFn)fp;
    void *p_kv, *p_ctx;
    cudaGetSymbolAddress(&p_kv, g_kv);
    cudaGetSymbolAddress(&p_ctx, g_ctx);
    CUtensorMap tm_kv_st, tm_x, tm_c, tm_wq, tm_wk, tm_wv, tm_wo, tm_kv, tm_ctx, tm_out;
    make_map(fn, &tm_x, d_in[0], DM, SEQ, 128);
    make_map(fn, &tm_c, d_in[1], DM, SEQ, 128);
    make_map(fn, &tm_wq, d_in[2], HDALL, DM, 64);
    make_map(fn, &tm_wk, d_in[3], HDALL, DM, 64);
    make_map(fn, &tm_wv, d_in[4], HDALL, DM, 64);
    make_map(fn, &tm_wo, d_in[5], DM, HDALL, 64);
    make_map(fn, &tm_kv, p_kv, 2 * HDALL, SEQ, 128);
    make_map(fn, &tm_kv_st, p_kv, 2 * HDALL, SEQ, 64);
    make_map(fn, &tm_ctx, p_ctx, HDALL, SEQ, 64);
    make_map(fn, &tm_out, d_out, 1024, SEQ, 64);
    CUtensorMap tm_u;
    {
        cuuint64_t dims[2] = {512, 2048}, strides[1] = {1024};
        cuuint32_t box[2] = {8, 256}, es[2] = {1, 1};
        fn(&tm_u, CU_TENSOR_MAP_DATA_TYPE_BFLOAT16, 2, d_in[6], dims, strides, box, es, CU_TENSOR_MAP_INTERLEAVE_NONE,
           CU_TENSOR_MAP_SWIZZLE_NONE, CU_TENSOR_MAP_L2_PROMOTION_NONE, CU_TENSOR_MAP_FLOAT_OOB_FILL_NONE);
    }
    SsmParams sp;
    sp.u = (const bf16*)d_in[6]; sp.lar = (const bf16*)d_in[7]; sp.aim = (const bf16*)d_in[8];
    sp.cre = (const bf16*)d_in[9]; sp.cim = (const bf16*)d_in[10]; sp.ldt = (const bf16*)d_in[11]; sp.dskip = (const bf16*)d_in[12];
    cudaFuncSetAttribute(gemm_kv_kernel, cudaFuncAttributeMaxDynamicSharedMemorySize, G1_SMEM);
    cudaFuncSetAttribute(attn_kernel, cudaFuncAttributeMaxDynamicSharedMemorySize, AT_SMEM);
    cudaFuncSetAttribute(outproj_kernel, cudaFuncAttributeMaxDynamicSharedMemorySize, OP_SMEM);
    cudaStream_t st = cudaStreamPerThread;
    gemm_kv_kernel<<<128, G1_THREADS, G1_SMEM, st>>>(tm_c, tm_wk, tm_wv, tm_kv_st, (const bf16*)d_in[0], (const bf16*)d_in[2]);
    cudaLaunchAttribute at[1];
    at[0].id = cudaLaunchAttributeProgrammaticStreamSerialization;
    at[0].val.programmaticStreamSerializationAllowed = 1;
    cudaLaunchConfig_t cfg = {};
    cfg.stream = st; cfg.attrs = at; cfg.numAttrs = 1;
    cfg.gridDim = dim3(132); cfg.blockDim = dim3(384); cfg.dynamicSmemBytes = AT_SMEM;
    cudaLaunchKernelEx(&cfg, attn_kernel, tm_x, tm_wq, tm_kv, tm_ctx, sp, (const bf16*)d_in[5]);
    cfg.gridDim = dim3(128); cfg.blockDim = dim3(512); cfg.dynamicSmemBytes = OP_SMEM;
    cudaLaunchKernelEx(&cfg, outproj_kernel, tm_ctx, tm_wo, tm_out, tm_u, sp, (bf16*)d_out);
}
```

```cpp
#include <cuda_runtime.h>
#include <cuda_bf16.h>
#include <cuda.h>
#include <stdint.h>

typedef __nv_bfloat16 bf16;

#define DEVI __device__ __forceinline__

constexpr int SEQ = 2048, DM = 512, NH = 32, HD = 128, HDALL = NH * HD;
constexpr int SSM_D = 512, SSM_N = 128;
constexpr int WTAB = 2112;

__device__ bf16 g_kv[(size_t)SEQ * 2 * HDALL];
__device__ bf16 g_ctx[(size_t)SEQ * HDALL];
__device__ uint4 g_y[32 * 4 * 4 * 2 * 128];
__device__ unsigned int g_ycnt[32];
__device__ unsigned int g_sched;

#define STAMP(cond, i)
DEVI uint32_t smem_u32(const void* p) { return (uint32_t)__cvta_generic_to_shared(p); }
DEVI void mbar_init(uint32_t a, uint32_t cnt) { asm volatile("mbarrier.init.shared::cta.b64 [%0], %1;" ::"r"(a), "r"(cnt)); }
DEVI void mbar_expect_tx(uint32_t a, uint32_t bytes) {
    asm volatile("mbarrier.arrive.expect_tx.shared::cta.b64 _, [%0], %1;" ::"r"(a), "r"(bytes) : "memory");
}
DEVI void mbar_arrive(uint32_t a) { asm volatile("mbarrier.arrive.shared::cta.b64 _, [%0];" ::"r"(a) : "memory"); }
DEVI void mbar_arrive_cluster(uint32_t a, uint32_t cta) {
    asm volatile("{\n.reg .b32 r;\nmapa.shared::cluster.u32 r, %0, %1;\n"
                 "mbarrier.arrive.shared::cluster.b64 _, [r];\n}" ::"r"(a), "r"(cta) : "memory");
}
#define MBAR_WAIT_ASM(OP)                                                                              \
    asm volatile("{\n.reg .pred p, q;\n.reg .u32 t0, t1;\n" OP " p, [%0], %1;\n@p bra D_%=;\n"         \
                 "mov.u32 t0, %%globaltimer_lo;\nW_%=:\n" OP " p, [%0], %1;\n"                         \
                 "mov.u32 t1, %%globaltimer_lo;\nsub.u32 t1, t1, t0;\n"                                \
                 "setp.gt.or.u32 q, t1, 4000000, p;\n@!q bra W_%=;\nD_%=:\n}" ::"r"(a), "r"(parity) : "memory")
DEVI void mbar_wait(uint32_t a, uint32_t parity) { MBAR_WAIT_ASM("mbarrier.try_wait.parity.shared::cta.b64"); }
DEVI void mbar_wait_cluster(uint32_t a, uint32_t parity) { MBAR_WAIT_ASM("mbarrier.try_wait.parity.acquire.cluster.shared::cta.b64"); }
DEVI void fence_barrier_init() { asm volatile("fence.mbarrier_init.release.cluster;" ::: "memory"); }
DEVI void fence_proxy_async() { asm volatile("fence.proxy.async.shared::cta;" ::: "memory"); }
DEVI void cluster_sync_all() {
    asm volatile("barrier.cluster.arrive.relaxed.aligned;\nbarrier.cluster.wait.aligned;" ::: "memory");
}
DEVI void cluster_arrive() { asm volatile("barrier.cluster.arrive.relaxed.aligned;" ::: "memory"); }
DEVI void cluster_wait() { asm volatile("barrier.cluster.wait.aligned;" ::: "memory"); }
DEVI uint32_t cluster_rank() { uint32_t r; asm volatile("mov.u32 %0, %%cluster_ctarank;" : "=r"(r)); return r; }
DEVI void tma_load_2d(uint32_t dst, const CUtensorMap* m, int c0, int c1, uint32_t bar) {
    asm volatile("cp.async.bulk.tensor.2d.shared::cluster.global.mbarrier::complete_tx::bytes [%0], [%1, {%3, %4}], [%2];"
                 ::"r"(dst), "l"(m), "r"(bar), "r"(c0), "r"(c1) : "memory");
}
DEVI void tma_load_2d_mc(uint32_t dst, const CUtensorMap* m, int c0, int c1, uint32_t bar, uint16_t mask) {
    asm volatile("cp.async.bulk.tensor.2d.shared::cluster.global.mbarrier::complete_tx::bytes.multicast::cluster [%0], [%1, {%3, %4}], [%2], %5;"
                 ::"r"(dst), "l"(m), "r"(bar), "r"(c0), "r"(c1), "h"(mask) : "memory");
}
DEVI void tma_prefetch_2d(const CUtensorMap* m, int c0, int c1) {
    asm volatile("cp.async.bulk.prefetch.tensor.2d.L2.global [%0, {%1, %2}];" ::"l"(m), "r"(c0), "r"(c1) : "memory");
}
DEVI void tma_store_2d(const CUtensorMap* m, uint32_t src, int c0, int c1) {
    asm volatile("cp.async.bulk.tensor.2d.global.shared::cta.bulk_group [%0, {%2, %3}], [%1];"
                 ::"l"(m), "r"(src), "r"(c0), "r"(c1) : "memory");
}
DEVI void bulk_load(uint32_t dst, const void* src, uint32_t bytes, uint32_t bar) {
    asm volatile("cp.async.bulk.shared::cluster.global.mbarrier::complete_tx::bytes [%0], [%1], %2, [%3];"
                 ::"r"(dst), "l"(src), "r"(bytes), "r"(bar) : "memory");
}
DEVI void bulk_prefetch(const void* src, uint32_t bytes) {
    asm volatile("cp.async.bulk.prefetch.L2.global [%0], %1;" ::"l"(src), "r"(bytes) : "memory");
}
DEVI void bulk_commit() { asm volatile("cp.async.bulk.commit_group;" ::: "memory"); }
template <int N> DEVI void bulk_wait_read() { asm volatile("cp.async.bulk.wait_group.read %0;" ::"n"(N) : "memory"); }
template <int N> DEVI void bulk_wait() { asm volatile("cp.async.bulk.wait_group %0;" ::"n"(N) : "memory"); }
DEVI void prefetch_tmap(const CUtensorMap* m) { asm volatile("prefetch.tensormap [%0];" ::"l"(m) : "memory"); }
DEVI void named_sync(int id, int n) { asm volatile("bar.sync %0, %1;" ::"r"(id), "r"(n) : "memory"); }
DEVI void named_arrive(int id, int n) { asm volatile("bar.arrive %0, %1;" ::"r"(id), "r"(n) : "memory"); }
DEVI void pdl_wait() { asm volatile("griddepcontrol.wait;" ::: "memory"); }
DEVI void pdl_launch() { asm volatile("griddepcontrol.launch_dependents;" ::: "memory"); }
template <int R> DEVI void reg_inc() { asm volatile("setmaxnreg.inc.sync.aligned.u32 %0;" ::"n"(R)); }
template <int R> DEVI void reg_dec() { asm volatile("setmaxnreg.dec.sync.aligned.u32 %0;" ::"n"(R)); }

DEVI void wg_fence() { asm volatile("wgmma.fence.sync.aligned;" ::: "memory"); }
DEVI void wg_commit() { asm volatile("wgmma.commit_group.sync.aligned;" ::: "memory"); }
template <int N> DEVI void wg_wait() { asm volatile("wgmma.wait_group.sync.aligned %0;" ::"n"(N) : "memory"); }

DEVI uint64_t make_desc(uint32_t addr, uint32_t lbo, uint32_t sbo, uint32_t swz) {
    return (uint64_t)((addr & 0x3FFFF) >> 4) | ((uint64_t)(lbo >> 4) << 16) | ((uint64_t)(sbo >> 4) << 32) | ((uint64_t)swz << 62);
}
DEVI uint64_t desc_kmajor(uint32_t addr) { return make_desc(addr, 16, 1024, 1); }
DEVI uint64_t desc_mnmajor(uint32_t addr, uint32_t lbo) { return make_desc(addr, lbo, 1024, 1); }

#define ACC8(d, o) "+f"(d[o + 0]), "+f"(d[o + 1]), "+f"(d[o + 2]), "+f"(d[o + 3]), "+f"(d[o + 4]), "+f"(d[o + 5]), "+f"(d[o + 6]), "+f"(d[o + 7])
#define ACC64(d) ACC8(d, 0), ACC8(d, 8), ACC8(d, 16), ACC8(d, 24), ACC8(d, 32), ACC8(d, 40), ACC8(d, 48), ACC8(d, 56)
#define R64 "{%0,%1,%2,%3,%4,%5,%6,%7,%8,%9,%10,%11,%12,%13,%14,%15,%16,%17,%18,%19,%20,%21,%22,%23,%24,%25,%26,%27,%28,%29,%30,%31," \
            "%32,%33,%34,%35,%36,%37,%38,%39,%40,%41,%42,%43,%44,%45,%46,%47,%48,%49,%50,%51,%52,%53,%54,%55,%56,%57,%58,%59,%60,%61,%62,%63}"

template <int TB> DEVI void wgmma_ss128(float* d, uint64_t da, uint64_t db, int acc) {
    asm volatile("{\n.reg .pred p;\nsetp.ne.b32 p, %66, 0;\n"
                 "wgmma.mma_async.sync.aligned.m64n128k16.f32.bf16.bf16 " R64 ", %64, %65, p, 1, 1, 0, %67;\n}"
                 : ACC64(d) : "l"(da), "l"(db), "r"(acc), "n"(TB));
}
template <int TB> DEVI void wgmma_rs128(float* d, const uint32_t* a, uint64_t db, int acc) {
    asm volatile("{\n.reg .pred p;\nsetp.ne.b32 p, %69, 0;\n"
                 "wgmma.mma_async.sync.aligned.m64n128k16.f32.bf16.bf16 " R64 ", {%64,%65,%66,%67}, %68, p, 1, 1, %70;\n}"
                 : ACC64(d) : "r"(a[0]), "r"(a[1]), "r"(a[2]), "r"(a[3]), "l"(db), "r"(acc), "n"(TB));
}
DEVI uint32_t pack_bf16(float lo, float hi) {
    uint32_t r;
    asm("cvt.rn.bf16x2.f32 %0, %1, %2;" : "=r"(r) : "f"(hi), "f"(lo));
    return r;
}
DEVI void stmatrix_x4(uint32_t addr, uint32_t r0, uint32_t r1, uint32_t r2, uint32_t r3) {
    asm volatile("stmatrix.sync.aligned.m8n8.x4.shared.b16 [%0], {%1,%2,%3,%4};" ::"r"(addr), "r"(r0), "r"(r1), "r"(r2), "r"(r3) : "memory");
}
DEVI float ex2(float x) { float y; asm("ex2.approx.ftz.f32 %0, %1;" : "=f"(y) : "f"(x)); return y; }

DEVI void store_slab64(uint32_t base, int row0, const float* d, float s0, float s1, int lane) {
    int mi = lane >> 3, r = lane & 7;
    int row = row0 + (mi & 1) * 8 + r;
#pragma unroll
    for (int j = 0; j < 8; j += 2) {
        uint32_t r0 = pack_bf16(d[4 * j + 0] * s0, d[4 * j + 1] * s0);
        uint32_t r1 = pack_bf16(d[4 * j + 2] * s1, d[4 * j + 3] * s1);
        uint32_t r2 = pack_bf16(d[4 * j + 4] * s0, d[4 * j + 5] * s0);
        uint32_t r3 = pack_bf16(d[4 * j + 6] * s1, d[4 * j + 7] * s1);
        int chunk = j + (mi >> 1);
        stmatrix_x4(base + row * 128 + ((chunk ^ (row & 7)) << 4), r0, r1, r2, r3);
    }
}
struct cf { float x, y; };
DEVI cf cmul(cf a, cf b) { cf r; r.x = fmaf(a.x, b.x, -a.y * b.y); r.y = fmaf(a.x, b.y, a.y * b.x); return r; }
DEVI cf csq(cf a) { cf r; r.x = fmaf(a.x, a.x, -a.y * a.y); r.y = (a.x + a.x) * a.y; return r; }
DEVI cf cexp_(float re, float im) {
    float m = __expf(re), s, c;
    __sincosf(im, &s, &c);
    cf r; r.x = m * c; r.y = m * s; return r;
}
DEVI uint32_t h2(cf v) { uint32_t r; asm("cvt.rn.f16x2.f32 %0, %1, %2;" : "=r"(r) : "f"(v.y), "f"(v.x)); return r; }
DEVI uint32_t h2c(cf v) { uint32_t r; asm("cvt.rn.f16x2.f32 %0, %1, %2;" : "=r"(r) : "f"(-v.y), "f"(v.x)); return r; }
DEVI void mma_group(float (*c)[4], const uint32_t (*a)[4], const uint32_t (*b)[2]) {
    asm volatile(
        "mma.sync.aligned.m16n8k16.row.col.f32.f16.f16.f32 {%0,%1,%2,%3}, {%20,%21,%22,%23}, {%40,%41}, {%0,%1,%2,%3};\n"
        "mma.sync.aligned.m16n8k16.row.col.f32.f16.f16.f32 {%4,%5,%6,%7}, {%24,%25,%26,%27}, {%40,%41}, {%4,%5,%6,%7};\n"
        "mma.sync.aligned.m16n8k16.row.col.f32.f16.f16.f32 {%8,%9,%10,%11}, {%28,%29,%30,%31}, {%42,%43}, {%8,%9,%10,%11};\n"
        "mma.sync.aligned.m16n8k16.row.col.f32.f16.f16.f32 {%12,%13,%14,%15}, {%32,%33,%34,%35}, {%44,%45}, {%12,%13,%14,%15};\n"
        "mma.sync.aligned.m16n8k16.row.col.f32.f16.f16.f32 {%16,%17,%18,%19}, {%36,%37,%38,%39}, {%46,%47}, {%16,%17,%18,%19};\n"
        : "+f"(c[0][0]), "+f"(c[0][1]), "+f"(c[0][2]), "+f"(c[0][3]), "+f"(c[1][0]), "+f"(c[1][1]), "+f"(c[1][2]), "+f"(c[1][3]),
          "+f"(c[2][0]), "+f"(c[2][1]), "+f"(c[2][2]), "+f"(c[2][3]), "+f"(c[3][0]), "+f"(c[3][1]), "+f"(c[3][2]), "+f"(c[3][3]),
          "+f"(c[4][0]), "+f"(c[4][1]), "+f"(c[4][2]), "+f"(c[4][3])
        : "r"(a[0][0]), "r"(a[0][1]), "r"(a[0][2]), "r"(a[0][3]), "r"(a[1][0]), "r"(a[1][1]), "r"(a[1][2]), "r"(a[1][3]),
          "r"(a[2][0]), "r"(a[2][1]), "r"(a[2][2]), "r"(a[2][3]), "r"(a[3][0]), "r"(a[3][1]), "r"(a[3][2]), "r"(a[3][3]),
          "r"(a[4][0]), "r"(a[4][1]), "r"(a[4][2]), "r"(a[4][3]),
          "r"(b[0][0]), "r"(b[0][1]), "r"(b[1][0]), "r"(b[1][1]), "r"(b[2][0]), "r"(b[2][1]), "r"(b[3][0]), "r"(b[3][1]));
}
DEVI float bf2f(bf16 v) { return __bfloat162float(v); }
DEVI float rbf(float v) { return __bfloat162float(__float2bfloat16_rn(v)); }

struct SsmParams { const bf16 *lar, *aim, *cre, *cim, *ldt, *dskip, *u; };

DEVI int kp_index(int l) {
    int p = (int)rbf((float)l);
    return p < 256 ? p : (p < 512 ? 128 + (p >> 1) : (p < 1024 ? 256 + (p >> 2) : 384 + (p >> 3)));
}

DEVI void reds(uint32_t a, float v, bool plain) {
    if (plain) asm volatile("st.shared.f32 [%0], %1;" ::"r"(a), "f"(v) : "memory");
    else asm volatile("red.shared.add.f32 [%0], %1;" ::"r"(a), "f"(v) : "memory");
}
DEVI uint32_t ldg16(const bf16* p) { uint16_t v; asm volatile("ld.global.nc.u16 %0, [%1];" : "=h"(v) : "l"(p)); return v; }
DEVI void ssm_kgen_load(const SsmParams& P, int d, int half, int lane, uint32_t* r) {
#pragma unroll
    for (int q = 0; q < 2; q++) {
        const int n = d * SSM_N + min(48 * half + 32 * q + lane, SSM_N - 1);
        r[4 * q] = ldg16(P.lar + n); r[4 * q + 1] = ldg16(P.aim + n); r[4 * q + 2] = ldg16(P.cre + n); r[4 * q + 3] = ldg16(P.cim + n);
    }
    r[8] = ldg16(P.ldt + d);
}
template <class F> DEVI void ssm_kgen_warp(const uint32_t* r, int lane, uint32_t kp, bool plain, F mid) {
    float raw[9];
#pragma unroll
    for (int i = 0; i < 9; i++) raw[i] = __uint_as_float(r[i] << 16);
    const int g = lane >> 2, t = lane & 3;
    float ar[2], ai[2], cr[2], ci[2], gr[2], gi[2];
    const float dt = rbf(expf(raw[8]));
#pragma unroll
    for (int q = 0; q < 2; q++) {
        ar[q] = -rbf(expf(raw[4 * q])) * dt;
        ai[q] = raw[4 * q + 1] * dt;
        cr[q] = 2.f * (raw[4 * q + 2] * dt);
        ci[q] = 2.f * (raw[4 * q + 3] * dt);
        float m = expf(ar[q] * 64.f), sn, cs;
        sincosf(ai[q] * 64.f, &sn, &cs);
        gr[q] = m * cs; gi[q] = m * sn;
    }
    float cm = 0.f;
#pragma unroll
    for (int q = 0; q < 2; q++) cm = fmaxf(cm, fmaxf(fabsf(cr[q]), fabsf(ci[q])));
#pragma unroll
    for (int o = 16; o; o >>= 1) cm = fmaxf(cm, __shfl_xor_sync(~0u, cm, o));
    const int ex = min(max((int)(__float_as_uint(cm) >> 23), 1), 253);
    const float cs_dn = __uint_as_float((uint32_t)(254 - ex) << 23), cs_up = __uint_as_float((uint32_t)ex << 23);
    float acc[5][4];
#pragma unroll
    for (int s = 0; s < 5; s++) { acc[s][0] = acc[s][1] = acc[s][2] = acc[s][3] = 0.f; }
    float klast = 0.f;
    const float gf = (float)g;
#pragma unroll
    for (int q = 0; q < 2; q++) {
#pragma unroll 1
        for (int g0 = 0; g0 < (q == 0 ? 8 : (plain ? 0 : 4)); g0 += 2) {
            uint32_t fa[5][4], fb[4][2];
#pragma unroll
            for (int h = 0; h < 2; h++) {
                const int src = ((g0 + h) << 2) | t;
                const float a_r = __shfl_sync(~0u, ar[q], src), a_i = __shfl_sync(~0u, ai[q], src);
                cf C, G;
                C.x = __shfl_sync(~0u, cr[q], src) * cs_dn; C.y = __shfl_sync(~0u, ci[q], src) * cs_dn;
                G.x = __shfl_sync(~0u, gr[q], src); G.y = __shfl_sync(~0u, gi[q], src);
                cf E = cexp_(a_r * gf, a_i * gf);
                cf B = csq(csq(csq(E)));
                fb[0][h] = h2c(cmul(C, B));
                cf EG = cmul(E, G);
                fa[0][2 * h] = h2(E); fa[0][2 * h + 1] = h2(EG);
                cf G2 = csq(G);
                cf X = cmul(E, G2), Xh = cmul(EG, G2);
                fa[1][2 * h] = h2(X); fa[1][2 * h + 1] = h2(Xh);
#pragma unroll
                for (int s = 2; s < 5; s++) {
                    B = csq(B); X = csq(X); Xh = csq(Xh);
                    fb[s - 1][h] = h2c(cmul(C, B));
                    fa[s][2 * h] = h2(X); fa[s][2 * h + 1] = h2(Xh);
                }
                X = csq(X);
                klast += fmaf(C.x, X.x, -C.y * X.y);
            }
            mma_group(acc, fa, fb);
        }
    }
    klast += __shfl_xor_sync(~0u, klast, 1);
    klast += __shfl_xor_sync(~0u, klast, 2);
    mid();
    if (lane == 1) reds(kp + 644 * 4, 0.f, plain);
#pragma unroll
    for (int s = 0; s < 5; s++) {
        const uint32_t b = kp + (128 * s + g + 16 * t) * 4;
        reds(b, acc[s][0] * cs_up, plain); reds(b + 32, acc[s][1] * cs_up, plain); reds(b + 256, acc[s][2] * cs_up, plain); reds(b + 288, acc[s][3] * cs_up, plain);
    }
    if (lane == 0) reds(kp + 2560, klast * cs_up, plain);
}

constexpr int G1_THREADS = 384;
constexpr int G1_NS = 11;
constexpr int G1_SMEM = G1_NS * 16384 + 32768 + 256 + 1024;

__global__ void __cluster_dims__(2, 1, 1) __launch_bounds__(G1_THREADS, 1)
gemm_kv_kernel(const __grid_constant__ CUtensorMap tm_c, const __grid_constant__ CUtensorMap tm_wk,
               const __grid_constant__ CUtensorMap tm_wv, const __grid_constant__ CUtensorMap tm_kv_st,
               const bf16* __restrict__ px, const bf16* __restrict__ pwq) {
    extern __shared__ uint8_t smem_raw[];
    const uint32_t sb = (smem_u32(smem_raw) + 1023) & ~1023u;
    const uint32_t sC = sb + G1_NS * 16384, bars = sC + 32768;
    const uint32_t full = bars, empty = bars + 128;
    const int tid = threadIdx.x, warp = tid >> 5, lane = tid & 31, wg = tid >> 7;
    const uint32_t rank = cluster_rank();
    const int cl = blockIdx.x >> 1;
    const int m0 = ((cl & 7) * 2 + rank) * 128;
    const int ng = cl >> 3;
    STAMP(blockIdx.x == 10 && tid == 0, 0);
    if (tid == 0) {
        for (int i = 0; i < G1_NS; i++) { mbar_init(full + 8 * i, 1); mbar_init(empty + 8 * i, 16); }
        fence_barrier_init();
        for (int it = 0; it < 8; it++) {
            mbar_expect_tx(full + 8 * it, 16384);
            tma_load_2d(sb + it * 16384, &tm_c, it * 64, m0, full + 8 * it);
        }
    }
    __syncthreads();
    cluster_sync_all();
    pdl_launch();
    if (wg == 2) {
        reg_dec<40>();
        if (tid == 256) {
            const CUtensorMap* tw = ng < 4 ? &tm_wk : &tm_wv;
            const int n0 = (ng & 3) * 1024 + rank * 64;
            int st = 8; uint32_t ph = 1;
            for (int it = 0; it < 64; it++) {
                mbar_wait(empty + 8 * st, ph);
                mbar_expect_tx(full + 8 * st, 16384);
                tma_load_2d_mc(sb + st * 16384 + rank * 8192, tw, n0 + (it >> 3) * 128, (it & 7) * 64, full + 8 * st, 3);
                if (it < 2) {
                    for (int j = 3 + it * 8 + (cl & 7); j < 19; j += 16) tma_prefetch_2d(tw, n0 + (j >> 3) * 128, (j & 7) * 64);
                }
                if (it >= 3 && it + 16 < 64 && (it & 7) == (cl & 7)) tma_prefetch_2d(tw, n0 + ((it + 16) >> 3) * 128, (it & 7) * 64);
                if (it == 24) bulk_prefetch(px + blockIdx.x * 8192, 16384);
                if (it == 32) bulk_prefetch(pwq + blockIdx.x * 16384, 32768);
                if (++st == G1_NS) { st = 0; ph ^= 1; }
            }
        }
        __syncwarp();
    } else {
        reg_inc<232>();
        uint32_t af[128];
        float acc[64];
        const int wq = warp & 3;
        const int row = wg * 64 + wq * 16 + (lane & 15);
        const uint32_t stg = sC + wg * 16384;
        int st = 8, pst = 0; uint32_t ph = 0;
#pragma unroll
        for (int kc = 0; kc < 8; kc++) {
            mbar_wait(full + 8 * kc, 0);
#pragma unroll
            for (int k = 0; k < 4; k++) {
                const uint32_t a = sb + kc * 16384 + row * 128 + (((2 * k + (lane >> 4)) ^ (row & 7)) << 4);
                uint32_t* f = af + kc * 16 + k * 4;
                asm volatile("ldmatrix.sync.aligned.m8n8.x4.shared.b16 {%0,%1,%2,%3}, [%4];"
                             : "=r"(f[0]), "=r"(f[1]), "=r"(f[2]), "=r"(f[3]) : "r"(a) : "memory");
            }
            __syncwarp();
            if (lane < 2) mbar_arrive_cluster(empty + 8 * kc, lane);
        }
#pragma unroll 1
        for (int t = 0; t < 8; t++) {
            if (wg == 1 || t > 0) named_sync(3 + wg, 256);
#pragma unroll
            for (int kc = 0; kc < 8; kc++) {
                mbar_wait(full + 8 * st, ph);
                STAMP(blockIdx.x == 10 && (tid & 127) == 0, 1 + wg * 96 + t * 12 + kc);
                wg_fence();
                const uint64_t db = desc_mnmajor(sb + st * 16384, 8192);
#pragma unroll
                for (int k = 0; k < 4; k++) wgmma_rs128<1>(acc, af + kc * 16 + k * 4, db + k * 128, (kc | k) != 0);
                wg_commit();
                if (kc == 3 && (wg == 0 || t < 7)) named_arrive(3 + (wg ^ 1), 256);
                if (kc > 0) {
                    wg_wait<1>();
                    if (lane < 2) mbar_arrive_cluster(empty + 8 * pst, lane);
                }
                pst = st;
                if (++st == G1_NS) { st = 0; ph ^= 1; }
            }
            if ((tid & 127) == 0) bulk_wait_read<0>();
            named_sync(1 + wg, 128);
            wg_wait<0>();
            STAMP(blockIdx.x == 10 && (tid & 127) == 0, 9 + wg * 96 + t * 12);
            if (lane < 2) mbar_arrive_cluster(empty + 8 * pst, lane);
            store_slab64(stg, wq * 16, acc, 1.f, 1.f, lane);
            store_slab64(stg + 8192, wq * 16, acc + 32, 1.f, 1.f, lane);
            fence_proxy_async();
            named_sync(1 + wg, 128);
            if ((tid & 127) == 0) {
                tma_store_2d(&tm_kv_st, stg, ng * 1024 + t * 128, m0 + wg * 64);
                tma_store_2d(&tm_kv_st, stg + 8192, ng * 1024 + t * 128 + 64, m0 + wg * 64);
                bulk_commit();
            }
            STAMP(blockIdx.x == 10 && (tid & 127) == 0, 10 + wg * 96 + t * 12);
        }
        if ((tid & 127) == 0) bulk_wait<0>();
        __syncwarp();
    }
    asm volatile("barrier.cluster.arrive.relaxed.aligned;\nbarrier.cluster.wait.aligned;" ::: "memory");
}
constexpr int AT_NS = 6;
constexpr int AT_SMEM = AT_NS * 32768 + 32768 + 256 + 1024;
constexpr int AT_ITEMS = 512;

DEVI uint32_t hmax2(uint32_t a, uint32_t b) { uint32_t r; asm("max.bf16x2 %0, %1, %2;" : "=r"(r) : "r"(a), "r"(b)); return r; }
DEVI uint32_t hmul2(uint32_t a, uint32_t b) { uint32_t r; asm("mul.rn.bf16x2 %0, %1, %2;" : "=r"(r) : "r"(a), "r"(b)); return r; }
DEVI uint32_t hfma2(uint32_t a, uint32_t b, uint32_t c) { uint32_t r; asm("fma.rn.bf16x2 %0, %1, %2, %3;" : "=r"(r) : "r"(a), "r"(b), "r"(c)); return r; }
DEVI float blo(uint32_t v) { return __uint_as_float(v << 16); }
DEVI float bhi(uint32_t v) { return __uint_as_float(v & 0xffff0000u); }

template <bool FIRST>
DEVI void softmax_tile(float* s, float& m0, float& m1, float& l0, float& l1, float& al0, float& al1) {
    const uint32_t HI = 0x3DB53DB5u;
    const uint32_t LO = 0x371E371Eu;
    const float L2E = 1.4426950408889634f;
    uint32_t x0 = 0xFF80FF80u, x1 = 0xFF80FF80u;
#pragma unroll
    for (int j = 0; j < 16; j++) {
        uint32_t a = pack_bf16(s[4 * j], s[4 * j + 1]), b = pack_bf16(s[4 * j + 2], s[4 * j + 3]);
        a = hfma2(a, HI, hmul2(a, LO));
        b = hfma2(b, HI, hmul2(b, LO));
        s[4 * j] = __uint_as_float(a); s[4 * j + 2] = __uint_as_float(b);
        x0 = hmax2(x0, a); x1 = hmax2(x1, b);
    }
    uint32_t x = hmax2(__byte_perm(x0, x1, 0x5410), __byte_perm(x0, x1, 0x7632));
    x = hmax2(x, __shfl_xor_sync(~0u, x, 1));
    x = hmax2(x, __shfl_xor_sync(~0u, x, 2));
    float n0 = blo(x), n1 = bhi(x);
    if (!FIRST) {
        n0 = fmaxf(n0, m0); n1 = fmaxf(n1, m1);
        al0 = ex2((m0 - n0) * L2E); al1 = ex2((m1 - n1) * L2E);
    }
    m0 = n0; m1 = n1;
    const float c0 = -n0 * L2E, c1 = -n1 * L2E;
    float s0 = 0.f, s1 = 0.f;
#pragma unroll
    for (int j = 0; j < 16; j++) {
        uint32_t a = __float_as_uint(s[4 * j]), b = __float_as_uint(s[4 * j + 2]);
        float e0 = ex2(fmaf(blo(a), L2E, c0)), e1 = ex2(fmaf(bhi(a), L2E, c0));
        float e2 = ex2(fmaf(blo(b), L2E, c1)), e3 = ex2(fmaf(bhi(b), L2E, c1));
        s0 += e0 + e1; s1 += e2 + e3;
        s[4 * j] = e0; s[4 * j + 1] = e1; s[4 * j + 2] = e2; s[4 * j + 3] = e3;
    }
    if (FIRST) { l0 = s0; l1 = s1; }
    else { l0 = fmaf(l0, al0, s0); l1 = fmaf(l1, al1, s1); }
}

struct Ring {
    int st; uint32_t ph;
    DEVI void next() { if (++st == AT_NS) { st = 0; ph ^= 1; } }
};

__global__ void __launch_bounds__(384, 1)
attn_kernel(const __grid_constant__ CUtensorMap tm_x, const __grid_constant__ CUtensorMap tm_wq,
            const __grid_constant__ CUtensorMap tm_kv, const __grid_constant__ CUtensorMap tm_ctx_st,
            const SsmParams sp, const bf16* __restrict__ pwo) {
    extern __shared__ uint8_t smem_raw[];
    const uint32_t sb = (smem_u32(smem_raw) + 1023) & ~1023u;
    const uint32_t sO = sb + AT_NS * 32768, bars = sO + 32768;
    const uint32_t full = bars, empty = bars + 64;
    volatile int* slots = reinterpret_cast<volatile int*>(smem_raw + (bars + 128 - smem_u32(smem_raw)));
    const int tid = threadIdx.x, warp = tid >> 5, lane = tid & 31, wg = tid >> 7;
    if (tid == 0) {
        for (int i = 0; i < AT_NS; i++) { mbar_init(full + 8 * i, 1); mbar_init(empty + 8 * i, 8); }
        fence_barrier_init();
    }
    __syncthreads();
    if (wg == 2) {
        reg_dec<24>();
        if (warp == 8 && lane == 0) {
            Ring r{0, 1};
            int n = 0;
            while (true) {
                int idx = (int)atomicInc(&g_sched, AT_ITEMS + gridDim.x - 1);
                if (idx >= AT_ITEMS - 128 && idx < AT_ITEMS) {
                    bulk_prefetch(sp.u + (idx - (AT_ITEMS - 128)) * 8192, 16384);
                    const int po = (idx - (AT_ITEMS - 128)) * 512;
                    bulk_prefetch(sp.lar + po, 1024); bulk_prefetch(sp.aim + po, 1024);
                    bulk_prefetch(sp.cre + po, 1024); bulk_prefetch(sp.cim + po, 1024);
                    if (po == 0) { bulk_prefetch(sp.ldt, 1024); bulk_prefetch(sp.dskip, 1024); }
                    bulk_prefetch(pwo + (idx - (AT_ITEMS - 128)) * 16384, 32768);
                }
                mbar_wait(empty + 8 * r.st, r.ph);
                if (idx >= AT_ITEMS) {
                    slots[n & 3] = -1;
                    mbar_arrive(full + 8 * r.st);
                    break;
                }
                slots[n & 3] = idx;
                const int qi = 15 - (idx >> 5), h = idx & 31;
                for (int kc = 0; kc < 8; kc++) {
                    if (kc) mbar_wait(empty + 8 * r.st, r.ph);
                    const uint32_t fb = full + 8 * r.st, dst = sb + r.st * 32768;
                    mbar_expect_tx(fb, 32768);
                    tma_load_2d(dst, &tm_x, kc * 64, qi * 128, fb);
                    tma_load_2d(dst + 16384, &tm_wq, h * 128, kc * 64, fb);
                    tma_load_2d(dst + 24576, &tm_wq, h * 128 + 64, kc * 64, fb);
                    r.next();
                }
                if (n == 0) { pdl_wait(); pdl_launch(); }
                for (int j = qi; j >= -1; j--) {
#pragma unroll
                    for (int v = 0; v < 2; v++) {
                        const int jj = j + v;
                        if (jj < 0 || jj > qi || (v == 0 && j < 0)) continue;
                        mbar_wait(empty + 8 * r.st, r.ph);
                        const uint32_t fb = full + 8 * r.st, dst = sb + r.st * 32768;
                        mbar_expect_tx(fb, 32768);
                        tma_load_2d(dst, &tm_kv, v * HDALL + h * 128, jj * 128, fb);
                        tma_load_2d(dst + 16384, &tm_kv, v * HDALL + h * 128 + 64, jj * 128, fb);
                        r.next();
                    }
                }
                n++;
            }
            if (n == 0) { pdl_wait(); pdl_launch(); }
        }
    } else {
        reg_inc<240>();
        Ring r{0, 0};
        float o[64], s[64];
        uint32_t qf[32], pa[32];
        const int g = lane >> 2, t = lane & 3, wq = warp & 3;
        const uint32_t stg = sO + wg * 16384;
        if (wg == 1) named_arrive(3, 256);
        for (int n = 0;; n++) {
            mbar_wait(full + 8 * r.st, r.ph);
            const int idx = slots[n & 3];
            if (idx < 0) break;
            const int qi = 15 - (idx >> 5), h = idx & 31;
#pragma unroll 1
            for (int kc = 0; kc < 8; kc++) {
                if (kc) mbar_wait(full + 8 * r.st, r.ph);
                wg_fence();
                const uint32_t base = sb + r.st * 32768;
                const uint64_t da = desc_kmajor(base + wg * 8192), db = desc_mnmajor(base + 16384, 8192);
#pragma unroll
                for (int k = 0; k < 4; k++) wgmma_ss128<1>(s, da + k * 2, db + k * 128, (kc | k) != 0);
                wg_commit();
                if (kc) {
                    wg_wait<1>();
                    if (lane == 0) mbar_arrive(empty + 8 * (r.st == 0 ? AT_NS - 1 : r.st - 1));
                }
                r.next();
            }
            wg_wait<0>();
            if (lane == 0) mbar_arrive(empty + 8 * (r.st == 0 ? AT_NS - 1 : r.st - 1));
#pragma unroll
            for (int i = 0; i < 32; i++) qf[i] = pack_bf16(s[2 * i], s[2 * i + 1]);
            float m0, m1, l0, l1, al0, al1;
            auto issue_qk = [&]() {
                mbar_wait(full + 8 * r.st, r.ph);
                wg_fence();
                const uint64_t db = desc_kmajor(sb + r.st * 32768);
#pragma unroll
                for (int k = 0; k < 8; k++) wgmma_rs128<0>(s, qf + 4 * k, db + (k >> 2) * 1024 + (k & 3) * 2, k != 0);
                wg_commit();
            };
            auto issue_pv = [&](const uint32_t* p, int st, uint32_t ph, int acc) {
                mbar_wait(full + 8 * st, ph);
                wg_fence();
                const uint64_t db = desc_mnmajor(sb + st * 32768, 16384);
#pragma unroll
                for (int k = 0; k < 8; k++) wgmma_rs128<1>(o, p + 4 * k, db + k * 128, acc | k);
                wg_commit();
            };
            issue_qk();
            wg_wait<0>();
            if (lane == 0) mbar_arrive(empty + 8 * r.st);
            r.next();
            {
                const int row = wg * 64 + wq * 16 + g;
#pragma unroll
                for (int j = 0; j < 16; j++) {
                    const int c = 8 * j + 2 * t;
                    if (c > row) s[4 * j] = -INFINITY;
                    if (c + 1 > row) s[4 * j + 1] = -INFINITY;
                    if (c > row + 8) s[4 * j + 2] = -INFINITY;
                    if (c + 1 > row + 8) s[4 * j + 3] = -INFINITY;
                }
            }
            softmax_tile<true>(s, m0, m1, l0, l1, al0, al1);
#pragma unroll
            for (int i = 0; i < 32; i++) pa[i] = pack_bf16(s[2 * i], s[2 * i + 1]);
            int first = 0;
#pragma unroll 1
            for (int j = qi; j >= 1; j--) {
                named_sync(3 + wg, 256);
                issue_qk();
                const int kst = r.st;
                r.next();
                issue_pv(pa, r.st, r.ph, first);
                named_arrive(3 + (wg ^ 1), 256);
                wg_wait<1>();
                if (lane == 0) mbar_arrive(empty + 8 * kst);
                softmax_tile<false>(s, m0, m1, l0, l1, al0, al1);
                wg_wait<0>();
                if (lane == 0) mbar_arrive(empty + 8 * r.st);
                r.next();
#pragma unroll
                for (int i = 0; i < 32; i++) pa[i] = pack_bf16(s[2 * i], s[2 * i + 1]);
#pragma unroll
                for (int i = 0; i < 16; i++) {
                    o[4 * i] *= al0; o[4 * i + 1] *= al0; o[4 * i + 2] *= al1; o[4 * i + 3] *= al1;
                }
                first = 1;
            }
            issue_pv(pa, r.st, r.ph, first);
            l0 += __shfl_xor_sync(~0u, l0, 1); l0 += __shfl_xor_sync(~0u, l0, 2);
            l1 += __shfl_xor_sync(~0u, l1, 1); l1 += __shfl_xor_sync(~0u, l1, 2);
            const float i0 = 1.f / l0, i1 = 1.f / l1;
            if ((tid & 127) == 0) bulk_wait_read<0>();
            named_sync(1 + wg, 128);
            wg_wait<0>();
            if (lane == 0) mbar_arrive(empty + 8 * r.st);
            r.next();
            store_slab64(stg, wq * 16, o, i0, i1, lane);
            store_slab64(stg + 8192, wq * 16, o + 32, i0, i1, lane);
            fence_proxy_async();
            named_sync(1 + wg, 128);
            if ((tid & 127) == 0) {
                tma_store_2d(&tm_ctx_st, stg, h * 128, qi * 128 + wg * 64);
                tma_store_2d(&tm_ctx_st, stg + 8192, h * 128 + 64, qi * 128 + wg * 64);
                bulk_commit();
            }
        }
        if ((tid & 127) == 0) bulk_wait<0>();
    }
}
constexpr int OP_NS = 4;
constexpr int OP_ULD = 164 * 16;
constexpr int OP_UCH = 2 * OP_ULD;
constexpr int OP_SMEM = OP_NS * 32768 + 32768 + 4 * WTAB * 4 + 4 * OP_UCH + 4 * 648 * 4 + 256 + 1024;

template <int N> DEVI void wgmma_conv(float* d, const uint32_t* a, uint64_t db);
template <> DEVI void wgmma_conv<128>(float* d, const uint32_t* a, uint64_t db) {
    asm volatile("wgmma.mma_async.sync.aligned.m64n128k16.f32.bf16.bf16 {%0,%1,%2,%3,%4,%5,%6,%7,%8,%9,%10,%11,%12,%13,%14,%15,%16,%17,%18,%19,%20,%21,%22,%23,%24,%25,%26,%27,%28,%29,%30,%31,%32,%33,%34,%35,%36,%37,%38,%39,%40,%41,%42,%43,%44,%45,%46,%47,%48,%49,%50,%51,%52,%53,%54,%55,%56,%57,%58,%59,%60,%61,%62,%63}, "
                 "{%64,%65,%66,%67}, %68, 1, 1, 1, 0;"
                 : ACC8(d, 0), ACC8(d, 8), ACC8(d, 16), ACC8(d, 24), ACC8(d, 32), ACC8(d, 40), ACC8(d, 48), ACC8(d, 56) : "r"(a[0]), "r"(a[1]), "r"(a[2]), "r"(a[3]), "l"(db));
}
template <> DEVI void wgmma_conv<96>(float* d, const uint32_t* a, uint64_t db) {
    asm volatile("wgmma.mma_async.sync.aligned.m64n96k16.f32.bf16.bf16 {%0,%1,%2,%3,%4,%5,%6,%7,%8,%9,%10,%11,%12,%13,%14,%15,%16,%17,%18,%19,%20,%21,%22,%23,%24,%25,%26,%27,%28,%29,%30,%31,%32,%33,%34,%35,%36,%37,%38,%39,%40,%41,%42,%43,%44,%45,%46,%47}, "
                 "{%48,%49,%50,%51}, %52, 1, 1, 1, 0;"
                 : ACC8(d, 0), ACC8(d, 8), ACC8(d, 16), ACC8(d, 24), ACC8(d, 32), ACC8(d, 40) : "r"(a[0]), "r"(a[1]), "r"(a[2]), "r"(a[3]), "l"(db));
}
template <> DEVI void wgmma_conv<64>(float* d, const uint32_t* a, uint64_t db) {
    asm volatile("wgmma.mma_async.sync.aligned.m64n64k16.f32.bf16.bf16 {%0,%1,%2,%3,%4,%5,%6,%7,%8,%9,%10,%11,%12,%13,%14,%15,%16,%17,%18,%19,%20,%21,%22,%23,%24,%25,%26,%27,%28,%29,%30,%31}, "
                 "{%32,%33,%34,%35}, %36, 1, 1, 1, 0;"
                 : ACC8(d, 0), ACC8(d, 8), ACC8(d, 16), ACC8(d, 24) : "r"(a[0]), "r"(a[1]), "r"(a[2]), "r"(a[3]), "l"(db));
}
template <> DEVI void wgmma_conv<32>(float* d, const uint32_t* a, uint64_t db) {
    asm volatile("wgmma.mma_async.sync.aligned.m64n32k16.f32.bf16.bf16 {%0,%1,%2,%3,%4,%5,%6,%7,%8,%9,%10,%11,%12,%13,%14,%15}, "
                 "{%16,%17,%18,%19}, %20, 1, 1, 1, 0;"
                 : ACC8(d, 0), ACC8(d, 8) : "r"(a[0]), "r"(a[1]), "r"(a[2]), "r"(a[3]), "l"(db));
}
DEVI uint32_t lds32(uint32_t a) { uint32_t v; asm volatile("ld.shared.b32 %0, [%1];" : "=r"(v) : "r"(a)); return v; }
DEVI uint32_t lds16(uint32_t a) { uint16_t v; asm volatile("ld.shared.b16 %0, [%1];" : "=h"(v) : "r"(a)); return v; }

DEVI void sts32(uint32_t a, float v) { asm volatile("st.shared.f32 [%0], %1;" ::"r"(a), "f"(v) : "memory"); }
template <int J> DEVI void conv_half(float* acc, uint32_t* f, uint32_t wa, uint64_t du) {
#pragma unroll
    for (int i = 0; i < 4; i++) {
        const uint32_t w = wa + (4 * J + i) * 256;
        f[4 * i] = lds32(w); f[4 * i + 1] = lds32(w + 32); f[4 * i + 2] = lds32(w - 32); f[4 * i + 3] = lds32(w);
    }
    wg_fence();
#pragma unroll
    for (int i = 0; i < 4; i++) wgmma_conv<128 - 32 * (J / 2)>(acc, f + 4 * i, du + (uint64_t)(4 * (4 * J + i)));
    wg_commit();
}
template <int J> DEVI void conv_group(float* acc, uint32_t* fa, uint32_t* fb, uint32_t wa, uint64_t du) {
    conv_half<2 * J>(acc, fa, wa, du);
    if (J) wg_wait<1>();
    conv_half<2 * J + 1>(acc, fb, wa, du);
    if (J < 3) wg_wait<1>();
}
DEVI uint32_t ypos(int a, int b) { return (uint32_t)(b * 128 + (a ^ ((b & 3) << 3))) * 4; }

DEVI void expand_table(int ct, uint32_t sW, uint32_t sK, uint32_t sK2) {
#pragma unroll 1
    for (int i = ct; i < WTAB; i += 384) {
        const int c = (i >> 3) & 3, qd = (i & 7) | ((i >> 5) << 3);
        float k[5];
#pragma unroll
        for (int e = 0; e < 5; e++) {
            const int l = qd * 4 - 65 + e;
            const int hi = (int)__bfloat16_as_ushort(__float2bfloat16_rn((float)l)) - 17024;
            const uint32_t ko = (c * 648 + (l < 0 ? 644 : (l < 128 ? l : hi))) * 4;
            k[e] = __uint_as_float(lds32(sK + ko)) + __uint_as_float(lds32(sK2 + ko));
        }
        asm volatile("st.shared.v4.b32 [%0], {%1,%2,%3,%4};" ::"r"(sW + (c * WTAB + qd * 4) * 4), "r"(pack_bf16(k[1], k[0])),
                     "r"(pack_bf16(k[2], k[1])), "r"(pack_bf16(k[3], k[2])), "r"(pack_bf16(k[4], k[3])) : "memory");
    }
}

__global__ void __cluster_dims__(2, 1, 1) __launch_bounds__(512, 1)
outproj_kernel(const __grid_constant__ CUtensorMap tm_ctx, const __grid_constant__ CUtensorMap tm_wo,
               const __grid_constant__ CUtensorMap tm_out, const __grid_constant__ CUtensorMap tm_u, SsmParams sp, bf16* __restrict__ out) {
    extern __shared__ uint8_t smem_raw[];
    const uint32_t sb = (smem_u32(smem_raw) + 1023) & ~1023u;
    const uint32_t sX = sb + OP_NS * 32768, sW = sX + 32768, sU = sW + 4 * WTAB * 4, sK = sU + 4 * OP_UCH, bars = sK + 4 * 648 * 4;
    const uint32_t full = bars, empty = bars + 64, xfull = bars + 128, wfull = bars + 136, xfree = bars + 144;
    const int tid = threadIdx.x, warp = tid >> 5, lane = tid & 31, wg = tid >> 7;
    const uint32_t rank = cluster_rank();
    const uint32_t kr = rank;
    const int cl = blockIdx.x >> 1;
    const int m0 = (cl >> 2) * 128, n0 = (cl & 3) * 128, k0 = kr * 2048;
    STAMP(blockIdx.x == 10 && tid == 0, 1000);
    uint32_t praw[9];
    ssm_kgen_load(sp, blockIdx.x * 4 + (warp & 3), wg, lane, praw);
    if (tid == 0) {
        for (int i = 0; i < OP_NS; i++) { mbar_init(full + 8 * i, 1); mbar_init(empty + 8 * i, 8); }
        mbar_init(xfull, 1);
        mbar_init(wfull, 1);
        mbar_init(xfree, 1);
        fence_barrier_init();
        mbar_expect_tx(wfull, 32768);
        for (int i = 0; i < 8; i++) tma_load_2d(sX + i * 4096, &tm_u, cl * 8, i * 256, wfull);
    }
    for (int i = tid; i < 648; i += 512) asm volatile("st.shared.v4.b32 [%0], {%1,%1,%1,%1};" ::"r"(sK + i * 16), "r"(0) : "memory");
    __syncthreads();
    cluster_arrive();
    if (wg == 3) {
        reg_dec<40>();
        cluster_wait();
        if (tid == 384) {
            mbar_expect_tx(xfull, 32768);
            for (int it = 0; it < OP_NS; it++) {
                const uint32_t dst = sb + it * 32768, fb = full + 8 * it;
                mbar_expect_tx(fb, 32768);
                tma_load_2d(dst + 16384, &tm_wo, n0, k0 + it * 64, fb);
                tma_load_2d(dst + 24576, &tm_wo, n0 + 64, k0 + it * 64, fb);
            }
            pdl_wait();
            STAMP(blockIdx.x == 10, 1005);
            for (int it = 0; it < 32; it++) {
                const int st = it & (OP_NS - 1);
                const uint32_t dst = sb + st * 32768, fb = full + 8 * st;
                if (it >= OP_NS) {
                    mbar_wait(empty + 8 * st, ((it / OP_NS) & 1) ^ 1);
                    mbar_expect_tx(fb, 32768);
                    tma_load_2d(dst + 16384, &tm_wo, n0, k0 + it * 64, fb);
                    tma_load_2d(dst + 24576, &tm_wo, n0 + 64, k0 + it * 64, fb);
                }
                tma_load_2d(dst, &tm_ctx, k0 + it * 64, m0, fb);
                tma_load_2d(dst + 8192, &tm_ctx, k0 + it * 64, m0 + 64, fb);
            }
        }
        __syncwarp();
    } else {
      const int ct = tid & 127, wq = warp & 3;
      ssm_kgen_warp(praw, lane, (wg == 2 ? sX : sK) + wq * 648 * 4, wg == 2, [&]() { if (wg == 2) {
        for (int i = ct; i < 8 * 32; i += 128) {
            const uint32_t a = sU + (i >> 5) * OP_ULD + (128 + (i & 31)) * 16;
            asm volatile("st.shared.v4.b32 [%0], {%1,%1,%1,%1};" ::"r"(a), "r"(0) : "memory");
        }
        const bool mine = ((lane >> 2) & 1) == (int)rank;
        const uint32_t ub = sU + (lane & 3) * OP_UCH + ((lane >> 3) & 1) * OP_ULD + (127 - 2 * wq - (lane >> 4)) * 16;
        mbar_wait(wfull, 0);
#pragma unroll 4
        for (int i = 0; i < 16; i++) {
            uint32_t r0, r1, r2, r3;
            asm volatile("ldmatrix.sync.aligned.m8n8.x4.trans.shared.b16 {%0,%1,%2,%3}, [%4];"
                         : "=r"(r0), "=r"(r1), "=r"(r2), "=r"(r3) : "r"(sX + (i * 128 + ct) * 16) : "memory");
            asm volatile("stmatrix.sync.aligned.m8n8.x4.shared.b16 [%0], {%1,%2,%3,%4};"
                         ::"r"(mine ? ub - i * 128 : sW + lane * 16), "r"(r0), "r"(r1), "r"(r2), "r"(r3) : "memory");
        }
        fence_proxy_async();
        named_sync(5, 128);
        STAMP(blockIdx.x == 10 && ct == 0, 1001);
      } });
      cluster_wait();
      named_sync(3, 384);
      STAMP(blockIdx.x == 10 && tid == 257, 1002);
      expand_table(tid, sW, sK, sX);
      if (wg == 2) {
        reg_inc<216>();
        const int g = lane >> 2, t = lane & 3;
        const int d0 = blockIdx.x * 4;
        const uint2 dsk = __ldg(reinterpret_cast<const uint2*>(sp.dskip + d0));
        named_sync(4, 384);
        if (tid == 256) mbar_arrive_cluster(xfree, rank ^ 1);
        uint32_t res[16][2];
        STAMP(blockIdx.x == 10 && ct == 0, 1003);
#pragma unroll 1
        for (int c = 0; c < 4; c++) {
            float acc[64];
            uint32_t fa[16], fb[16];
#pragma unroll
            for (int i = 0; i < 64; i++) acc[i] = 0.f;
            const uint32_t wa = sW + (c * WTAB + 64 + 16 * wq + g - 2 * t) * 4;
            const uint64_t du = make_desc(sU + c * OP_UCH, OP_ULD, 128, 0);
            conv_group<0>(acc, fa, fb, wa, du);
            conv_group<1>(acc, fa, fb, wa, du);
            conv_group<2>(acc, fa, fb, wa, du);
            conv_group<3>(acc, fa, fb, wa, du);
            named_sync(5, 128);
            wg_wait<0>();
            const uint32_t yb = (wq & 1) ? sW + c * WTAB * 4 : sK;
            const bool skip0 = wq >= 2 && t == 0;
            if (wq >= 2) {
                named_sync(6, 128);
#pragma unroll
                for (int hf = 0; hf < 2; hf++) {
                    float2 v[16];
#pragma unroll
                    for (int i = 0; i < 16; i++)
                        asm volatile("ld.shared.v2.f32 {%0,%1}, [%2];" : "=f"(v[i].x), "=f"(v[i].y)
                                     : "r"(yb + ypos((128 - 8 * (8 * hf + (i >> 1)) - 2 * t) & 127, g + 8 * (i & 1))));
#pragma unroll
                    for (int i = 0; i < 16; i++) { acc[32 * hf + 2 * i] += v[i].y; acc[32 * hf + 2 * i + 1] += v[i].x; }
                }
            }
#pragma unroll
            for (int i = 0; i < 32; i++) {
                const uint32_t p = yb + ypos(126 - 8 * (i >> 1) - 2 * t + (wq & 2), g + 8 * (i & 1));
                if (i >= 2 || !skip0) asm volatile("st.shared.v2.f32 [%0], {%1,%2};" ::"r"(p), "f"(acc[2 * i + 1]), "f"(acc[2 * i]) : "memory");
            }
            if (wq < 2) named_arrive(6, 128);
            named_sync(5, 128);
            const uint32_t dw = (c & 2) ? dsk.y : dsk.x;
            const float D = (c & 1) ? bhi(dw) : blo(dw);
            const int yb2 = (lane >> 3) + 4 * wq;
#pragma unroll
            for (int i = 0; i < 16; i++) {
                const int a = 8 * i + (lane & 7);
                float y = __uint_as_float(lds32(sW + c * WTAB * 4 + ypos((a - 1) & 127, yb2)));
                y = __uint_as_float(lds32(sK + ypos(a, yb2))) + (a == 0 ? 0.f : y);
                const float u = __uint_as_float(lds16(sU + c * OP_UCH + (wq >> 1) * OP_ULD + (127 - a) * 16 + (yb2 & 7) * 2) << 16);
                const uint32_t o = __bfloat16_as_ushort(__float2bfloat16_rn(rbf(y) + rbf(u * D)));
                res[i][0] = __byte_perm(res[i][0], res[i][1], 0x5432); res[i][1] = __byte_perm(res[i][1], o, 0x5432);
            }
        }
        STAMP(blockIdx.x == 10 && ct == 0, 1004);
        const int grp = blockIdx.x >> 2, me = blockIdx.x & 3;
#pragma unroll
        for (int i = 0; i < 8; i++)
            __stcg(g_y + (((grp * 4 + (i >> 1)) * 4 + me) * 2 + (i & 1)) * 128 + ct,
                   make_uint4(res[2 * i][0], res[2 * i][1], res[2 * i + 1][0], res[2 * i + 1][1]));
        named_sync(5, 128);
        if (ct == 0) {
            __threadfence();
            const unsigned int target = (atomicAdd(g_ycnt + grp, 1u) & ~3u) + 4u;
            uint32_t t0, t1, v;
            asm volatile("mov.u32 %0, %%globaltimer_lo;" : "=r"(t0));
            do {
                asm volatile("ld.acquire.gpu.global.u32 %0, [%1];" : "=r"(v) : "l"(g_ycnt + grp) : "memory");
                asm volatile("mov.u32 %0, %%globaltimer_lo;" : "=r"(t1));
            } while ((int)(v - target) < 0 && t1 - t0 < 4000000u);
        }
        named_sync(5, 128);
        uint4 y[8];
#pragma unroll
        for (int i = 0; i < 8; i++)
            y[i] = __ldcg(g_y + ((blockIdx.x * 4 + 2 * (t & 1) + ((i >> 1) & 1)) * 2 + (i & 1)) * 128 + (ct & ~1) + (i >> 2));
#pragma unroll
        for (int i = 0; i < 8; i++) {
            const int row = 128 * (4 * me + (i & 3)) + 16 * ((lane & 6) + (i >> 2)) + 4 * wq + (lane >> 3);
            const uint4 p = y[(i & 4) + ((i >> 1) & 1)], q = y[(i & 4) + 2 + ((i >> 1) & 1)];
            *reinterpret_cast<uint4*>(out + (size_t)row * 1024 + 512 + grp * 16 + (t & 1) * 8) =
                (i & 1) ? make_uint4(p.z, p.w, q.z, q.w) : make_uint4(p.x, p.y, q.x, q.y);
        }
      } else {
        named_arrive(4, 384);
        float acc[64];
#pragma unroll 1
        for (int it = 0; it < 32; it++) {
            const int st = it & (OP_NS - 1);
            mbar_wait(full + 8 * st, (it / OP_NS) & 1);
            STAMP(blockIdx.x == 10 && tid == 0, 1009 + it);
            wg_fence();
            const uint32_t base = sb + st * 32768;
            const uint64_t da = desc_kmajor(base + wg * 8192), db = desc_mnmajor(base + 16384, 8192);
#pragma unroll
            for (int k = 0; k < 4; k++) wgmma_ss128<1>(acc, da + k * 2, db + k * 128, (it | k) != 0);
            wg_commit();
            if (it > 0 && it + OP_NS - 1 < 32) {
                wg_wait<1>();
                if (lane == 0) mbar_arrive(empty + 8 * ((it - 1) & (OP_NS - 1)));
            }
        }
        wg_wait<0>();
        mbar_wait(xfree, 0);
        uint32_t peer, pbar;
        asm volatile("mapa.shared::cluster.u32 %0, %1, %2;" : "=r"(peer) : "r"(sX + tid * 16), "r"(rank ^ 1));
        asm volatile("mapa.shared::cluster.u32 %0, %1, %2;" : "=r"(pbar) : "r"(xfull), "r"(rank ^ 1));
#pragma unroll
        for (int i = 0; i < 8; i++) {
            const float* s = acc + 4 * i;
            const float a = kr ? s[0] : s[32], b = kr ? s[1] : s[33], c = kr ? s[2] : s[34], d = kr ? s[3] : s[35];
            asm volatile("st.async.weak.shared::cluster.mbarrier::complete_tx::bytes.v4.f32 [%0], {%1,%2,%3,%4}, [%5];"
                         ::"r"(peer + i * 4096), "f"(a), "f"(b), "f"(c), "f"(d), "r"(pbar) : "memory");
        }
        STAMP(blockIdx.x == 10 && tid == 0, 1006);
        mbar_wait(xfull, 0);
        STAMP(blockIdx.x == 10 && tid == 0, 1007);
        float r[32];
#pragma unroll
        for (int i = 0; i < 8; i++) {
            float a, b, c, d;
            asm volatile("ld.shared.v4.f32 {%0,%1,%2,%3}, [%4];" : "=f"(a), "=f"(b), "=f"(c), "=f"(d) : "r"(sX + tid * 16 + i * 4096));
            const float* s = acc + 4 * i;
            r[4 * i] = a + (kr ? s[32] : s[0]); r[4 * i + 1] = b + (kr ? s[33] : s[1]);
            r[4 * i + 2] = c + (kr ? s[34] : s[2]); r[4 * i + 3] = d + (kr ? s[35] : s[3]);
        }
        const uint32_t stg = sb + wg * 8192;
        store_slab64(stg, (warp & 3) * 16, r, 1.f, 1.f, lane);
        fence_proxy_async();
        named_sync(1 + wg, 128);
        if ((tid & 127) == 0) {
            tma_store_2d(&tm_out, stg, n0 + kr * 64, m0 + wg * 64);
            bulk_commit();
            bulk_wait<0>();
            STAMP(blockIdx.x == 10 && tid == 0, 1008);
        }
      }
    }
}

typedef CUresult (*EncodeFn)(CUtensorMap*, CUtensorMapDataType, cuuint32_t, void*, const cuuint64_t*, const cuuint64_t*,
                             const cuuint32_t*, const cuuint32_t*, CUtensorMapInterleave, CUtensorMapSwizzle,
                             CUtensorMapL2promotion, CUtensorMapFloatOOBfill);

static void make_map(EncodeFn fn, CUtensorMap* m, const void* p, uint64_t cols, uint64_t rows, uint32_t box_rows) {
    cuuint64_t dims[2] = {cols, rows};
    cuuint64_t strides[1] = {cols * 2};
    cuuint32_t box[2] = {64, box_rows};
    cuuint32_t es[2] = {1, 1};
    fn(m, CU_TENSOR_MAP_DATA_TYPE_BFLOAT16, 2, const_cast<void*>(p), dims, strides, box, es, CU_TENSOR_MAP_INTERLEAVE_NONE,
       CU_TENSOR_MAP_SWIZZLE_128B, CU_TENSOR_MAP_L2_PROMOTION_L2_256B, CU_TENSOR_MAP_FLOAT_OOB_FILL_NONE);
}

extern "C" void kernel_launch(void* const* d_in, const int* in_sizes, int n_in, void* d_out, int out_size) {
    void* fp = nullptr;
    cudaDriverEntryPointQueryResult qr;
    cudaGetDriverEntryPoint("cuTensorMapEncodeTiled", &fp, cudaEnableDefault, &qr);
    EncodeFn fn = (EncodeFn)fp;
    void *p_kv, *p_ctx;
    cudaGetSymbolAddress(&p_kv, g_kv);
    cudaGetSymbolAddress(&p_ctx, g_ctx);
    CUtensorMap tm_kv_st, tm_x, tm_c, tm_wq, tm_wk, tm_wv, tm_wo, tm_kv, tm_ctx, tm_out;
    make_map(fn, &tm_x, d_in[0], DM, SEQ, 128);
    make_map(fn, &tm_c, d_in[1], DM, SEQ, 128);
    make_map(fn, &tm_wq, d_in[2], HDALL, DM, 64);
    make_map(fn, &tm_wk, d_in[3], HDALL, DM, 64);
    make_map(fn, &tm_wv, d_in[4], HDALL, DM, 64);
    make_map(fn, &tm_wo, d_in[5], DM, HDALL, 64);
    make_map(fn, &tm_kv, p_kv, 2 * HDALL, SEQ, 128);
    make_map(fn, &tm_kv_st, p_kv, 2 * HDALL, SEQ, 64);
    make_map(fn, &tm_ctx, p_ctx, HDALL, SEQ, 64);
    make_map(fn, &tm_out, d_out, 1024, SEQ, 64);
    CUtensorMap tm_u;
    {
        cuuint64_t dims[2] = {512, 2048}, strides[1] = {1024};
        cuuint32_t box[2] = {8, 256}, es[2] = {1, 1};
        fn(&tm_u, CU_TENSOR_MAP_DATA_TYPE_BFLOAT16, 2, d_in[6], dims, strides, box, es, CU_TENSOR_MAP_INTERLEAVE_NONE,
           CU_TENSOR_MAP_SWIZZLE_NONE, CU_TENSOR_MAP_L2_PROMOTION_NONE, CU_TENSOR_MAP_FLOAT_OOB_FILL_NONE);
    }
    SsmParams sp;
    sp.u = (const bf16*)d_in[6]; sp.lar = (const bf16*)d_in[7]; sp.aim = (const bf16*)d_in[8];
    sp.cre = (const bf16*)d_in[9]; sp.cim = (const bf16*)d_in[10]; sp.ldt = (const bf16*)d_in[11]; sp.dskip = (const bf16*)d_in[12];
    cudaFuncSetAttribute(gemm_kv_kernel, cudaFuncAttributeMaxDynamicSharedMemorySize, G1_SMEM);
    cudaFuncSetAttribute(attn_kernel, cudaFuncAttributeMaxDynamicSharedMemorySize, AT_SMEM);
    cudaFuncSetAttribute(outproj_kernel, cudaFuncAttributeMaxDynamicSharedMemorySize, OP_SMEM);
    cudaStream_t st = cudaStreamPerThread;
    gemm_kv_kernel<<<128, G1_THREADS, G1_SMEM, st>>>(tm_c, tm_wk, tm_wv, tm_kv_st, (const bf16*)d_in[0], (const bf16*)d_in[2]);
    cudaLaunchAttribute at[1];
    at[0].id = cudaLaunchAttributeProgrammaticStreamSerialization;
    at[0].val.programmaticStreamSerializationAllowed = 1;
    cudaLaunchConfig_t cfg = {};
    cfg.stream = st; cfg.attrs = at; cfg.numAttrs = 1;
    cfg.gridDim = dim3(132); cfg.blockDim = dim3(384); cfg.dynamicSmemBytes = AT_SMEM;
    cudaLaunchKernelEx(&cfg, attn_kernel, tm_x, tm_wq, tm_kv, tm_ctx, sp, (const bf16*)d_in[5]);
    cfg.gridDim = dim3(128); cfg.blockDim = dim3(512); cfg.dynamicSmemBytes = OP_SMEM;
    cudaLaunchKernelEx(&cfg, outproj_kernel, tm_ctx, tm_wo, tm_out, tm_u, sp, (bf16*)d_out);
}
```

```cpp
#include <cuda_runtime.h>
#include <cuda_bf16.h>
#include <cuda.h>
#include <stdint.h>

typedef __nv_bfloat16 bf16;

#define DEVI __device__ __forceinline__

constexpr int SEQ = 2048, DM = 512, NH = 32, HD = 128, HDALL = NH * HD;
constexpr int SSM_D = 512, SSM_N = 128;
constexpr int WTAB = 2112;

__device__ bf16 g_kv[(size_t)SEQ * 2 * HDALL];
__device__ bf16 g_ctx[(size_t)SEQ * HDALL];
__device__ uint4 g_y[32 * 4 * 4 * 2 * 128];
__device__ unsigned int g_ycnt[32];
__device__ unsigned int g_sched;

#define STAMP(cond, i)
DEVI uint32_t smem_u32(const void* p) { return (uint32_t)__cvta_generic_to_shared(p); }
DEVI void mbar_init(uint32_t a, uint32_t cnt) { asm volatile("mbarrier.init.shared::cta.b64 [%0], %1;" ::"r"(a), "r"(cnt)); }
DEVI void mbar_expect_tx(uint32_t a, uint32_t bytes) {
    asm volatile("mbarrier.arrive.expect_tx.shared::cta.b64 _, [%0], %1;" ::"r"(a), "r"(bytes) : "memory");
}
DEVI void mbar_arrive(uint32_t a) { asm volatile("mbarrier.arrive.shared::cta.b64 _, [%0];" ::"r"(a) : "memory"); }
DEVI void mbar_arrive_cluster(uint32_t a, uint32_t cta) {
    asm volatile("{\n.reg .b32 r;\nmapa.shared::cluster.u32 r, %0, %1;\n"
                 "mbarrier.arrive.shared::cluster.b64 _, [r];\n}" ::"r"(a), "r"(cta) : "memory");
}
#define MBAR_WAIT_ASM(OP)                                                                              \
    asm volatile("{\n.reg .pred p, q;\n.reg .u32 t0, t1;\n" OP " p, [%0], %1;\n@p bra D_%=;\n"         \
                 "mov.u32 t0, %%globaltimer_lo;\nW_%=:\n" OP " p, [%0], %1;\n"                         \
                 "mov.u32 t1, %%globaltimer_lo;\nsub.u32 t1, t1, t0;\n"                                \
                 "setp.gt.or.u32 q, t1, 4000000, p;\n@!q bra W_%=;\nD_%=:\n}" ::"r"(a), "r"(parity) : "memory")
DEVI void mbar_wait(uint32_t a, uint32_t parity) { MBAR_WAIT_ASM("mbarrier.try_wait.parity.shared::cta.b64"); }
DEVI void mbar_wait_cluster(uint32_t a, uint32_t parity) { MBAR_WAIT_ASM("mbarrier.try_wait.parity.acquire.cluster.shared::cta.b64"); }
DEVI void fence_barrier_init() { asm volatile("fence.mbarrier_init.release.cluster;" ::: "memory"); }
DEVI void fence_proxy_async() { asm volatile("fence.proxy.async.shared::cta;" ::: "memory"); }
DEVI void cluster_sync_all() {
    asm volatile("barrier.cluster.arrive.relaxed.aligned;\nbarrier.cluster.wait.aligned;" ::: "memory");
}
DEVI void cluster_arrive() { asm volatile("barrier.cluster.arrive.relaxed.aligned;" ::: "memory"); }
DEVI void cluster_wait() { asm volatile("barrier.cluster.wait.aligned;" ::: "memory"); }
DEVI uint32_t cluster_rank() { uint32_t r; asm volatile("mov.u32 %0, %%cluster_ctarank;" : "=r"(r)); return r; }
DEVI void tma_load_2d(uint32_t dst, const CUtensorMap* m, int c0, int c1, uint32_t bar) {
    asm volatile("cp.async.bulk.tensor.2d.shared::cluster.global.mbarrier::complete_tx::bytes [%0], [%1, {%3, %4}], [%2];"
                 ::"r"(dst), "l"(m), "r"(bar), "r"(c0), "r"(c1) : "memory");
}
DEVI void tma_load_2d_mc(uint32_t dst, const CUtensorMap* m, int c0, int c1, uint32_t bar, uint16_t mask) {
    asm volatile("cp.async.bulk.tensor.2d.shared::cluster.global.mbarrier::complete_tx::bytes.multicast::cluster [%0], [%1, {%3, %4}], [%2], %5;"
                 ::"r"(dst), "l"(m), "r"(bar), "r"(c0), "r"(c1), "h"(mask) : "memory");
}
DEVI void tma_prefetch_2d(const CUtensorMap* m, int c0, int c1) {
    asm volatile("cp.async.bulk.prefetch.tensor.2d.L2.global [%0, {%1, %2}];" ::"l"(m), "r"(c0), "r"(c1) : "memory");
}
DEVI void tma_store_2d(const CUtensorMap* m, uint32_t src, int c0, int c1) {
    asm volatile("cp.async.bulk.tensor.2d.global.shared::cta.bulk_group [%0, {%2, %3}], [%1];"
                 ::"l"(m), "r"(src), "r"(c0), "r"(c1) : "memory");
}
DEVI void bulk_load(uint32_t dst, const void* src, uint32_t bytes, uint32_t bar) {
    asm volatile("cp.async.bulk.shared::cluster.global.mbarrier::complete_tx::bytes [%0], [%1], %2, [%3];"
                 ::"r"(dst), "l"(src), "r"(bytes), "r"(bar) : "memory");
}
DEVI void bulk_prefetch(const void* src, uint32_t bytes) {
    asm volatile("cp.async.bulk.prefetch.L2.global [%0], %1;" ::"l"(src), "r"(bytes) : "memory");
}
DEVI void bulk_commit() { asm volatile("cp.async.bulk.commit_group;" ::: "memory"); }
template <int N> DEVI void bulk_wait_read() { asm volatile("cp.async.bulk.wait_group.read %0;" ::"n"(N) : "memory"); }
template <int N> DEVI void bulk_wait() { asm volatile("cp.async.bulk.wait_group %0;" ::"n"(N) : "memory"); }
DEVI void prefetch_tmap(const CUtensorMap* m) { asm volatile("prefetch.tensormap [%0];" ::"l"(m) : "memory"); }
DEVI void named_sync(int id, int n) { asm volatile("bar.sync %0, %1;" ::"r"(id), "r"(n) : "memory"); }
DEVI void named_arrive(int id, int n) { asm volatile("bar.arrive %0, %1;" ::"r"(id), "r"(n) : "memory"); }
DEVI void pdl_wait() { asm volatile("griddepcontrol.wait;" ::: "memory"); }
DEVI void pdl_launch() { asm volatile("griddepcontrol.launch_dependents;" ::: "memory"); }
template <int R> DEVI void reg_inc() { asm volatile("setmaxnreg.inc.sync.aligned.u32 %0;" ::"n"(R)); }
template <int R> DEVI void reg_dec() { asm volatile("setmaxnreg.dec.sync.aligned.u32 %0;" ::"n"(R)); }

DEVI void wg_fence() { asm volatile("wgmma.fence.sync.aligned;" ::: "memory"); }
DEVI void wg_commit() { asm volatile("wgmma.commit_group.sync.aligned;" ::: "memory"); }
template <int N> DEVI void wg_wait() { asm volatile("wgmma.wait_group.sync.aligned %0;" ::"n"(N) : "memory"); }

DEVI uint64_t make_desc(uint32_t addr, uint32_t lbo, uint32_t sbo, uint32_t swz) {
    return (uint64_t)((addr & 0x3FFFF) >> 4) | ((uint64_t)(lbo >> 4) << 16) | ((uint64_t)(sbo >> 4) << 32) | ((uint64_t)swz << 62);
}
DEVI uint64_t desc_kmajor(uint32_t addr) { return make_desc(addr, 16, 1024, 1); }
DEVI uint64_t desc_mnmajor(uint32_t addr, uint32_t lbo) { return make_desc(addr, lbo, 1024, 1); }

#define ACC8(d, o) "+f"(d[o + 0]), "+f"(d[o + 1]), "+f"(d[o + 2]), "+f"(d[o + 3]), "+f"(d[o + 4]), "+f"(d[o + 5]), "+f"(d[o + 6]), "+f"(d[o + 7])
#define ACC64(d) ACC8(d, 0), ACC8(d, 8), ACC8(d, 16), ACC8(d, 24), ACC8(d, 32), ACC8(d, 40), ACC8(d, 48), ACC8(d, 56)
#define R64 "{%0,%1,%2,%3,%4,%5,%6,%7,%8,%9,%10,%11,%12,%13,%14,%15,%16,%17,%18,%19,%20,%21,%22,%23,%24,%25,%26,%27,%28,%29,%30,%31," \
            "%32,%33,%34,%35,%36,%37,%38,%39,%40,%41,%42,%43,%44,%45,%46,%47,%48,%49,%50,%51,%52,%53,%54,%55,%56,%57,%58,%59,%60,%61,%62,%63}"

template <int TB> DEVI void wgmma_ss128(float* d, uint64_t da, uint64_t db, int acc) {
    asm volatile("{\n.reg .pred p;\nsetp.ne.b32 p, %66, 0;\n"
                 "wgmma.mma_async.sync.aligned.m64n128k16.f32.bf16.bf16 " R64 ", %64, %65, p, 1, 1, 0, %67;\n}"
                 : ACC64(d) : "l"(da), "l"(db), "r"(acc), "n"(TB));
}
template <int TB> DEVI void wgmma_rs128(float* d, const uint32_t* a, uint64_t db, int acc) {
    asm volatile("{\n.reg .pred p;\nsetp.ne.b32 p, %69, 0;\n"
                 "wgmma.mma_async.sync.aligned.m64n128k16.f32.bf16.bf16 " R64 ", {%64,%65,%66,%67}, %68, p, 1, 1, %70;\n}"
                 : ACC64(d) : "r"(a[0]), "r"(a[1]), "r"(a[2]), "r"(a[3]), "l"(db), "r"(acc), "n"(TB));
}
DEVI uint32_t pack_bf16(float lo, float hi) {
    uint32_t r;
    asm("cvt.rn.bf16x2.f32 %0, %1, %2;" : "=r"(r) : "f"(hi), "f"(lo));
    return r;
}
DEVI void stmatrix_x4(uint32_t addr, uint32_t r0, uint32_t r1, uint32_t r2, uint32_t r3) {
    asm volatile("stmatrix.sync.aligned.m8n8.x4.shared.b16 [%0], {%1,%2,%3,%4};" ::"r"(addr), "r"(r0), "r"(r1), "r"(r2), "r"(r3) : "memory");
}
DEVI float ex2(float x) { float y; asm("ex2.approx.ftz.f32 %0, %1;" : "=f"(y) : "f"(x)); return y; }

DEVI void store_slab64(uint32_t base, int row0, const float* d, float s0, float s1, int lane) {
    int mi = lane >> 3, r = lane & 7;
    int row = row0 + (mi & 1) * 8 + r;
#pragma unroll
    for (int j = 0; j < 8; j += 2) {
        uint32_t r0 = pack_bf16(d[4 * j + 0] * s0, d[4 * j + 1] * s0);
        uint32_t r1 = pack_bf16(d[4 * j + 2] * s1, d[4 * j + 3] * s1);
        uint32_t r2 = pack_bf16(d[4 * j + 4] * s0, d[4 * j + 5] * s0);
        uint32_t r3 = pack_bf16(d[4 * j + 6] * s1, d[4 * j + 7] * s1);
        int chunk = j + (mi >> 1);
        stmatrix_x4(base + row * 128 + ((chunk ^ (row & 7)) << 4), r0, r1, r2, r3);
    }
}
struct cf { float x, y; };
DEVI cf cmul(cf a, cf b) { cf r; r.x = fmaf(a.x, b.x, -a.y * b.y); r.y = fmaf(a.x, b.y, a.y * b.x); return r; }
DEVI cf csq(cf a) { cf r; r.x = fmaf(a.x, a.x, -a.y * a.y); r.y = (a.x + a.x) * a.y; return r; }
DEVI cf cexp_(float re, float im) {
    float m = __expf(re), s, c;
    __sincosf(im, &s, &c);
    cf r; r.x = m * c; r.y = m * s; return r;
}
DEVI uint32_t h2(cf v) { uint32_t r; asm("cvt.rn.f16x2.f32 %0, %1, %2;" : "=r"(r) : "f"(v.y), "f"(v.x)); return r; }
DEVI uint32_t h2c(cf v) { uint32_t r; asm("cvt.rn.f16x2.f32 %0, %1, %2;" : "=r"(r) : "f"(-v.y), "f"(v.x)); return r; }
DEVI void mma_group(float (*c)[4], const uint32_t (*a)[4], const uint32_t (*b)[2]) {
    asm volatile(
        "mma.sync.aligned.m16n8k16.row.col.f32.f16.f16.f32 {%0,%1,%2,%3}, {%20,%21,%22,%23}, {%40,%41}, {%0,%1,%2,%3};\n"
        "mma.sync.aligned.m16n8k16.row.col.f32.f16.f16.f32 {%4,%5,%6,%7}, {%24,%25,%26,%27}, {%40,%41}, {%4,%5,%6,%7};\n"
        "mma.sync.aligned.m16n8k16.row.col.f32.f16.f16.f32 {%8,%9,%10,%11}, {%28,%29,%30,%31}, {%42,%43}, {%8,%9,%10,%11};\n"
        "mma.sync.aligned.m16n8k16.row.col.f32.f16.f16.f32 {%12,%13,%14,%15}, {%32,%33,%34,%35}, {%44,%45}, {%12,%13,%14,%15};\n"
        "mma.sync.aligned.m16n8k16.row.col.f32.f16.f16.f32 {%16,%17,%18,%19}, {%36,%37,%38,%39}, {%46,%47}, {%16,%17,%18,%19};\n"
        : "+f"(c[0][0]), "+f"(c[0][1]), "+f"(c[0][2]), "+f"(c[0][3]), "+f"(c[1][0]), "+f"(c[1][1]), "+f"(c[1][2]), "+f"(c[1][3]),
          "+f"(c[2][0]), "+f"(c[2][1]), "+f"(c[2][2]), "+f"(c[2][3]), "+f"(c[3][0]), "+f"(c[3][1]), "+f"(c[3][2]), "+f"(c[3][3]),
          "+f"(c[4][0]), "+f"(c[4][1]), "+f"(c[4][2]), "+f"(c[4][3])
        : "r"(a[0][0]), "r"(a[0][1]), "r"(a[0][2]), "r"(a[0][3]), "r"(a[1][0]), "r"(a[1][1]), "r"(a[1][2]), "r"(a[1][3]),
          "r"(a[2][0]), "r"(a[2][1]), "r"(a[2][2]), "r"(a[2][3]), "r"(a[3][0]), "r"(a[3][1]), "r"(a[3][2]), "r"(a[3][3]),
          "r"(a[4][0]), "r"(a[4][1]), "r"(a[4][2]), "r"(a[4][3]),
          "r"(b[0][0]), "r"(b[0][1]), "r"(b[1][0]), "r"(b[1][1]), "r"(b[2][0]), "r"(b[2][1]), "r"(b[3][0]), "r"(b[3][1]));
}
DEVI float bf2f(bf16 v) { return __bfloat162float(v); }
DEVI float rbf(float v) { return __bfloat162float(__float2bfloat16_rn(v)); }

struct SsmParams { const bf16 *lar, *aim, *cre, *cim, *ldt, *dskip, *u; };

DEVI int kp_index(int l) {
    int p = (int)rbf((float)l);
    return p < 256 ? p : (p < 512 ? 128 + (p >> 1) : (p < 1024 ? 256 + (p >> 2) : 384 + (p >> 3)));
}

DEVI void reds(uint32_t a, float v) { asm volatile("red.shared.add.f32 [%0], %1;" ::"r"(a), "f"(v) : "memory"); }
DEVI uint32_t ldg16(const bf16* p) { uint16_t v; asm volatile("ld.global.nc.u16 %0, [%1];" : "=h"(v) : "l"(p)); return v; }
DEVI void ssm_kgen_load(const SsmParams& P, int d, int half, int lane, uint32_t* r) {
#pragma unroll
    for (int q = 0; q < 2; q++) {
        const int n = d * SSM_N + 64 * half + 32 * q + lane;
        r[4 * q] = ldg16(P.lar + n); r[4 * q + 1] = ldg16(P.aim + n); r[4 * q + 2] = ldg16(P.cre + n); r[4 * q + 3] = ldg16(P.cim + n);
    }
    r[8] = ldg16(P.ldt + d);
}
DEVI void ssm_kgen_warp(const uint32_t* r, int lane, uint32_t kp) {
    float raw[9];
#pragma unroll
    for (int i = 0; i < 9; i++) raw[i] = __uint_as_float(r[i] << 16);
    const int g = lane >> 2, t = lane & 3;
    float ar[2], ai[2], cr[2], ci[2], gr[2], gi[2];
    const float dt = rbf(expf(raw[8]));
#pragma unroll
    for (int q = 0; q < 2; q++) {
        ar[q] = -rbf(expf(raw[4 * q])) * dt;
        ai[q] = raw[4 * q + 1] * dt;
        cr[q] = 2.f * (raw[4 * q + 2] * dt);
        ci[q] = 2.f * (raw[4 * q + 3] * dt);
        float m = expf(ar[q] * 64.f), sn, cs;
        sincosf(ai[q] * 64.f, &sn, &cs);
        gr[q] = m * cs; gi[q] = m * sn;
    }
    float cm = 0.f;
#pragma unroll
    for (int q = 0; q < 2; q++) cm = fmaxf(cm, fmaxf(fabsf(cr[q]), fabsf(ci[q])));
#pragma unroll
    for (int o = 16; o; o >>= 1) cm = fmaxf(cm, __shfl_xor_sync(~0u, cm, o));
    const int ex = min(max((int)(__float_as_uint(cm) >> 23), 1), 253);
    const float cs_dn = __uint_as_float((uint32_t)(254 - ex) << 23), cs_up = __uint_as_float((uint32_t)ex << 23);
    float acc[5][4];
#pragma unroll
    for (int s = 0; s < 5; s++) { acc[s][0] = acc[s][1] = acc[s][2] = acc[s][3] = 0.f; }
    float klast = 0.f;
    const float gf = (float)g;
#pragma unroll 1
    for (int g0 = 0; g0 < 8; g0 += 2) {
#pragma unroll
        for (int q = 0; q < 2; q++) {
            uint32_t fa[5][4], fb[4][2];
#pragma unroll
            for (int h = 0; h < 2; h++) {
                const int src = ((g0 + h) << 2) | t;
                const float a_r = __shfl_sync(~0u, ar[q], src), a_i = __shfl_sync(~0u, ai[q], src);
                cf C, G;
                C.x = __shfl_sync(~0u, cr[q], src) * cs_dn; C.y = __shfl_sync(~0u, ci[q], src) * cs_dn;
                G.x = __shfl_sync(~0u, gr[q], src); G.y = __shfl_sync(~0u, gi[q], src);
                cf E = cexp_(a_r * gf, a_i * gf);
                cf B = csq(csq(csq(E)));
                fb[0][h] = h2c(cmul(C, B));
                cf EG = cmul(E, G);
                fa[0][2 * h] = h2(E); fa[0][2 * h + 1] = h2(EG);
                cf G2 = csq(G);
                cf X = cmul(E, G2), Xh = cmul(EG, G2);
                fa[1][2 * h] = h2(X); fa[1][2 * h + 1] = h2(Xh);
#pragma unroll
                for (int s = 2; s < 5; s++) {
                    B = csq(B); X = csq(X); Xh = csq(Xh);
                    fb[s - 1][h] = h2c(cmul(C, B));
                    fa[s][2 * h] = h2(X); fa[s][2 * h + 1] = h2(Xh);
                }
                X = csq(X);
                klast += fmaf(C.x, X.x, -C.y * X.y);
            }
            mma_group(acc, fa, fb);
        }
    }
    klast += __shfl_xor_sync(~0u, klast, 1);
    klast += __shfl_xor_sync(~0u, klast, 2);
#pragma unroll
    for (int s = 0; s < 5; s++) {
        const uint32_t b = kp + (128 * s + g + 16 * t) * 4;
        reds(b, acc[s][0] * cs_up); reds(b + 32, acc[s][1] * cs_up); reds(b + 256, acc[s][2] * cs_up); reds(b + 288, acc[s][3] * cs_up);
    }
    if (lane == 0) reds(kp + 2560, klast * cs_up);
}

constexpr int G1_THREADS = 384;
constexpr int G1_NS = 11;
constexpr int G1_SMEM = G1_NS * 16384 + 32768 + 256 + 1024;

__global__ void __cluster_dims__(2, 1, 1) __launch_bounds__(G1_THREADS, 1)
gemm_kv_kernel(const __grid_constant__ CUtensorMap tm_c, const __grid_constant__ CUtensorMap tm_wk,
               const __grid_constant__ CUtensorMap tm_wv, const __grid_constant__ CUtensorMap tm_kv_st,
               const bf16* __restrict__ px, const bf16* __restrict__ pwq) {
    extern __shared__ uint8_t smem_raw[];
    const uint32_t sb = (smem_u32(smem_raw) + 1023) & ~1023u;
    const uint32_t sC = sb + G1_NS * 16384, bars = sC + 32768;
    const uint32_t full = bars, empty = bars + 128;
    const int tid = threadIdx.x, warp = tid >> 5, lane = tid & 31, wg = tid >> 7;
    const uint32_t rank = cluster_rank();
    const int cl = blockIdx.x >> 1;
    const int m0 = ((cl & 7) * 2 + rank) * 128;
    const int ng = cl >> 3;
    STAMP(blockIdx.x == 10 && tid == 0, 0);
    if (tid == 0) {
        for (int i = 0; i < G1_NS; i++) { mbar_init(full + 8 * i, 1); mbar_init(empty + 8 * i, 16); }
        fence_barrier_init();
        for (int it = 0; it < 8; it++) {
            mbar_expect_tx(full + 8 * it, 16384);
            tma_load_2d(sb + it * 16384, &tm_c, it * 64, m0, full + 8 * it);
        }
    }
    __syncthreads();
    cluster_sync_all();
    pdl_launch();
    if (wg == 2) {
        reg_dec<40>();
        if (tid == 256) {
            const CUtensorMap* tw = ng < 4 ? &tm_wk : &tm_wv;
            const int n0 = (ng & 3) * 1024 + rank * 64;
            int st = 8; uint32_t ph = 1;
            for (int it = 0; it < 64; it++) {
                mbar_wait(empty + 8 * st, ph);
                mbar_expect_tx(full + 8 * st, 16384);
                tma_load_2d_mc(sb + st * 16384 + rank * 8192, tw, n0 + (it >> 3) * 128, (it & 7) * 64, full + 8 * st, 3);
                if (it < 2) {
                    for (int j = 3 + it * 8 + (cl & 7); j < 19; j += 16) tma_prefetch_2d(tw, n0 + (j >> 3) * 128, (j & 7) * 64);
                }
                if (it >= 3 && it + 16 < 64 && (it & 7) == (cl & 7)) tma_prefetch_2d(tw, n0 + ((it + 16) >> 3) * 128, (it & 7) * 64);
                if (it == 24) bulk_prefetch(px + blockIdx.x * 8192, 16384);
                if (it == 32) bulk_prefetch(pwq + blockIdx.x * 16384, 32768);
                if (++st == G1_NS) { st = 0; ph ^= 1; }
            }
        }
        __syncwarp();
    } else {
        reg_inc<232>();
        uint32_t af[128];
        float acc[64];
        const int wq = warp & 3;
        const int row = wg * 64 + wq * 16 + (lane & 15);
        const uint32_t stg = sC + wg * 16384;
        int st = 8, pst = 0; uint32_t ph = 0;
#pragma unroll
        for (int kc = 0; kc < 8; kc++) {
            mbar_wait(full + 8 * kc, 0);
#pragma unroll
            for (int k = 0; k < 4; k++) {
                const uint32_t a = sb + kc * 16384 + row * 128 + (((2 * k + (lane >> 4)) ^ (row & 7)) << 4);
                uint32_t* f = af + kc * 16 + k * 4;
                asm volatile("ldmatrix.sync.aligned.m8n8.x4.shared.b16 {%0,%1,%2,%3}, [%4];"
                             : "=r"(f[0]), "=r"(f[1]), "=r"(f[2]), "=r"(f[3]) : "r"(a) : "memory");
            }
            __syncwarp();
            if (lane < 2) mbar_arrive_cluster(empty + 8 * kc, lane);
        }
#pragma unroll 1
        for (int t = 0; t < 8; t++) {
            if (wg == 1 || t > 0) named_sync(3 + wg, 256);
#pragma unroll
            for (int kc = 0; kc < 8; kc++) {
                mbar_wait(full + 8 * st, ph);
                STAMP(blockIdx.x == 10 && (tid & 127) == 0, 1 + wg * 96 + t * 12 + kc);
                wg_fence();
                const uint64_t db = desc_mnmajor(sb + st * 16384, 8192);
#pragma unroll
                for (int k = 0; k < 4; k++) wgmma_rs128<1>(acc, af + kc * 16 + k * 4, db + k * 128, (kc | k) != 0);
                wg_commit();
                if (kc == 3 && (wg == 0 || t < 7)) named_arrive(3 + (wg ^ 1), 256);
                if (kc > 0) {
                    wg_wait<1>();
                    if (lane < 2) mbar_arrive_cluster(empty + 8 * pst, lane);
                }
                pst = st;
                if (++st == G1_NS) { st = 0; ph ^= 1; }
            }
            if ((tid & 127) == 0) bulk_wait_read<0>();
            named_sync(1 + wg, 128);
            wg_wait<0>();
            STAMP(blockIdx.x == 10 && (tid & 127) == 0, 9 + wg * 96 + t * 12);
            if (lane < 2) mbar_arrive_cluster(empty + 8 * pst, lane);
            store_slab64(stg, wq * 16, acc, 1.f, 1.f, lane);
            store_slab64(stg + 8192, wq * 16, acc + 32, 1.f, 1.f, lane);
            fence_proxy_async();
            named_sync(1 + wg, 128);
            if ((tid & 127) == 0) {
                tma_store_2d(&tm_kv_st, stg, ng * 1024 + t * 128, m0 + wg * 64);
                tma_store_2d(&tm_kv_st, stg + 8192, ng * 1024 + t * 128 + 64, m0 + wg * 64);
                bulk_commit();
            }
            STAMP(blockIdx.x == 10 && (tid & 127) == 0, 10 + wg * 96 + t * 12);
        }
        if ((tid & 127) == 0) bulk_wait<0>();
        __syncwarp();
    }
    asm volatile("barrier.cluster.arrive.relaxed.aligned;\nbarrier.cluster.wait.aligned;" ::: "memory");
}
constexpr int AT_NS = 6;
constexpr int AT_SMEM = AT_NS * 32768 + 32768 + 256 + 1024;
constexpr int AT_ITEMS = 512;

DEVI uint32_t hmax2(uint32_t a, uint32_t b) { uint32_t r; asm("max.bf16x2 %0, %1, %2;" : "=r"(r) : "r"(a), "r"(b)); return r; }
DEVI uint32_t hmul2(uint32_t a, uint32_t b) { uint32_t r; asm("mul.rn.bf16x2 %0, %1, %2;" : "=r"(r) : "r"(a), "r"(b)); return r; }
DEVI uint32_t hfma2(uint32_t a, uint32_t b, uint32_t c) { uint32_t r; asm("fma.rn.bf16x2 %0, %1, %2, %3;" : "=r"(r) : "r"(a), "r"(b), "r"(c)); return r; }
DEVI float blo(uint32_t v) { return __uint_as_float(v << 16); }
DEVI float bhi(uint32_t v) { return __uint_as_float(v & 0xffff0000u); }

template <bool FIRST>
DEVI void softmax_tile(float* s, float& m0, float& m1, float& l0, float& l1, float& al0, float& al1) {
    const uint32_t HI = 0x3DB53DB5u;
    const uint32_t LO = 0x371E371Eu;
    const float L2E = 1.4426950408889634f;
    uint32_t x0 = 0xFF80FF80u, x1 = 0xFF80FF80u;
#pragma unroll
    for (int j = 0; j < 16; j++) {
        uint32_t a = pack_bf16(s[4 * j], s[4 * j + 1]), b = pack_bf16(s[4 * j + 2], s[4 * j + 3]);
        a = hfma2(a, HI, hmul2(a, LO));
        b = hfma2(b, HI, hmul2(b, LO));
        s[4 * j] = __uint_as_float(a); s[4 * j + 2] = __uint_as_float(b);
        x0 = hmax2(x0, a); x1 = hmax2(x1, b);
    }
    uint32_t x = hmax2(__byte_perm(x0, x1, 0x5410), __byte_perm(x0, x1, 0x7632));
    x = hmax2(x, __shfl_xor_sync(~0u, x, 1));
    x = hmax2(x, __shfl_xor_sync(~0u, x, 2));
    float n0 = blo(x), n1 = bhi(x);
    if (!FIRST) {
        n0 = fmaxf(n0, m0); n1 = fmaxf(n1, m1);
        al0 = ex2((m0 - n0) * L2E); al1 = ex2((m1 - n1) * L2E);
    }
    m0 = n0; m1 = n1;
    const float c0 = -n0 * L2E, c1 = -n1 * L2E;
    float s0 = 0.f, s1 = 0.f;
#pragma unroll
    for (int j = 0; j < 16; j++) {
        uint32_t a = __float_as_uint(s[4 * j]), b = __float_as_uint(s[4 * j + 2]);
        float e0 = ex2(fmaf(blo(a), L2E, c0)), e1 = ex2(fmaf(bhi(a), L2E, c0));
        float e2 = ex2(fmaf(blo(b), L2E, c1)), e3 = ex2(fmaf(bhi(b), L2E, c1));
        s0 += e0 + e1; s1 += e2 + e3;
        s[4 * j] = e0; s[4 * j + 1] = e1; s[4 * j + 2] = e2; s[4 * j + 3] = e3;
    }
    if (FIRST) { l0 = s0; l1 = s1; }
    else { l0 = fmaf(l0, al0, s0); l1 = fmaf(l1, al1, s1); }
}

struct Ring {
    int st; uint32_t ph;
    DEVI void next() { if (++st == AT_NS) { st = 0; ph ^= 1; } }
};

__global__ void __launch_bounds__(384, 1)
attn_kernel(const __grid_constant__ CUtensorMap tm_x, const __grid_constant__ CUtensorMap tm_wq,
            const __grid_constant__ CUtensorMap tm_kv, const __grid_constant__ CUtensorMap tm_ctx_st,
            const SsmParams sp, const bf16* __restrict__ pwo) {
    extern __shared__ uint8_t smem_raw[];
    const uint32_t sb = (smem_u32(smem_raw) + 1023) & ~1023u;
    const uint32_t sO = sb + AT_NS * 32768, bars = sO + 32768;
    const uint32_t full = bars, empty = bars + 64;
    volatile int* slots = reinterpret_cast<volatile int*>(smem_raw + (bars + 128 - smem_u32(smem_raw)));
    const int tid = threadIdx.x, warp = tid >> 5, lane = tid & 31, wg = tid >> 7;
    if (tid == 0) {
        for (int i = 0; i < AT_NS; i++) { mbar_init(full + 8 * i, 1); mbar_init(empty + 8 * i, 8); }
        fence_barrier_init();
    }
    __syncthreads();
    if (wg == 2) {
        reg_dec<24>();
        if (warp == 8 && lane == 0) {
            Ring r{0, 1};
            int n = 0;
            while (true) {
                int idx = (int)atomicInc(&g_sched, AT_ITEMS + gridDim.x - 1);
                if (idx >= AT_ITEMS - 128 && idx < AT_ITEMS) {
                    bulk_prefetch(sp.u + (idx - (AT_ITEMS - 128)) * 8192, 16384);
                    const int po = (idx - (AT_ITEMS - 128)) * 512;
                    bulk_prefetch(sp.lar + po, 1024); bulk_prefetch(sp.aim + po, 1024);
                    bulk_prefetch(sp.cre + po, 1024); bulk_prefetch(sp.cim + po, 1024);
                    if (po == 0) { bulk_prefetch(sp.ldt, 1024); bulk_prefetch(sp.dskip, 1024); }
                    bulk_prefetch(pwo + (idx - (AT_ITEMS - 128)) * 16384, 32768);
                }
                mbar_wait(empty + 8 * r.st, r.ph);
                if (idx >= AT_ITEMS) {
                    slots[n & 3] = -1;
                    mbar_arrive(full + 8 * r.st);
                    break;
                }
                slots[n & 3] = idx;
                const int qi = 15 - (idx >> 5), h = idx & 31;
                for (int kc = 0; kc < 8; kc++) {
                    if (kc) mbar_wait(empty + 8 * r.st, r.ph);
                    const uint32_t fb = full + 8 * r.st, dst = sb + r.st * 32768;
                    mbar_expect_tx(fb, 32768);
                    tma_load_2d(dst, &tm_x, kc * 64, qi * 128, fb);
                    tma_load_2d(dst + 16384, &tm_wq, h * 128, kc * 64, fb);
                    tma_load_2d(dst + 24576, &tm_wq, h * 128 + 64, kc * 64, fb);
                    r.next();
                }
                if (n == 0) { pdl_wait(); pdl_launch(); }
                for (int j = qi; j >= -1; j--) {
#pragma unroll
                    for (int v = 0; v < 2; v++) {
                        const int jj = j + v;
                        if (jj < 0 || jj > qi || (v == 0 && j < 0)) continue;
                        mbar_wait(empty + 8 * r.st, r.ph);
                        const uint32_t fb = full + 8 * r.st, dst = sb + r.st * 32768;
                        mbar_expect_tx(fb, 32768);
                        tma_load_2d(dst, &tm_kv, v * HDALL + h * 128, jj * 128, fb);
                        tma_load_2d(dst + 16384, &tm_kv, v * HDALL + h * 128 + 64, jj * 128, fb);
                        r.next();
                    }
                }
                n++;
            }
            if (n == 0) { pdl_wait(); pdl_launch(); }
        }
    } else {
        reg_inc<240>();
        Ring r{0, 0};
        float o[64], s[64];
        uint32_t qf[32], pa[32];
        const int g = lane >> 2, t = lane & 3, wq = warp & 3;
        const uint32_t stg = sO + wg * 16384;
        if (wg == 1) named_arrive(3, 256);
        for (int n = 0;; n++) {
            mbar_wait(full + 8 * r.st, r.ph);
            const int idx = slots[n & 3];
            if (idx < 0) break;
            const int qi = 15 - (idx >> 5), h = idx & 31;
#pragma unroll 1
            for (int kc = 0; kc < 8; kc++) {
                if (kc) mbar_wait(full + 8 * r.st, r.ph);
                wg_fence();
                const uint32_t base = sb + r.st * 32768;
                const uint64_t da = desc_kmajor(base + wg * 8192), db = desc_mnmajor(base + 16384, 8192);
#pragma unroll
                for (int k = 0; k < 4; k++) wgmma_ss128<1>(s, da + k * 2, db + k * 128, (kc | k) != 0);
                wg_commit();
                if (kc) {
                    wg_wait<1>();
                    if (lane == 0) mbar_arrive(empty + 8 * (r.st == 0 ? AT_NS - 1 : r.st - 1));
                }
                r.next();
            }
            wg_wait<0>();
            if (lane == 0) mbar_arrive(empty + 8 * (r.st == 0 ? AT_NS - 1 : r.st - 1));
#pragma unroll
            for (int i = 0; i < 32; i++) qf[i] = pack_bf16(s[2 * i], s[2 * i + 1]);
            float m0, m1, l0, l1, al0, al1;
            auto issue_qk = [&]() {
                mbar_wait(full + 8 * r.st, r.ph);
                wg_fence();
                const uint64_t db = desc_kmajor(sb + r.st * 32768);
#pragma unroll
                for (int k = 0; k < 8; k++) wgmma_rs128<0>(s, qf + 4 * k, db + (k >> 2) * 1024 + (k & 3) * 2, k != 0);
                wg_commit();
            };
            auto issue_pv = [&](const uint32_t* p, int st, uint32_t ph, int acc) {
                mbar_wait(full + 8 * st, ph);
                wg_fence();
                const uint64_t db = desc_mnmajor(sb + st * 32768, 16384);
#pragma unroll
                for (int k = 0; k < 8; k++) wgmma_rs128<1>(o, p + 4 * k, db + k * 128, acc | k);
                wg_commit();
            };
            issue_qk();
            wg_wait<0>();
            if (lane == 0) mbar_arrive(empty + 8 * r.st);
            r.next();
            {
                const int row = wg * 64 + wq * 16 + g;
#pragma unroll
                for (int j = 0; j < 16; j++) {
                    const int c = 8 * j + 2 * t;
                    if (c > row) s[4 * j] = -INFINITY;
                    if (c + 1 > row) s[4 * j + 1] = -INFINITY;
                    if (c > row + 8) s[4 * j + 2] = -INFINITY;
                    if (c + 1 > row + 8) s[4 * j + 3] = -INFINITY;
                }
            }
            softmax_tile<true>(s, m0, m1, l0, l1, al0, al1);
#pragma unroll
            for (int i = 0; i < 32; i++) pa[i] = pack_bf16(s[2 * i], s[2 * i + 1]);
            int first = 0;
#pragma unroll 1
            for (int j = qi; j >= 1; j--) {
                named_sync(3 + wg, 256);
                issue_qk();
                const int kst = r.st;
                r.next();
                issue_pv(pa, r.st, r.ph, first);
                named_arrive(3 + (wg ^ 1), 256);
                wg_wait<1>();
                if (lane == 0) mbar_arrive(empty + 8 * kst);
                softmax_tile<false>(s, m0, m1, l0, l1, al0, al1);
                wg_wait<0>();
                if (lane == 0) mbar_arrive(empty + 8 * r.st);
                r.next();
#pragma unroll
                for (int i = 0; i < 32; i++) pa[i] = pack_bf16(s[2 * i], s[2 * i + 1]);
#pragma unroll
                for (int i = 0; i < 16; i++) {
                    o[4 * i] *= al0; o[4 * i + 1] *= al0; o[4 * i + 2] *= al1; o[4 * i + 3] *= al1;
                }
                first = 1;
            }
            issue_pv(pa, r.st, r.ph, first);
            l0 += __shfl_xor_sync(~0u, l0, 1); l0 += __shfl_xor_sync(~0u, l0, 2);
            l1 += __shfl_xor_sync(~0u, l1, 1); l1 += __shfl_xor_sync(~0u, l1, 2);
            const float i0 = 1.f / l0, i1 = 1.f / l1;
            if ((tid & 127) == 0) bulk_wait_read<0>();
            named_sync(1 + wg, 128);
            wg_wait<0>();
            if (lane == 0) mbar_arrive(empty + 8 * r.st);
            r.next();
            store_slab64(stg, wq * 16, o, i0, i1, lane);
            store_slab64(stg + 8192, wq * 16, o + 32, i0, i1, lane);
            fence_proxy_async();
            named_sync(1 + wg, 128);
            if ((tid & 127) == 0) {
                tma_store_2d(&tm_ctx_st, stg, h * 128, qi * 128 + wg * 64);
                tma_store_2d(&tm_ctx_st, stg + 8192, h * 128 + 64, qi * 128 + wg * 64);
                bulk_commit();
            }
        }
        if ((tid & 127) == 0) bulk_wait<0>();
    }
}
constexpr int OP_NS = 4;
constexpr int OP_ULD = 164 * 16;
constexpr int OP_UCH = 2 * OP_ULD;
constexpr int OP_SMEM = OP_NS * 32768 + 32768 + 4 * WTAB * 4 + 4 * OP_UCH + 4 * 648 * 4 + 256 + 1024;

template <int N> DEVI void wgmma_conv(float* d, const uint32_t* a, uint64_t db);
template <> DEVI void wgmma_conv<128>(float* d, const uint32_t* a, uint64_t db) {
    asm volatile("wgmma.mma_async.sync.aligned.m64n128k16.f32.bf16.bf16 {%0,%1,%2,%3,%4,%5,%6,%7,%8,%9,%10,%11,%12,%13,%14,%15,%16,%17,%18,%19,%20,%21,%22,%23,%24,%25,%26,%27,%28,%29,%30,%31,%32,%33,%34,%35,%36,%37,%38,%39,%40,%41,%42,%43,%44,%45,%46,%47,%48,%49,%50,%51,%52,%53,%54,%55,%56,%57,%58,%59,%60,%61,%62,%63}, "
                 "{%64,%65,%66,%67}, %68, 1, 1, 1, 0;"
                 : ACC8(d, 0), ACC8(d, 8), ACC8(d, 16), ACC8(d, 24), ACC8(d, 32), ACC8(d, 40), ACC8(d, 48), ACC8(d, 56) : "r"(a[0]), "r"(a[1]), "r"(a[2]), "r"(a[3]), "l"(db));
}
template <> DEVI void wgmma_conv<96>(float* d, const uint32_t* a, uint64_t db) {
    asm volatile("wgmma.mma_async.sync.aligned.m64n96k16.f32.bf16.bf16 {%0,%1,%2,%3,%4,%5,%6,%7,%8,%9,%10,%11,%12,%13,%14,%15,%16,%17,%18,%19,%20,%21,%22,%23,%24,%25,%26,%27,%28,%29,%30,%31,%32,%33,%34,%35,%36,%37,%38,%39,%40,%41,%42,%43,%44,%45,%46,%47}, "
                 "{%48,%49,%50,%51}, %52, 1, 1, 1, 0;"
                 : ACC8(d, 0), ACC8(d, 8), ACC8(d, 16), ACC8(d, 24), ACC8(d, 32), ACC8(d, 40) : "r"(a[0]), "r"(a[1]), "r"(a[2]), "r"(a[3]), "l"(db));
}
template <> DEVI void wgmma_conv<64>(float* d, const uint32_t* a, uint64_t db) {
    asm volatile("wgmma.mma_async.sync.aligned.m64n64k16.f32.bf16.bf16 {%0,%1,%2,%3,%4,%5,%6,%7,%8,%9,%10,%11,%12,%13,%14,%15,%16,%17,%18,%19,%20,%21,%22,%23,%24,%25,%26,%27,%28,%29,%30,%31}, "
                 "{%32,%33,%34,%35}, %36, 1, 1, 1, 0;"
                 : ACC8(d, 0), ACC8(d, 8), ACC8(d, 16), ACC8(d, 24) : "r"(a[0]), "r"(a[1]), "r"(a[2]), "r"(a[3]), "l"(db));
}
template <> DEVI void wgmma_conv<32>(float* d, const uint32_t* a, uint64_t db) {
    asm volatile("wgmma.mma_async.sync.aligned.m64n32k16.f32.bf16.bf16 {%0,%1,%2,%3,%4,%5,%6,%7,%8,%9,%10,%11,%12,%13,%14,%15}, "
                 "{%16,%17,%18,%19}, %20, 1, 1, 1, 0;"
                 : ACC8(d, 0), ACC8(d, 8) : "r"(a[0]), "r"(a[1]), "r"(a[2]), "r"(a[3]), "l"(db));
}
DEVI uint32_t lds32(uint32_t a) { uint32_t v; asm volatile("ld.shared.b32 %0, [%1];" : "=r"(v) : "r"(a)); return v; }
DEVI uint32_t lds16(uint32_t a) { uint16_t v; asm volatile("ld.shared.b16 %0, [%1];" : "=h"(v) : "r"(a)); return v; }

DEVI void sts32(uint32_t a, float v) { asm volatile("st.shared.f32 [%0], %1;" ::"r"(a), "f"(v) : "memory"); }
template <int J> DEVI void conv_half(float* acc, uint32_t* f, uint32_t wa, uint64_t du) {
#pragma unroll
    for (int i = 0; i < 4; i++) {
        const uint32_t w = wa + (4 * J + i) * 256;
        f[4 * i] = lds32(w); f[4 * i + 1] = lds32(w + 32); f[4 * i + 2] = lds32(w - 32); f[4 * i + 3] = lds32(w);
    }
    wg_fence();
#pragma unroll
    for (int i = 0; i < 4; i++) wgmma_conv<128 - 32 * (J / 2)>(acc, f + 4 * i, du + (uint64_t)(4 * (4 * J + i)));
    wg_commit();
}
template <int J> DEVI void conv_group(float* acc, uint32_t* fa, uint32_t* fb, uint32_t wa, uint64_t du) {
    conv_half<2 * J>(acc, fa, wa, du);
    if (J) wg_wait<1>();
    conv_half<2 * J + 1>(acc, fb, wa, du);
    if (J < 3) wg_wait<1>();
}
DEVI uint32_t ypos(int a, int b) { return (uint32_t)(b * 128 + (a ^ ((b & 3) << 3))) * 4; }

DEVI void expand_table(int ct, uint32_t sW, uint32_t sK) {
#pragma unroll 1
    for (int i = ct; i < WTAB; i += 384) {
        const int c = (i >> 3) & 3, qd = (i & 7) | ((i >> 5) << 3);
        float k[5];
#pragma unroll
        for (int e = 0; e < 5; e++) {
            const int l = qd * 4 - 65 + e;
            const int hi = (int)__bfloat16_as_ushort(__float2bfloat16_rn((float)l)) - 17024;
            k[e] = __uint_as_float(lds32(sK + (c * 648 + (l < 0 ? 644 : (l < 128 ? l : hi))) * 4));
        }
        asm volatile("st.shared.v4.b32 [%0], {%1,%2,%3,%4};" ::"r"(sW + (c * WTAB + qd * 4) * 4), "r"(pack_bf16(k[1], k[0])),
                     "r"(pack_bf16(k[2], k[1])), "r"(pack_bf16(k[3], k[2])), "r"(pack_bf16(k[4], k[3])) : "memory");
    }
}

__global__ void __cluster_dims__(2, 1, 1) __launch_bounds__(512, 1)
outproj_kernel(const __grid_constant__ CUtensorMap tm_ctx, const __grid_constant__ CUtensorMap tm_wo,
               const __grid_constant__ CUtensorMap tm_out, const __grid_constant__ CUtensorMap tm_u, SsmParams sp, bf16* __restrict__ out) {
    extern __shared__ uint8_t smem_raw[];
    const uint32_t sb = (smem_u32(smem_raw) + 1023) & ~1023u;
    const uint32_t sX = sb + OP_NS * 32768, sW = sX + 32768, sU = sW + 4 * WTAB * 4, sK = sU + 4 * OP_UCH, bars = sK + 4 * 648 * 4;
    const uint32_t full = bars, empty = bars + 64, xfull = bars + 128, wfull = bars + 136, xfree = bars + 144;
    const int tid = threadIdx.x, warp = tid >> 5, lane = tid & 31, wg = tid >> 7;
    const uint32_t rank = cluster_rank();
    const uint32_t kr = rank;
    const int cl = blockIdx.x >> 1;
    const int m0 = (cl >> 2) * 128, n0 = (cl & 3) * 128, k0 = kr * 2048;
    STAMP(blockIdx.x == 10 && tid == 0, 1000);
    uint32_t praw[9];
    ssm_kgen_load(sp, blockIdx.x * 4 + (warp & 3), wg & 1, lane, praw);
    if (tid == 0) {
        for (int i = 0; i < OP_NS; i++) { mbar_init(full + 8 * i, 1); mbar_init(empty + 8 * i, 8); }
        mbar_init(xfull, 1);
        mbar_init(wfull, 1);
        mbar_init(xfree, 1);
        fence_barrier_init();
        mbar_expect_tx(wfull, 32768);
        for (int i = 0; i < 8; i++) tma_load_2d(sX + i * 4096, &tm_u, cl * 8, i * 256, wfull);
    }
    for (int i = tid; i < 648; i += 512) asm volatile("st.shared.v4.b32 [%0], {%1,%1,%1,%1};" ::"r"(sK + i * 16), "r"(0) : "memory");
    __syncthreads();
    cluster_arrive();
    if (wg == 3) {
        reg_dec<40>();
        cluster_wait();
        if (tid == 384) {
            mbar_expect_tx(xfull, 32768);
            for (int it = 0; it < OP_NS; it++) {
                const uint32_t dst = sb + it * 32768, fb = full + 8 * it;
                mbar_expect_tx(fb, 32768);
                tma_load_2d(dst + 16384, &tm_wo, n0, k0 + it * 64, fb);
                tma_load_2d(dst + 24576, &tm_wo, n0 + 64, k0 + it * 64, fb);
            }
            pdl_wait();
            STAMP(blockIdx.x == 10, 1005);
            for (int it = 0; it < 32; it++) {
                const int st = it & (OP_NS - 1);
                const uint32_t dst = sb + st * 32768, fb = full + 8 * st;
                if (it >= OP_NS) {
                    mbar_wait(empty + 8 * st, ((it / OP_NS) & 1) ^ 1);
                    mbar_expect_tx(fb, 32768);
                    tma_load_2d(dst + 16384, &tm_wo, n0, k0 + it * 64, fb);
                    tma_load_2d(dst + 24576, &tm_wo, n0 + 64, k0 + it * 64, fb);
                }
                tma_load_2d(dst, &tm_ctx, k0 + it * 64, m0, fb);
                tma_load_2d(dst + 8192, &tm_ctx, k0 + it * 64, m0 + 64, fb);
            }
        }
        __syncwarp();
    } else {
      const int ct = tid & 127, wq = warp & 3;
      if (wg == 2) {
        for (int i = ct; i < 8 * 32; i += 128) {
            const uint32_t a = sU + (i >> 5) * OP_ULD + (128 + (i & 31)) * 16;
            asm volatile("st.shared.v4.b32 [%0], {%1,%1,%1,%1};" ::"r"(a), "r"(0) : "memory");
        }
        const bool mine = ((lane >> 2) & 1) == (int)rank;
        const uint32_t ub = sU + (lane & 3) * OP_UCH + ((lane >> 3) & 1) * OP_ULD + (127 - 2 * wq - (lane >> 4)) * 16;
        mbar_wait(wfull, 0);
#pragma unroll 4
        for (int i = 0; i < 16; i++) {
            uint32_t r0, r1, r2, r3;
            asm volatile("ldmatrix.sync.aligned.m8n8.x4.trans.shared.b16 {%0,%1,%2,%3}, [%4];"
                         : "=r"(r0), "=r"(r1), "=r"(r2), "=r"(r3) : "r"(sX + (i * 128 + ct) * 16) : "memory");
            asm volatile("stmatrix.sync.aligned.m8n8.x4.shared.b16 [%0], {%1,%2,%3,%4};"
                         ::"r"(mine ? ub - i * 128 : sW + lane * 16), "r"(r0), "r"(r1), "r"(r2), "r"(r3) : "memory");
        }
        fence_proxy_async();
        STAMP(blockIdx.x == 10 && ct == 0, 1001);
      } else {
        ssm_kgen_warp(praw, lane, sK + wq * 648 * 4);
      }
      cluster_wait();
      named_sync(3, 384);
      if (tid == 256) mbar_arrive_cluster(xfree, rank ^ 1);
      STAMP(blockIdx.x == 10 && tid == 257, 1002);
      expand_table(tid, sW, sK);
      if (wg == 2) {
        reg_inc<216>();
        const int g = lane >> 2, t = lane & 3;
        const int d0 = blockIdx.x * 4;
        const uint2 dsk = __ldg(reinterpret_cast<const uint2*>(sp.dskip + d0));
        named_sync(4, 384);
        uint32_t res[16][2];
        STAMP(blockIdx.x == 10 && ct == 0, 1003);
#pragma unroll 1
        for (int c = 0; c < 4; c++) {
            float acc[64];
            uint32_t fa[16], fb[16];
#pragma unroll
            for (int i = 0; i < 64; i++) acc[i] = 0.f;
            const uint32_t wa = sW + (c * WTAB + 64 + 16 * wq + g - 2 * t) * 4;
            const uint64_t du = make_desc(sU + c * OP_UCH, OP_ULD, 128, 0);
            conv_group<0>(acc, fa, fb, wa, du);
            conv_group<1>(acc, fa, fb, wa, du);
            conv_group<2>(acc, fa, fb, wa, du);
            conv_group<3>(acc, fa, fb, wa, du);
            named_sync(5, 128);
            wg_wait<0>();
            const uint32_t yb = (wq & 1) ? sW + c * WTAB * 4 : sK;
            const bool skip0 = wq >= 2 && t == 0;
            if (wq >= 2) {
                named_sync(6, 128);
#pragma unroll
                for (int hf = 0; hf < 2; hf++) {
                    float2 v[16];
#pragma unroll
                    for (int i = 0; i < 16; i++)
                        asm volatile("ld.shared.v2.f32 {%0,%1}, [%2];" : "=f"(v[i].x), "=f"(v[i].y)
                                     : "r"(yb + ypos((128 - 8 * (8 * hf + (i >> 1)) - 2 * t) & 127, g + 8 * (i & 1))));
#pragma unroll
                    for (int i = 0; i < 16; i++) { acc[32 * hf + 2 * i] += v[i].y; acc[32 * hf + 2 * i + 1] += v[i].x; }
                }
            }
#pragma unroll
            for (int i = 0; i < 32; i++) {
                const uint32_t p = yb + ypos(126 - 8 * (i >> 1) - 2 * t + (wq & 2), g + 8 * (i & 1));
                if (i >= 2 || !skip0) asm volatile("st.shared.v2.f32 [%0], {%1,%2};" ::"r"(p), "f"(acc[2 * i + 1]), "f"(acc[2 * i]) : "memory");
            }
            if (wq < 2) named_arrive(6, 128);
            named_sync(5, 128);
            const uint32_t dw = (c & 2) ? dsk.y : dsk.x;
            const float D = (c & 1) ? bhi(dw) : blo(dw);
            const int yb2 = (lane >> 3) + 4 * wq;
#pragma unroll
            for (int i = 0; i < 16; i++) {
                const int a = 8 * i + (lane & 7);
                float y = __uint_as_float(lds32(sW + c * WTAB * 4 + ypos((a - 1) & 127, yb2)));
                y = __uint_as_float(lds32(sK + ypos(a, yb2))) + (a == 0 ? 0.f : y);
                const float u = __uint_as_float(lds16(sU + c * OP_UCH + (wq >> 1) * OP_ULD + (127 - a) * 16 + (yb2 & 7) * 2) << 16);
                const uint32_t o = __bfloat16_as_ushort(__float2bfloat16_rn(rbf(y) + rbf(u * D)));
                res[i][0] = __byte_perm(res[i][0], res[i][1], 0x5432); res[i][1] = __byte_perm(res[i][1], o, 0x5432);
            }
        }
        STAMP(blockIdx.x == 10 && ct == 0, 1004);
        const int grp = blockIdx.x >> 2, me = blockIdx.x & 3;
#pragma unroll
        for (int i = 0; i < 8; i++)
            __stcg(g_y + (((grp * 4 + (i >> 1)) * 4 + me) * 2 + (i & 1)) * 128 + ct,
                   make_uint4(res[2 * i][0], res[2 * i][1], res[2 * i + 1][0], res[2 * i + 1][1]));
        named_sync(5, 128);
        if (ct == 0) {
            __threadfence();
            const unsigned int target = (atomicAdd(g_ycnt + grp, 1u) & ~3u) + 4u;
            uint32_t t0, t1, v;
            asm volatile("mov.u32 %0, %%globaltimer_lo;" : "=r"(t0));
            do {
                asm volatile("ld.acquire.gpu.global.u32 %0, [%1];" : "=r"(v) : "l"(g_ycnt + grp) : "memory");
                asm volatile("mov.u32 %0, %%globaltimer_lo;" : "=r"(t1));
            } while ((int)(v - target) < 0 && t1 - t0 < 4000000u);
        }
        named_sync(5, 128);
        uint4 y[8];
#pragma unroll
        for (int i = 0; i < 8; i++)
            y[i] = __ldcg(g_y + ((blockIdx.x * 4 + 2 * (t & 1) + ((i >> 1) & 1)) * 2 + (i & 1)) * 128 + (ct & ~1) + (i >> 2));
#pragma unroll
        for (int i = 0; i < 8; i++) {
            const int row = 128 * (4 * me + (i & 3)) + 16 * ((lane & 6) + (i >> 2)) + 4 * wq + (lane >> 3);
            const uint4 p = y[(i & 4) + ((i >> 1) & 1)], q = y[(i & 4) + 2 + ((i >> 1) & 1)];
            *reinterpret_cast<uint4*>(out + (size_t)row * 1024 + 512 + grp * 16 + (t & 1) * 8) =
                (i & 1) ? make_uint4(p.z, p.w, q.z, q.w) : make_uint4(p.x, p.y, q.x, q.y);
        }
      } else {
        named_arrive(4, 384);
        float acc[64];
#pragma unroll 1
        for (int it = 0; it < 32; it++) {
            const int st = it & (OP_NS - 1);
            mbar_wait(full + 8 * st, (it / OP_NS) & 1);
            STAMP(blockIdx.x == 10 && tid == 0, 1009 + it);
            wg_fence();
            const uint32_t base = sb + st * 32768;
            const uint64_t da = desc_kmajor(base + wg * 8192), db = desc_mnmajor(base + 16384, 8192);
#pragma unroll
            for (int k = 0; k < 4; k++) wgmma_ss128<1>(acc, da + k * 2, db + k * 128, (it | k) != 0);
            wg_commit();
            if (it > 0 && it + OP_NS - 1 < 32) {
                wg_wait<1>();
                if (lane == 0) mbar_arrive(empty + 8 * ((it - 1) & (OP_NS - 1)));
            }
        }
        wg_wait<0>();
        mbar_wait(xfree, 0);
        uint32_t peer, pbar;
        asm volatile("mapa.shared::cluster.u32 %0, %1, %2;" : "=r"(peer) : "r"(sX + tid * 16), "r"(rank ^ 1));
        asm volatile("mapa.shared::cluster.u32 %0, %1, %2;" : "=r"(pbar) : "r"(xfull), "r"(rank ^ 1));
#pragma unroll
        for (int i = 0; i < 8; i++) {
            const float* s = acc + 4 * i;
            const float a = kr ? s[0] : s[32], b = kr ? s[1] : s[33], c = kr ? s[2] : s[34], d = kr ? s[3] : s[35];
            asm volatile("st.async.weak.shared::cluster.mbarrier::complete_tx::bytes.v4.f32 [%0], {%1,%2,%3,%4}, [%5];"
                         ::"r"(peer + i * 4096), "f"(a), "f"(b), "f"(c), "f"(d), "r"(pbar) : "memory");
        }
        STAMP(blockIdx.x == 10 && tid == 0, 1006);
        mbar_wait(xfull, 0);
        STAMP(blockIdx.x == 10 && tid == 0, 1007);
        float r[32];
#pragma unroll
        for (int i = 0; i < 8; i++) {
            float a, b, c, d;
            asm volatile("ld.shared.v4.f32 {%0,%1,%2,%3}, [%4];" : "=f"(a), "=f"(b), "=f"(c), "=f"(d) : "r"(sX + tid * 16 + i * 4096));
            const float* s = acc + 4 * i;
            r[4 * i] = a + (kr ? s[32] : s[0]); r[4 * i + 1] = b + (kr ? s[33] : s[1]);
            r[4 * i + 2] = c + (kr ? s[34] : s[2]); r[4 * i + 3] = d + (kr ? s[35] : s[3]);
        }
        const uint32_t stg = sb + wg * 8192;
        store_slab64(stg, (warp & 3) * 16, r, 1.f, 1.f, lane);
        fence_proxy_async();
        named_sync(1 + wg, 128);
        if ((tid & 127) == 0) {
            tma_store_2d(&tm_out, stg, n0 + kr * 64, m0 + wg * 64);
            bulk_commit();
            bulk_wait<0>();
            STAMP(blockIdx.x == 10 && tid == 0, 1008);
        }
      }
    }
}

typedef CUresult (*EncodeFn)(CUtensorMap*, CUtensorMapDataType, cuuint32_t, void*, const cuuint64_t*, const cuuint64_t*,
                             const cuuint32_t*, const cuuint32_t*, CUtensorMapInterleave, CUtensorMapSwizzle,
                             CUtensorMapL2promotion, CUtensorMapFloatOOBfill);

static void make_map(EncodeFn fn, CUtensorMap* m, const void* p, uint64_t cols, uint64_t rows, uint32_t box_rows) {
    cuuint64_t dims[2] = {cols, rows};
    cuuint64_t strides[1] = {cols * 2};
    cuuint32_t box[2] = {64, box_rows};
    cuuint32_t es[2] = {1, 1};
    fn(m, CU_TENSOR_MAP_DATA_TYPE_BFLOAT16, 2, const_cast<void*>(p), dims, strides, box, es, CU_TENSOR_MAP_INTERLEAVE_NONE,
       CU_TENSOR_MAP_SWIZZLE_128B, CU_TENSOR_MAP_L2_PROMOTION_L2_256B, CU_TENSOR_MAP_FLOAT_OOB_FILL_NONE);
}

extern "C" void kernel_launch(void* const* d_in, const int* in_sizes, int n_in, void* d_out, int out_size) {
    void* fp = nullptr;
    cudaDriverEntryPointQueryResult qr;
    cudaGetDriverEntryPoint("cuTensorMapEncodeTiled", &fp, cudaEnableDefault, &qr);
    EncodeFn fn = (EncodeFn)fp;
    void *p_kv, *p_ctx;
    cudaGetSymbolAddress(&p_kv, g_kv);
    cudaGetSymbolAddress(&p_ctx, g_ctx);
    CUtensorMap tm_kv_st, tm_x, tm_c, tm_wq, tm_wk, tm_wv, tm_wo, tm_kv, tm_ctx, tm_out;
    make_map(fn, &tm_x, d_in[0], DM, SEQ, 128);
    make_map(fn, &tm_c, d_in[1], DM, SEQ, 128);
    make_map(fn, &tm_wq, d_in[2], HDALL, DM, 64);
    make_map(fn, &tm_wk, d_in[3], HDALL, DM, 64);
    make_map(fn, &tm_wv, d_in[4], HDALL, DM, 64);
    make_map(fn, &tm_wo, d_in[5], DM, HDALL, 64);
    make_map(fn, &tm_kv, p_kv, 2 * HDALL, SEQ, 128);
    make_map(fn, &tm_kv_st, p_kv, 2 * HDALL, SEQ, 64);
    make_map(fn, &tm_ctx, p_ctx, HDALL, SEQ, 64);
    make_map(fn, &tm_out, d_out, 1024, SEQ, 64);
    CUtensorMap tm_u;
    {
        cuuint64_t dims[2] = {512, 2048}, strides[1] = {1024};
        cuuint32_t box[2] = {8, 256}, es[2] = {1, 1};
        fn(&tm_u, CU_TENSOR_MAP_DATA_TYPE_BFLOAT16, 2, d_in[6], dims, strides, box, es, CU_TENSOR_MAP_INTERLEAVE_NONE,
           CU_TENSOR_MAP_SWIZZLE_NONE, CU_TENSOR_MAP_L2_PROMOTION_NONE, CU_TENSOR_MAP_FLOAT_OOB_FILL_NONE);
    }
    SsmParams sp;
    sp.u = (const bf16*)d_in[6]; sp.lar = (const bf16*)d_in[7]; sp.aim = (const bf16*)d_in[8];
    sp.cre = (const bf16*)d_in[9]; sp.cim = (const bf16*)d_in[10]; sp.ldt = (const bf16*)d_in[11]; sp.dskip = (const bf16*)d_in[12];
    cudaFuncSetAttribute(gemm_kv_kernel, cudaFuncAttributeMaxDynamicSharedMemorySize, G1_SMEM);
    cudaFuncSetAttribute(attn_kernel, cudaFuncAttributeMaxDynamicSharedMemorySize, AT_SMEM);
    cudaFuncSetAttribute(outproj_kernel, cudaFuncAttributeMaxDynamicSharedMemorySize, OP_SMEM);
    cudaStream_t st = cudaStreamPerThread;
    gemm_kv_kernel<<<128, G1_THREADS, G1_SMEM, st>>>(tm_c, tm_wk, tm_wv, tm_kv_st, (const bf16*)d_in[0], (const bf16*)d_in[2]);
    cudaLaunchAttribute at[1];
    at[0].id = cudaLaunchAttributeProgrammaticStreamSerialization;
    at[0].val.programmaticStreamSerializationAllowed = 1;
    cudaLaunchConfig_t cfg = {};
    cfg.stream = st; cfg.attrs = at; cfg.numAttrs = 1;
    cfg.gridDim = dim3(132); cfg.blockDim = dim3(384); cfg.dynamicSmemBytes = AT_SMEM;
    cudaLaunchKernelEx(&cfg, attn_kernel, tm_x, tm_wq, tm_kv, tm_ctx, sp, (const bf16*)d_in[5]);
    cfg.gridDim = dim3(128); cfg.blockDim = dim3(512); cfg.dynamicSmemBytes = OP_SMEM;
    cudaLaunchKernelEx(&cfg, outproj_kernel, tm_ctx, tm_wo, tm_out, tm_u, sp, (bf16*)d_out);
}
```

```cpp
#include <cuda_runtime.h>
#include <cuda_bf16.h>
#include <cuda.h>
#include <stdint.h>

typedef __nv_bfloat16 bf16;

#define DEVI __device__ __forceinline__

constexpr int SEQ = 2048, DM = 512, NH = 32, HD = 128, HDALL = NH * HD;
constexpr int SSM_D = 512, SSM_N = 128;
constexpr int WTAB = 2112;

__device__ bf16 g_kv[(size_t)SEQ * 2 * HDALL];
__device__ bf16 g_ctx[(size_t)SEQ * HDALL];
__device__ uint4 g_y[32 * 4 * 4 * 2 * 128];
__device__ unsigned int g_ycnt[32];
__device__ unsigned int g_sched;

#define STAMP(cond, i)
DEVI uint32_t smem_u32(const void* p) { return (uint32_t)__cvta_generic_to_shared(p); }
DEVI void mbar_init(uint32_t a, uint32_t cnt) { asm volatile("mbarrier.init.shared::cta.b64 [%0], %1;" ::"r"(a), "r"(cnt)); }
DEVI void mbar_expect_tx(uint32_t a, uint32_t bytes) {
    asm volatile("mbarrier.arrive.expect_tx.shared::cta.b64 _, [%0], %1;" ::"r"(a), "r"(bytes) : "memory");
}
DEVI void mbar_arrive(uint32_t a) { asm volatile("mbarrier.arrive.shared::cta.b64 _, [%0];" ::"r"(a) : "memory"); }
DEVI void mbar_arrive_cluster(uint32_t a, uint32_t cta) {
    asm volatile("{\n.reg .b32 r;\nmapa.shared::cluster.u32 r, %0, %1;\n"
                 "mbarrier.arrive.shared::cluster.b64 _, [r];\n}" ::"r"(a), "r"(cta) : "memory");
}
#define MBAR_WAIT_ASM(OP)                                                                              \
    asm volatile("{\n.reg .pred p, q;\n.reg .u32 t0, t1;\n" OP " p, [%0], %1;\n@p bra D_%=;\n"         \
                 "mov.u32 t0, %%globaltimer_lo;\nW_%=:\n" OP " p, [%0], %1;\n"                         \
                 "mov.u32 t1, %%globaltimer_lo;\nsub.u32 t1, t1, t0;\n"                                \
                 "setp.gt.or.u32 q, t1, 4000000, p;\n@!q bra W_%=;\nD_%=:\n}" ::"r"(a), "r"(parity) : "memory")
DEVI void mbar_wait(uint32_t a, uint32_t parity) { MBAR_WAIT_ASM("mbarrier.try_wait.parity.shared::cta.b64"); }
DEVI void mbar_wait_cluster(uint32_t a, uint32_t parity) { MBAR_WAIT_ASM("mbarrier.try_wait.parity.acquire.cluster.shared::cta.b64"); }
DEVI void fence_barrier_init() { asm volatile("fence.mbarrier_init.release.cluster;" ::: "memory"); }
DEVI void fence_proxy_async() { asm volatile("fence.proxy.async.shared::cta;" ::: "memory"); }
DEVI void cluster_sync_all() {
    asm volatile("barrier.cluster.arrive.relaxed.aligned;\nbarrier.cluster.wait.aligned;" ::: "memory");
}
DEVI void cluster_arrive() { asm volatile("barrier.cluster.arrive.relaxed.aligned;" ::: "memory"); }
DEVI void cluster_wait() { asm volatile("barrier.cluster.wait.aligned;" ::: "memory"); }
DEVI uint32_t cluster_rank() { uint32_t r; asm volatile("mov.u32 %0, %%cluster_ctarank;" : "=r"(r)); return r; }
DEVI void tma_load_2d(uint32_t dst, const CUtensorMap* m, int c0, int c1, uint32_t bar) {
    asm volatile("cp.async.bulk.tensor.2d.shared::cluster.global.mbarrier::complete_tx::bytes [%0], [%1, {%3, %4}], [%2];"
                 ::"r"(dst), "l"(m), "r"(bar), "r"(c0), "r"(c1) : "memory");
}
DEVI void tma_load_2d_mc(uint32_t dst, const CUtensorMap* m, int c0, int c1, uint32_t bar, uint16_t mask) {
    asm volatile("cp.async.bulk.tensor.2d.shared::cluster.global.mbarrier::complete_tx::bytes.multicast::cluster [%0], [%1, {%3, %4}], [%2], %5;"
                 ::"r"(dst), "l"(m), "r"(bar), "r"(c0), "r"(c1), "h"(mask) : "memory");
}
DEVI void tma_prefetch_2d(const CUtensorMap* m, int c0, int c1) {
    asm volatile("cp.async.bulk.prefetch.tensor.2d.L2.global [%0, {%1, %2}];" ::"l"(m), "r"(c0), "r"(c1) : "memory");
}
DEVI void tma_store_2d(const CUtensorMap* m, uint32_t src, int c0, int c1) {
    asm volatile("cp.async.bulk.tensor.2d.global.shared::cta.bulk_group [%0, {%2, %3}], [%1];"
                 ::"l"(m), "r"(src), "r"(c0), "r"(c1) : "memory");
}
DEVI void bulk_load(uint32_t dst, const void* src, uint32_t bytes, uint32_t bar) {
    asm volatile("cp.async.bulk.shared::cluster.global.mbarrier::complete_tx::bytes [%0], [%1], %2, [%3];"
                 ::"r"(dst), "l"(src), "r"(bytes), "r"(bar) : "memory");
}
DEVI void bulk_prefetch(const void* src, uint32_t bytes) {
    asm volatile("cp.async.bulk.prefetch.L2.global [%0], %1;" ::"l"(src), "r"(bytes) : "memory");
}
DEVI void bulk_commit() { asm volatile("cp.async.bulk.commit_group;" ::: "memory"); }
template <int N> DEVI void bulk_wait_read() { asm volatile("cp.async.bulk.wait_group.read %0;" ::"n"(N) : "memory"); }
template <int N> DEVI void bulk_wait() { asm volatile("cp.async.bulk.wait_group %0;" ::"n"(N) : "memory"); }
DEVI void prefetch_tmap(const CUtensorMap* m) { asm volatile("prefetch.tensormap [%0];" ::"l"(m) : "memory"); }
DEVI void named_sync(int id, int n) { asm volatile("bar.sync %0, %1;" ::"r"(id), "r"(n) : "memory"); }
DEVI void named_arrive(int id, int n) { asm volatile("bar.arrive %0, %1;" ::"r"(id), "r"(n) : "memory"); }
DEVI void pdl_wait() { asm volatile("griddepcontrol.wait;" ::: "memory"); }
DEVI void pdl_launch() { asm volatile("griddepcontrol.launch_dependents;" ::: "memory"); }
template <int R> DEVI void reg_inc() { asm volatile("setmaxnreg.inc.sync.aligned.u32 %0;" ::"n"(R)); }
template <int R> DEVI void reg_dec() { asm volatile("setmaxnreg.dec.sync.aligned.u32 %0;" ::"n"(R)); }

DEVI void wg_fence() { asm volatile("wgmma.fence.sync.aligned;" ::: "memory"); }
DEVI void wg_commit() { asm volatile("wgmma.commit_group.sync.aligned;" ::: "memory"); }
template <int N> DEVI void wg_wait() { asm volatile("wgmma.wait_group.sync.aligned %0;" ::"n"(N) : "memory"); }

DEVI uint64_t make_desc(uint32_t addr, uint32_t lbo, uint32_t sbo, uint32_t swz) {
    return (uint64_t)((addr & 0x3FFFF) >> 4) | ((uint64_t)(lbo >> 4) << 16) | ((uint64_t)(sbo >> 4) << 32) | ((uint64_t)swz << 62);
}
DEVI uint64_t desc_kmajor(uint32_t addr) { return make_desc(addr, 16, 1024, 1); }
DEVI uint64_t desc_mnmajor(uint32_t addr, uint32_t lbo) { return make_desc(addr, lbo, 1024, 1); }

#define ACC8(d, o) "+f"(d[o + 0]), "+f"(d[o + 1]), "+f"(d[o + 2]), "+f"(d[o + 3]), "+f"(d[o + 4]), "+f"(d[o + 5]), "+f"(d[o + 6]), "+f"(d[o + 7])
#define ACC64(d) ACC8(d, 0), ACC8(d, 8), ACC8(d, 16), ACC8(d, 24), ACC8(d, 32), ACC8(d, 40), ACC8(d, 48), ACC8(d, 56)
#define R64 "{%0,%1,%2,%3,%4,%5,%6,%7,%8,%9,%10,%11,%12,%13,%14,%15,%16,%17,%18,%19,%20,%21,%22,%23,%24,%25,%26,%27,%28,%29,%30,%31," \
            "%32,%33,%34,%35,%36,%37,%38,%39,%40,%41,%42,%43,%44,%45,%46,%47,%48,%49,%50,%51,%52,%53,%54,%55,%56,%57,%58,%59,%60,%61,%62,%63}"

template <int TB> DEVI void wgmma_ss128(float* d, uint64_t da, uint64_t db, int acc) {
    asm volatile("{\n.reg .pred p;\nsetp.ne.b32 p, %66, 0;\n"
                 "wgmma.mma_async.sync.aligned.m64n128k16.f32.bf16.bf16 " R64 ", %64, %65, p, 1, 1, 0, %67;\n}"
                 : ACC64(d) : "l"(da), "l"(db), "r"(acc), "n"(TB));
}
template <int TB> DEVI void wgmma_rs128(float* d, const uint32_t* a, uint64_t db, int acc) {
    asm volatile("{\n.reg .pred p;\nsetp.ne.b32 p, %69, 0;\n"
                 "wgmma.mma_async.sync.aligned.m64n128k16.f32.bf16.bf16 " R64 ", {%64,%65,%66,%67}, %68, p, 1, 1, %70;\n}"
                 : ACC64(d) : "r"(a[0]), "r"(a[1]), "r"(a[2]), "r"(a[3]), "l"(db), "r"(acc), "n"(TB));
}
DEVI uint32_t pack_bf16(float lo, float hi) {
    uint32_t r;
    asm("cvt.rn.bf16x2.f32 %0, %1, %2;" : "=r"(r) : "f"(hi), "f"(lo));
    return r;
}
DEVI void stmatrix_x4(uint32_t addr, uint32_t r0, uint32_t r1, uint32_t r2, uint32_t r3) {
    asm volatile("stmatrix.sync.aligned.m8n8.x4.shared.b16 [%0], {%1,%2,%3,%4};" ::"r"(addr), "r"(r0), "r"(r1), "r"(r2), "r"(r3) : "memory");
}
DEVI float ex2(float x) { float y; asm("ex2.approx.ftz.f32 %0, %1;" : "=f"(y) : "f"(x)); return y; }

DEVI void store_slab64(uint32_t base, int row0, const float* d, float s0, float s1, int lane) {
    int mi = lane >> 3, r = lane & 7;
    int row = row0 + (mi & 1) * 8 + r;
#pragma unroll
    for (int j = 0; j < 8; j += 2) {
        uint32_t r0 = pack_bf16(d[4 * j + 0] * s0, d[4 * j + 1] * s0);
        uint32_t r1 = pack_bf16(d[4 * j + 2] * s1, d[4 * j + 3] * s1);
        uint32_t r2 = pack_bf16(d[4 * j + 4] * s0, d[4 * j + 5] * s0);
        uint32_t r3 = pack_bf16(d[4 * j + 6] * s1, d[4 * j + 7] * s1);
        int chunk = j + (mi >> 1);
        stmatrix_x4(base + row * 128 + ((chunk ^ (row & 7)) << 4), r0, r1, r2, r3);
    }
}
struct cf { float x, y; };
DEVI cf cmul(cf a, cf b) { cf r; r.x = fmaf(a.x, b.x, -a.y * b.y); r.y = fmaf(a.x, b.y, a.y * b.x); return r; }
DEVI cf csq(cf a) { cf r; r.x = fmaf(a.x, a.x, -a.y * a.y); r.y = (a.x + a.x) * a.y; return r; }
DEVI cf cexp_(float re, float im) {
    float m = __expf(re), s, c;
    __sincosf(im, &s, &c);
    cf r; r.x = m * c; r.y = m * s; return r;
}
DEVI uint32_t h2(cf v) { uint32_t r; asm("cvt.rn.f16x2.f32 %0, %1, %2;" : "=r"(r) : "f"(v.y), "f"(v.x)); return r; }
DEVI uint32_t h2c(cf v) { uint32_t r; asm("cvt.rn.f16x2.f32 %0, %1, %2;" : "=r"(r) : "f"(-v.y), "f"(v.x)); return r; }
DEVI void mma_group(float (*c)[4], const uint32_t (*a)[4], const uint32_t (*b)[2]) {
    asm volatile(
        "mma.sync.aligned.m16n8k16.row.col.f32.f16.f16.f32 {%0,%1,%2,%3}, {%20,%21,%22,%23}, {%40,%41}, {%0,%1,%2,%3};\n"
        "mma.sync.aligned.m16n8k16.row.col.f32.f16.f16.f32 {%4,%5,%6,%7}, {%24,%25,%26,%27}, {%40,%41}, {%4,%5,%6,%7};\n"
        "mma.sync.aligned.m16n8k16.row.col.f32.f16.f16.f32 {%8,%9,%10,%11}, {%28,%29,%30,%31}, {%42,%43}, {%8,%9,%10,%11};\n"
        "mma.sync.aligned.m16n8k16.row.col.f32.f16.f16.f32 {%12,%13,%14,%15}, {%32,%33,%34,%35}, {%44,%45}, {%12,%13,%14,%15};\n"
        "mma.sync.aligned.m16n8k16.row.col.f32.f16.f16.f32 {%16,%17,%18,%19}, {%36,%37,%38,%39}, {%46,%47}, {%16,%17,%18,%19};\n"
        : "+f"(c[0][0]), "+f"(c[0][1]), "+f"(c[0][2]), "+f"(c[0][3]), "+f"(c[1][0]), "+f"(c[1][1]), "+f"(c[1][2]), "+f"(c[1][3]),
          "+f"(c[2][0]), "+f"(c[2][1]), "+f"(c[2][2]), "+f"(c[2][3]), "+f"(c[3][0]), "+f"(c[3][1]), "+f"(c[3][2]), "+f"(c[3][3]),
          "+f"(c[4][0]), "+f"(c[4][1]), "+f"(c[4][2]), "+f"(c[4][3])
        : "r"(a[0][0]), "r"(a[0][1]), "r"(a[0][2]), "r"(a[0][3]), "r"(a[1][0]), "r"(a[1][1]), "r"(a[1][2]), "r"(a[1][3]),
          "r"(a[2][0]), "r"(a[2][1]), "r"(a[2][2]), "r"(a[2][3]), "r"(a[3][0]), "r"(a[3][1]), "r"(a[3][2]), "r"(a[3][3]),
          "r"(a[4][0]), "r"(a[4][1]), "r"(a[4][2]), "r"(a[4][3]),
          "r"(b[0][0]), "r"(b[0][1]), "r"(b[1][0]), "r"(b[1][1]), "r"(b[2][0]), "r"(b[2][1]), "r"(b[3][0]), "r"(b[3][1]));
}
DEVI float bf2f(bf16 v) { return __bfloat162float(v); }
DEVI float rbf(float v) { return __bfloat162float(__float2bfloat16_rn(v)); }

struct SsmParams { const bf16 *lar, *aim, *cre, *cim, *ldt, *dskip, *u; };

DEVI int kp_index(int l) {
    int p = (int)rbf((float)l);
    return p < 256 ? p : (p < 512 ? 128 + (p >> 1) : (p < 1024 ? 256 + (p >> 2) : 384 + (p >> 3)));
}

DEVI void reds(uint32_t a, float v) { asm volatile("st.shared.f32 [%0], %1;" ::"r"(a), "f"(v) : "memory"); }
DEVI uint32_t ldg16(const bf16* p) { uint16_t v; asm volatile("ld.global.nc.u16 %0, [%1];" : "=h"(v) : "l"(p)); return v; }
DEVI void ssm_kgen_load(const SsmParams& P, int d, int half, int lane, uint32_t* r) {
#pragma unroll
    for (int q = 0; q < 2; q++) {
        const int n = d * SSM_N + 64 * half + 32 * q + lane;
        r[4 * q] = ldg16(P.lar + n); r[4 * q + 1] = ldg16(P.aim + n); r[4 * q + 2] = ldg16(P.cre + n); r[4 * q + 3] = ldg16(P.cim + n);
    }
    r[8] = ldg16(P.ldt + d);
}
DEVI void ssm_kgen_warp(const uint32_t* r, int half, int lane, uint32_t kp) {
    float raw[9];
#pragma unroll
    for (int i = 0; i < 9; i++) raw[i] = __uint_as_float(r[i] << 16);
    const int g = lane >> 2, t = lane & 3;
    float ar[2], ai[2], cr[2], ci[2], gr[2], gi[2];
    const float dt = rbf(expf(raw[8]));
#pragma unroll
    for (int q = 0; q < 2; q++) {
        ar[q] = -rbf(expf(raw[4 * q])) * dt;
        ai[q] = raw[4 * q + 1] * dt;
        cr[q] = 2.f * (raw[4 * q + 2] * dt);
        ci[q] = 2.f * (raw[4 * q + 3] * dt);
        float m = expf(ar[q] * 64.f), sn, cs;
        sincosf(ai[q] * 64.f, &sn, &cs);
        gr[q] = m * cs; gi[q] = m * sn;
    }
    float cm = 0.f;
#pragma unroll
    for (int q = 0; q < 2; q++) cm = fmaxf(cm, fmaxf(fabsf(cr[q]), fabsf(ci[q])));
#pragma unroll
    for (int o = 16; o; o >>= 1) cm = fmaxf(cm, __shfl_xor_sync(~0u, cm, o));
    const int ex = min(max((int)(__float_as_uint(cm) >> 23), 1), 253);
    const float cs_dn = __uint_as_float((uint32_t)(254 - ex) << 23), cs_up = __uint_as_float((uint32_t)ex << 23);
    float acc[5][4];
#pragma unroll
    for (int s = 0; s < 5; s++) { acc[s][0] = acc[s][1] = acc[s][2] = acc[s][3] = 0.f; }
    float klast = 0.f;
    const float gf = (float)g;
#pragma unroll 1
    for (int g0 = 0; g0 < 8; g0 += 2) {
#pragma unroll
        for (int q = 0; q < 2; q++) {
            uint32_t fa[5][4], fb[4][2];
#pragma unroll
            for (int h = 0; h < 2; h++) {
                const int src = ((g0 + h) << 2) | t;
                const float a_r = __shfl_sync(~0u, ar[q], src), a_i = __shfl_sync(~0u, ai[q], src);
                cf C, G;
                C.x = __shfl_sync(~0u, cr[q], src) * cs_dn; C.y = __shfl_sync(~0u, ci[q], src) * cs_dn;
                G.x = __shfl_sync(~0u, gr[q], src); G.y = __shfl_sync(~0u, gi[q], src);
                cf E = cexp_(a_r * gf, a_i * gf);
                cf B = csq(csq(csq(E)));
                fb[0][h] = h2c(cmul(C, B));
                cf EG = cmul(E, G);
                fa[0][2 * h] = h2(E); fa[0][2 * h + 1] = h2(EG);
                cf G2 = csq(G);
                cf X = cmul(E, G2), Xh = cmul(EG, G2);
                fa[1][2 * h] = h2(X); fa[1][2 * h + 1] = h2(Xh);
#pragma unroll
                for (int s = 2; s < 5; s++) {
                    B = csq(B); X = csq(X); Xh = csq(Xh);
                    fb[s - 1][h] = h2c(cmul(C, B));
                    fa[s][2 * h] = h2(X); fa[s][2 * h + 1] = h2(Xh);
                }
                X = csq(X);
                klast += fmaf(C.x, X.x, -C.y * X.y);
            }
            mma_group(acc, fa, fb);
        }
    }
    klast += __shfl_xor_sync(~0u, klast, 1);
    klast += __shfl_xor_sync(~0u, klast, 2);
    float o[21];
#pragma unroll
    for (int i = 0; i < 21; i++) o[i] = 0.f;
    const uint32_t kb = kp + (g + 16 * t) * 4;
    if (half == 0) {
        named_sync(7, 256);
#pragma unroll
        for (int i = 0; i < 20; i++)
            asm volatile("ld.shared.f32 %0, [%1];" : "=f"(o[i]) : "r"(kb + (i >> 2) * 512 + (i & 1) * 32 + (i & 2) * 128));
        asm volatile("ld.shared.f32 %0, [%1];" : "=f"(o[20]) : "r"(kp + 2560));
    }
#pragma unroll
    for (int i = 0; i < 20; i++) reds(kb + (i >> 2) * 512 + (i & 1) * 32 + (i & 2) * 128, fmaf(acc[i >> 2][i & 3], cs_up, o[i]));
    if (lane == 0) reds(kp + 2560, fmaf(klast, cs_up, o[20]));
    if (half == 1) named_arrive(7, 256);
}

constexpr int G1_THREADS = 384;
constexpr int G1_NS = 11;
constexpr int G1_SMEM = G1_NS * 16384 + 32768 + 256 + 1024;

__global__ void __cluster_dims__(2, 1, 1) __launch_bounds__(G1_THREADS, 1)
gemm_kv_kernel(const __grid_constant__ CUtensorMap tm_c, const __grid_constant__ CUtensorMap tm_wk,
               const __grid_constant__ CUtensorMap tm_wv, const __grid_constant__ CUtensorMap tm_kv_st,
               const bf16* __restrict__ px, const bf16* __restrict__ pwq) {
    extern __shared__ uint8_t smem_raw[];
    const uint32_t sb = (smem_u32(smem_raw) + 1023) & ~1023u;
    const uint32_t sC = sb + G1_NS * 16384, bars = sC + 32768;
    const uint32_t full = bars, empty = bars + 128;
    const int tid = threadIdx.x, warp = tid >> 5, lane = tid & 31, wg = tid >> 7;
    const uint32_t rank = cluster_rank();
    const int cl = blockIdx.x >> 1;
    const int m0 = ((cl & 7) * 2 + rank) * 128;
    const int ng = cl >> 3;
    STAMP(blockIdx.x == 10 && tid == 0, 0);
    if (tid == 0) {
        for (int i = 0; i < G1_NS; i++) { mbar_init(full + 8 * i, 1); mbar_init(empty + 8 * i, 16); }
        fence_barrier_init();
        for (int it = 0; it < 8; it++) {
            mbar_expect_tx(full + 8 * it, 16384);
            tma_load_2d(sb + it * 16384, &tm_c, it * 64, m0, full + 8 * it);
        }
    }
    __syncthreads();
    cluster_sync_all();
    pdl_launch();
    if (wg == 2) {
        reg_dec<40>();
        if (tid == 256) {
            const CUtensorMap* tw = ng < 4 ? &tm_wk : &tm_wv;
            const int n0 = (ng & 3) * 1024 + rank * 64;
            int st = 8; uint32_t ph = 1;
            for (int it = 0; it < 64; it++) {
                mbar_wait(empty + 8 * st, ph);
                mbar_expect_tx(full + 8 * st, 16384);
                tma_load_2d_mc(sb + st * 16384 + rank * 8192, tw, n0 + (it >> 3) * 128, (it & 7) * 64, full + 8 * st, 3);
                if (it < 2) {
                    for (int j = 3 + it * 8 + (cl & 7); j < 19; j += 16) tma_prefetch_2d(tw, n0 + (j >> 3) * 128, (j & 7) * 64);
                }
                if (it >= 3 && it + 16 < 64 && (it & 7) == (cl & 7)) tma_prefetch_2d(tw, n0 + ((it + 16) >> 3) * 128, (it & 7) * 64);
                if (it == 24) bulk_prefetch(px + blockIdx.x * 8192, 16384);
                if (it == 32) bulk_prefetch(pwq + blockIdx.x * 16384, 32768);
                if (++st == G1_NS) { st = 0; ph ^= 1; }
            }
        }
        __syncwarp();
    } else {
        reg_inc<232>();
        uint32_t af[128];
        float acc[64];
        const int wq = warp & 3;
        const int row = wg * 64 + wq * 16 + (lane & 15);
        const uint32_t stg = sC + wg * 16384;
        int st = 8, pst = 0; uint32_t ph = 0;
#pragma unroll
        for (int kc = 0; kc < 8; kc++) {
            mbar_wait(full + 8 * kc, 0);
#pragma unroll
            for (int k = 0; k < 4; k++) {
                const uint32_t a = sb + kc * 16384 + row * 128 + (((2 * k + (lane >> 4)) ^ (row & 7)) << 4);
                uint32_t* f = af + kc * 16 + k * 4;
                asm volatile("ldmatrix.sync.aligned.m8n8.x4.shared.b16 {%0,%1,%2,%3}, [%4];"
                             : "=r"(f[0]), "=r"(f[1]), "=r"(f[2]), "=r"(f[3]) : "r"(a) : "memory");
            }
            __syncwarp();
            if (lane < 2) mbar_arrive_cluster(empty + 8 * kc, lane);
        }
#pragma unroll 1
        for (int t = 0; t < 8; t++) {
            if (wg == 1 || t > 0) named_sync(3 + wg, 256);
#pragma unroll
            for (int kc = 0; kc < 8; kc++) {
                mbar_wait(full + 8 * st, ph);
                STAMP(blockIdx.x == 10 && (tid & 127) == 0, 1 + wg * 96 + t * 12 + kc);
                wg_fence();
                const uint64_t db = desc_mnmajor(sb + st * 16384, 8192);
#pragma unroll
                for (int k = 0; k < 4; k++) wgmma_rs128<1>(acc, af + kc * 16 + k * 4, db + k * 128, (kc | k) != 0);
                wg_commit();
                if (kc == 3 && (wg == 0 || t < 7)) named_arrive(3 + (wg ^ 1), 256);
                if (kc > 0) {
                    wg_wait<1>();
                    if (lane < 2) mbar_arrive_cluster(empty + 8 * pst, lane);
                }
                pst = st;
                if (++st == G1_NS) { st = 0; ph ^= 1; }
            }
            if ((tid & 127) == 0) bulk_wait_read<0>();
            named_sync(1 + wg, 128);
            wg_wait<0>();
            STAMP(blockIdx.x == 10 && (tid & 127) == 0, 9 + wg * 96 + t * 12);
            if (lane < 2) mbar_arrive_cluster(empty + 8 * pst, lane);
            store_slab64(stg, wq * 16, acc, 1.f, 1.f, lane);
            store_slab64(stg + 8192, wq * 16, acc + 32, 1.f, 1.f, lane);
            fence_proxy_async();
            named_sync(1 + wg, 128);
            if ((tid & 127) == 0) {
                tma_store_2d(&tm_kv_st, stg, ng * 1024 + t * 128, m0 + wg * 64);
                tma_store_2d(&tm_kv_st, stg + 8192, ng * 1024 + t * 128 + 64, m0 + wg * 64);
                bulk_commit();
            }
            STAMP(blockIdx.x == 10 && (tid & 127) == 0, 10 + wg * 96 + t * 12);
        }
        if ((tid & 127) == 0) bulk_wait<0>();
        __syncwarp();
    }
    asm volatile("barrier.cluster.arrive.relaxed.aligned;\nbarrier.cluster.wait.aligned;" ::: "memory");
}
constexpr int AT_NS = 6;
constexpr int AT_SMEM = AT_NS * 32768 + 32768 + 256 + 1024;
constexpr int AT_ITEMS = 512;

DEVI uint32_t hmax2(uint32_t a, uint32_t b) { uint32_t r; asm("max.bf16x2 %0, %1, %2;" : "=r"(r) : "r"(a), "r"(b)); return r; }
DEVI uint32_t hmul2(uint32_t a, uint32_t b) { uint32_t r; asm("mul.rn.bf16x2 %0, %1, %2;" : "=r"(r) : "r"(a), "r"(b)); return r; }
DEVI uint32_t hfma2(uint32_t a, uint32_t b, uint32_t c) { uint32_t r; asm("fma.rn.bf16x2 %0, %1, %2, %3;" : "=r"(r) : "r"(a), "r"(b), "r"(c)); return r; }
DEVI float blo(uint32_t v) { return __uint_as_float(v << 16); }
DEVI float bhi(uint32_t v) { return __uint_as_float(v & 0xffff0000u); }

template <bool FIRST>
DEVI void softmax_tile(float* s, float& m0, float& m1, float& l0, float& l1, float& al0, float& al1) {
    const uint32_t HI = 0x3DB53DB5u;
    const uint32_t LO = 0x371E371Eu;
    const float L2E = 1.4426950408889634f;
    uint32_t x0 = 0xFF80FF80u, x1 = 0xFF80FF80u;
#pragma unroll
    for (int j = 0; j < 16; j++) {
        uint32_t a = pack_bf16(s[4 * j], s[4 * j + 1]), b = pack_bf16(s[4 * j + 2], s[4 * j + 3]);
        a = hfma2(a, HI, hmul2(a, LO));
        b = hfma2(b, HI, hmul2(b, LO));
        s[4 * j] = __uint_as_float(a); s[4 * j + 2] = __uint_as_float(b);
        x0 = hmax2(x0, a); x1 = hmax2(x1, b);
    }
    uint32_t x = hmax2(__byte_perm(x0, x1, 0x5410), __byte_perm(x0, x1, 0x7632));
    x = hmax2(x, __shfl_xor_sync(~0u, x, 1));
    x = hmax2(x, __shfl_xor_sync(~0u, x, 2));
    float n0 = blo(x), n1 = bhi(x);
    if (!FIRST) {
        n0 = fmaxf(n0, m0); n1 = fmaxf(n1, m1);
        al0 = ex2((m0 - n0) * L2E); al1 = ex2((m1 - n1) * L2E);
    }
    m0 = n0; m1 = n1;
    const float c0 = -n0 * L2E, c1 = -n1 * L2E;
    float s0 = 0.f, s1 = 0.f;
#pragma unroll
    for (int j = 0; j < 16; j++) {
        uint32_t a = __float_as_uint(s[4 * j]), b = __float_as_uint(s[4 * j + 2]);
        float e0 = ex2(fmaf(blo(a), L2E, c0)), e1 = ex2(fmaf(bhi(a), L2E, c0));
        float e2 = ex2(fmaf(blo(b), L2E, c1)), e3 = ex2(fmaf(bhi(b), L2E, c1));
        s0 += e0 + e1; s1 += e2 + e3;
        s[4 * j] = e0; s[4 * j + 1] = e1; s[4 * j + 2] = e2; s[4 * j + 3] = e3;
    }
    if (FIRST) { l0 = s0; l1 = s1; }
    else { l0 = fmaf(l0, al0, s0); l1 = fmaf(l1, al1, s1); }
}

struct Ring {
    int st; uint32_t ph;
    DEVI void next() { if (++st == AT_NS) { st = 0; ph ^= 1; } }
};

__global__ void __launch_bounds__(384, 1)
attn_kernel(const __grid_constant__ CUtensorMap tm_x, const __grid_constant__ CUtensorMap tm_wq,
            const __grid_constant__ CUtensorMap tm_kv, const __grid_constant__ CUtensorMap tm_ctx_st,
            const SsmParams sp, const bf16* __restrict__ pwo) {
    extern __shared__ uint8_t smem_raw[];
    const uint32_t sb = (smem_u32(smem_raw) + 1023) & ~1023u;
    const uint32_t sO = sb + AT_NS * 32768, bars = sO + 32768;
    const uint32_t full = bars, empty = bars + 64;
    volatile int* slots = reinterpret_cast<volatile int*>(smem_raw + (bars + 128 - smem_u32(smem_raw)));
    const int tid = threadIdx.x, warp = tid >> 5, lane = tid & 31, wg = tid >> 7;
    if (tid == 0) {
        for (int i = 0; i < AT_NS; i++) { mbar_init(full + 8 * i, 1); mbar_init(empty + 8 * i, 8); }
        fence_barrier_init();
    }
    __syncthreads();
    if (wg == 2) {
        reg_dec<24>();
        if (warp == 8 && lane == 0) {
            Ring r{0, 1};
            int n = 0;
            while (true) {
                int idx = (int)atomicInc(&g_sched, AT_ITEMS + gridDim.x - 1);
                if (idx >= AT_ITEMS - 128 && idx < AT_ITEMS) {
                    bulk_prefetch(sp.u + (idx - (AT_ITEMS - 128)) * 8192, 16384);
                    const int po = (idx - (AT_ITEMS - 128)) * 512;
                    bulk_prefetch(sp.lar + po, 1024); bulk_prefetch(sp.aim + po, 1024);
                    bulk_prefetch(sp.cre + po, 1024); bulk_prefetch(sp.cim + po, 1024);
                    if (po == 0) { bulk_prefetch(sp.ldt, 1024); bulk_prefetch(sp.dskip, 1024); }
                    bulk_prefetch(pwo + (idx - (AT_ITEMS - 128)) * 16384, 32768);
                }
                mbar_wait(empty + 8 * r.st, r.ph);
                if (idx >= AT_ITEMS) {
                    slots[n & 3] = -1;
                    mbar_arrive(full + 8 * r.st);
                    break;
                }
                slots[n & 3] = idx;
                const int qi = 15 - (idx >> 5), h = idx & 31;
                for (int kc = 0; kc < 8; kc++) {
                    if (kc) mbar_wait(empty + 8 * r.st, r.ph);
                    const uint32_t fb = full + 8 * r.st, dst = sb + r.st * 32768;
                    mbar_expect_tx(fb, 32768);
                    tma_load_2d(dst, &tm_x, kc * 64, qi * 128, fb);
                    tma_load_2d(dst + 16384, &tm_wq, h * 128, kc * 64, fb);
                    tma_load_2d(dst + 24576, &tm_wq, h * 128 + 64, kc * 64, fb);
                    r.next();
                }
                if (n == 0) { pdl_wait(); pdl_launch(); }
                for (int j = qi; j >= -1; j--) {
#pragma unroll
                    for (int v = 0; v < 2; v++) {
                        const int jj = j + v;
                        if (jj < 0 || jj > qi || (v == 0 && j < 0)) continue;
                        mbar_wait(empty + 8 * r.st, r.ph);
                        const uint32_t fb = full + 8 * r.st, dst = sb + r.st * 32768;
                        mbar_expect_tx(fb, 32768);
                        tma_load_2d(dst, &tm_kv, v * HDALL + h * 128, jj * 128, fb);
                        tma_load_2d(dst + 16384, &tm_kv, v * HDALL + h * 128 + 64, jj * 128, fb);
                        r.next();
                    }
                }
                n++;
            }
            if (n == 0) { pdl_wait(); pdl_launch(); }
        }
    } else {
        reg_inc<240>();
        Ring r{0, 0};
        float o[64], s[64];
        uint32_t qf[32], pa[32];
        const int g = lane >> 2, t = lane & 3, wq = warp & 3;
        const uint32_t stg = sO + wg * 16384;
        if (wg == 1) named_arrive(3, 256);
        for (int n = 0;; n++) {
            mbar_wait(full + 8 * r.st, r.ph);
            const int idx = slots[n & 3];
            if (idx < 0) break;
            const int qi = 15 - (idx >> 5), h = idx & 31;
#pragma unroll 1
            for (int kc = 0; kc < 8; kc++) {
                if (kc) mbar_wait(full + 8 * r.st, r.ph);
                wg_fence();
                const uint32_t base = sb + r.st * 32768;
                const uint64_t da = desc_kmajor(base + wg * 8192), db = desc_mnmajor(base + 16384, 8192);
#pragma unroll
                for (int k = 0; k < 4; k++) wgmma_ss128<1>(s, da + k * 2, db + k * 128, (kc | k) != 0);
                wg_commit();
                if (kc) {
                    wg_wait<1>();
                    if (lane == 0) mbar_arrive(empty + 8 * (r.st == 0 ? AT_NS - 1 : r.st - 1));
                }
                r.next();
            }
            wg_wait<0>();
            if (lane == 0) mbar_arrive(empty + 8 * (r.st == 0 ? AT_NS - 1 : r.st - 1));
#pragma unroll
            for (int i = 0; i < 32; i++) qf[i] = pack_bf16(s[2 * i], s[2 * i + 1]);
            float m0, m1, l0, l1, al0, al1;
            auto issue_qk = [&]() {
                mbar_wait(full + 8 * r.st, r.ph);
                wg_fence();
                const uint64_t db = desc_kmajor(sb + r.st * 32768);
#pragma unroll
                for (int k = 0; k < 8; k++) wgmma_rs128<0>(s, qf + 4 * k, db + (k >> 2) * 1024 + (k & 3) * 2, k != 0);
                wg_commit();
            };
            auto issue_pv = [&](const uint32_t* p, int st, uint32_t ph, int acc) {
                mbar_wait(full + 8 * st, ph);
                wg_fence();
                const uint64_t db = desc_mnmajor(sb + st * 32768, 16384);
#pragma unroll
                for (int k = 0; k < 8; k++) wgmma_rs128<1>(o, p + 4 * k, db + k * 128, acc | k);
                wg_commit();
            };
            issue_qk();
            wg_wait<0>();
            if (lane == 0) mbar_arrive(empty + 8 * r.st);
            r.next();
            {
                const int row = wg * 64 + wq * 16 + g;
#pragma unroll
                for (int j = 0; j < 16; j++) {
                    const int c = 8 * j + 2 * t;
                    if (c > row) s[4 * j] = -INFINITY;
                    if (c + 1 > row) s[4 * j + 1] = -INFINITY;
                    if (c > row + 8) s[4 * j + 2] = -INFINITY;
                    if (c + 1 > row + 8) s[4 * j + 3] = -INFINITY;
                }
            }
            softmax_tile<true>(s, m0, m1, l0, l1, al0, al1);
#pragma unroll
            for (int i = 0; i < 32; i++) pa[i] = pack_bf16(s[2 * i], s[2 * i + 1]);
            int first = 0;
#pragma unroll 1
            for (int j = qi; j >= 1; j--) {
                named_sync(3 + wg, 256);
                issue_qk();
                const int kst = r.st;
                r.next();
                issue_pv(pa, r.st, r.ph, first);
                named_arrive(3 + (wg ^ 1), 256);
                wg_wait<1>();
                if (lane == 0) mbar_arrive(empty + 8 * kst);
                softmax_tile<false>(s, m0, m1, l0, l1, al0, al1);
                wg_wait<0>();
                if (lane == 0) mbar_arrive(empty + 8 * r.st);
                r.next();
#pragma unroll
                for (int i = 0; i < 32; i++) pa[i] = pack_bf16(s[2 * i], s[2 * i + 1]);
#pragma unroll
                for (int i = 0; i < 16; i++) {
                    o[4 * i] *= al0; o[4 * i + 1] *= al0; o[4 * i + 2] *= al1; o[4 * i + 3] *= al1;
                }
                first = 1;
            }
            issue_pv(pa, r.st, r.ph, first);
            l0 += __shfl_xor_sync(~0u, l0, 1); l0 += __shfl_xor_sync(~0u, l0, 2);
            l1 += __shfl_xor_sync(~0u, l1, 1); l1 += __shfl_xor_sync(~0u, l1, 2);
            const float i0 = 1.f / l0, i1 = 1.f / l1;
            if ((tid & 127) == 0) bulk_wait_read<0>();
            named_sync(1 + wg, 128);
            wg_wait<0>();
            if (lane == 0) mbar_arrive(empty + 8 * r.st);
            r.next();
            store_slab64(stg, wq * 16, o, i0, i1, lane);
            store_slab64(stg + 8192, wq * 16, o + 32, i0, i1, lane);
            fence_proxy_async();
            named_sync(1 + wg, 128);
            if ((tid & 127) == 0) {
                tma_store_2d(&tm_ctx_st, stg, h * 128, qi * 128 + wg * 64);
                tma_store_2d(&tm_ctx_st, stg + 8192, h * 128 + 64, qi * 128 + wg * 64);
                bulk_commit();
            }
        }
        if ((tid & 127) == 0) bulk_wait<0>();
    }
}
constexpr int OP_NS = 4;
constexpr int OP_ULD = 164 * 16;
constexpr int OP_UCH = 2 * OP_ULD;
constexpr int OP_SMEM = OP_NS * 32768 + 32768 + 4 * WTAB * 4 + 4 * OP_UCH + 4 * 648 * 4 + 256 + 1024;

template <int N> DEVI void wgmma_conv(float* d, const uint32_t* a, uint64_t db);
template <> DEVI void wgmma_conv<128>(float* d, const uint32_t* a, uint64_t db) {
    asm volatile("wgmma.mma_async.sync.aligned.m64n128k16.f32.bf16.bf16 {%0,%1,%2,%3,%4,%5,%6,%7,%8,%9,%10,%11,%12,%13,%14,%15,%16,%17,%18,%19,%20,%21,%22,%23,%24,%25,%26,%27,%28,%29,%30,%31,%32,%33,%34,%35,%36,%37,%38,%39,%40,%41,%42,%43,%44,%45,%46,%47,%48,%49,%50,%51,%52,%53,%54,%55,%56,%57,%58,%59,%60,%61,%62,%63}, "
                 "{%64,%65,%66,%67}, %68, 1, 1, 1, 0;"
                 : ACC8(d, 0), ACC8(d, 8), ACC8(d, 16), ACC8(d, 24), ACC8(d, 32), ACC8(d, 40), ACC8(d, 48), ACC8(d, 56) : "r"(a[0]), "r"(a[1]), "r"(a[2]), "r"(a[3]), "l"(db));
}
template <> DEVI void wgmma_conv<96>(float* d, const uint32_t* a, uint64_t db) {
    asm volatile("wgmma.mma_async.sync.aligned.m64n96k16.f32.bf16.bf16 {%0,%1,%2,%3,%4,%5,%6,%7,%8,%9,%10,%11,%12,%13,%14,%15,%16,%17,%18,%19,%20,%21,%22,%23,%24,%25,%26,%27,%28,%29,%30,%31,%32,%33,%34,%35,%36,%37,%38,%39,%40,%41,%42,%43,%44,%45,%46,%47}, "
                 "{%48,%49,%50,%51}, %52, 1, 1, 1, 0;"
                 : ACC8(d, 0), ACC8(d, 8), ACC8(d, 16), ACC8(d, 24), ACC8(d, 32), ACC8(d, 40) : "r"(a[0]), "r"(a[1]), "r"(a[2]), "r"(a[3]), "l"(db));
}
template <> DEVI void wgmma_conv<64>(float* d, const uint32_t* a, uint64_t db) {
    asm volatile("wgmma.mma_async.sync.aligned.m64n64k16.f32.bf16.bf16 {%0,%1,%2,%3,%4,%5,%6,%7,%8,%9,%10,%11,%12,%13,%14,%15,%16,%17,%18,%19,%20,%21,%22,%23,%24,%25,%26,%27,%28,%29,%30,%31}, "
                 "{%32,%33,%34,%35}, %36, 1, 1, 1, 0;"
                 : ACC8(d, 0), ACC8(d, 8), ACC8(d, 16), ACC8(d, 24) : "r"(a[0]), "r"(a[1]), "r"(a[2]), "r"(a[3]), "l"(db));
}
template <> DEVI void wgmma_conv<32>(float* d, const uint32_t* a, uint64_t db) {
    asm volatile("wgmma.mma_async.sync.aligned.m64n32k16.f32.bf16.bf16 {%0,%1,%2,%3,%4,%5,%6,%7,%8,%9,%10,%11,%12,%13,%14,%15}, "
                 "{%16,%17,%18,%19}, %20, 1, 1, 1, 0;"
                 : ACC8(d, 0), ACC8(d, 8) : "r"(a[0]), "r"(a[1]), "r"(a[2]), "r"(a[3]), "l"(db));
}
DEVI uint32_t lds32(uint32_t a) { uint32_t v; asm volatile("ld.shared.b32 %0, [%1];" : "=r"(v) : "r"(a)); return v; }
DEVI uint32_t lds16(uint32_t a) { uint16_t v; asm volatile("ld.shared.b16 %0, [%1];" : "=h"(v) : "r"(a)); return v; }

DEVI void sts32(uint32_t a, float v) { asm volatile("st.shared.f32 [%0], %1;" ::"r"(a), "f"(v) : "memory"); }
template <int J> DEVI void conv_half(float* acc, uint32_t* f, uint32_t wa, uint64_t du) {
#pragma unroll
    for (int i = 0; i < 4; i++) {
        const uint32_t w = wa + (4 * J + i) * 256;
        f[4 * i] = lds32(w); f[4 * i + 1] = lds32(w + 32); f[4 * i + 2] = lds32(w - 32); f[4 * i + 3] = lds32(w);
    }
    wg_fence();
#pragma unroll
    for (int i = 0; i < 4; i++) wgmma_conv<128 - 32 * (J / 2)>(acc, f + 4 * i, du + (uint64_t)(4 * (4 * J + i)));
    wg_commit();
}
template <int J> DEVI void conv_group(float* acc, uint32_t* fa, uint32_t* fb, uint32_t wa, uint64_t du) {
    conv_half<2 * J>(acc, fa, wa, du);
    if (J) wg_wait<1>();
    conv_half<2 * J + 1>(acc, fb, wa, du);
    if (J < 3) wg_wait<1>();
}
DEVI uint32_t ypos(int a, int b) { return (uint32_t)(b * 128 + (a ^ ((b & 3) << 3))) * 4; }

DEVI void expand_table(int ct, uint32_t sW, uint32_t sK) {
#pragma unroll 1
    for (int i = ct; i < WTAB; i += 384) {
        const int c = (i >> 3) & 3, qd = (i & 7) | ((i >> 5) << 3);
        float k[5];
#pragma unroll
        for (int e = 0; e < 5; e++) {
            const int l = qd * 4 - 65 + e;
            const int hi = (int)__bfloat16_as_ushort(__float2bfloat16_rn((float)l)) - 17024;
            k[e] = __uint_as_float(lds32(sK + (c * 648 + (l < 0 ? 644 : (l < 128 ? l : hi))) * 4));
        }
        asm volatile("st.shared.v4.b32 [%0], {%1,%2,%3,%4};" ::"r"(sW + (c * WTAB + qd * 4) * 4), "r"(pack_bf16(k[1], k[0])),
                     "r"(pack_bf16(k[2], k[1])), "r"(pack_bf16(k[3], k[2])), "r"(pack_bf16(k[4], k[3])) : "memory");
    }
}

__global__ void __cluster_dims__(2, 1, 1) __launch_bounds__(512, 1)
outproj_kernel(const __grid_constant__ CUtensorMap tm_ctx, const __grid_constant__ CUtensorMap tm_wo,
               const __grid_constant__ CUtensorMap tm_out, const __grid_constant__ CUtensorMap tm_u, SsmParams sp, bf16* __restrict__ out) {
    extern __shared__ uint8_t smem_raw[];
    const uint32_t sb = (smem_u32(smem_raw) + 1023) & ~1023u;
    const uint32_t sX = sb + OP_NS * 32768, sW = sX + 32768, sU = sW + 4 * WTAB * 4, sK = sU + 4 * OP_UCH, bars = sK + 4 * 648 * 4;
    const uint32_t full = bars, empty = bars + 64, xfull = bars + 128, wfull = bars + 136, xfree = bars + 144;
    const int tid = threadIdx.x, warp = tid >> 5, lane = tid & 31, wg = tid >> 7;
    const uint32_t rank = cluster_rank();
    const uint32_t kr = rank;
    const int cl = blockIdx.x >> 1;
    const int m0 = (cl >> 2) * 128, n0 = (cl & 3) * 128, k0 = kr * 2048;
    STAMP(blockIdx.x == 10 && tid == 0, 1000);
    uint32_t praw[9];
    ssm_kgen_load(sp, blockIdx.x * 4 + (warp & 3), wg & 1, lane, praw);
    if (tid == 0) {
        for (int i = 0; i < OP_NS; i++) { mbar_init(full + 8 * i, 1); mbar_init(empty + 8 * i, 8); }
        mbar_init(xfull, 1);
        mbar_init(wfull, 1);
        mbar_init(xfree, 1);
        fence_barrier_init();
        mbar_expect_tx(wfull, 32768);
        for (int i = 0; i < 8; i++) tma_load_2d(sX + i * 4096, &tm_u, cl * 8, i * 256, wfull);
    }
    for (int i = tid; i < 648; i += 512) asm volatile("st.shared.v4.b32 [%0], {%1,%1,%1,%1};" ::"r"(sK + i * 16), "r"(0) : "memory");
    __syncthreads();
    cluster_arrive();
    if (wg == 3) {
        reg_dec<40>();
        if (tid == 384) {
            mbar_expect_tx(xfull, 32768);
            for (int it = 0; it < OP_NS; it++) {
                const uint32_t dst = sb + it * 32768, fb = full + 8 * it;
                mbar_expect_tx(fb, 32768);
                tma_load_2d(dst + 16384, &tm_wo, n0, k0 + it * 64, fb);
                tma_load_2d(dst + 24576, &tm_wo, n0 + 64, k0 + it * 64, fb);
            }
            pdl_wait();
            STAMP(blockIdx.x == 10, 1005);
            for (int it = 0; it < 32; it++) {
                const int st = it & (OP_NS - 1);
                const uint32_t dst = sb + st * 32768, fb = full + 8 * st;
                if (it >= OP_NS) {
                    mbar_wait(empty + 8 * st, ((it / OP_NS) & 1) ^ 1);
                    mbar_expect_tx(fb, 32768);
                    tma_load_2d(dst + 16384, &tm_wo, n0, k0 + it * 64, fb);
                    tma_load_2d(dst + 24576, &tm_wo, n0 + 64, k0 + it * 64, fb);
                }
                tma_load_2d(dst, &tm_ctx, k0 + it * 64, m0, fb);
                tma_load_2d(dst + 8192, &tm_ctx, k0 + it * 64, m0 + 64, fb);
            }
        }
        __syncwarp();
        cluster_wait();
    } else {
      const int ct = tid & 127, wq = warp & 3;
      if (wg == 2) {
        for (int i = ct; i < 8 * 32; i += 128) {
            const uint32_t a = sU + (i >> 5) * OP_ULD + (128 + (i & 31)) * 16;
            asm volatile("st.shared.v4.b32 [%0], {%1,%1,%1,%1};" ::"r"(a), "r"(0) : "memory");
        }
        const bool mine = ((lane >> 2) & 1) == (int)rank;
        const uint32_t ub = sU + (lane & 3) * OP_UCH + ((lane >> 3) & 1) * OP_ULD + (127 - 2 * wq - (lane >> 4)) * 16;
        mbar_wait(wfull, 0);
#pragma unroll 4
        for (int i = 0; i < 16; i++) {
            uint32_t r0, r1, r2, r3;
            asm volatile("ldmatrix.sync.aligned.m8n8.x4.trans.shared.b16 {%0,%1,%2,%3}, [%4];"
                         : "=r"(r0), "=r"(r1), "=r"(r2), "=r"(r3) : "r"(sX + (i * 128 + ct) * 16) : "memory");
            asm volatile("stmatrix.sync.aligned.m8n8.x4.shared.b16 [%0], {%1,%2,%3,%4};"
                         ::"r"(mine ? ub - i * 128 : sW + lane * 16), "r"(r0), "r"(r1), "r"(r2), "r"(r3) : "memory");
        }
        fence_proxy_async();
        STAMP(blockIdx.x == 10 && ct == 0, 1001);
      } else {
        ssm_kgen_warp(praw, wg, lane, sK + wq * 648 * 4);
      }
      cluster_wait();
      named_sync(3, 384);
      if (tid == 256) mbar_arrive_cluster(xfree, rank ^ 1);
      STAMP(blockIdx.x == 10 && tid == 257, 1002);
      expand_table(tid, sW, sK);
      if (wg == 2) {
        reg_inc<216>();
        const int g = lane >> 2, t = lane & 3;
        const int d0 = blockIdx.x * 4;
        const uint2 dsk = __ldg(reinterpret_cast<const uint2*>(sp.dskip + d0));
        named_sync(4, 384);
        uint32_t res[16][2];
        STAMP(blockIdx.x == 10 && ct == 0, 1003);
#pragma unroll 1
        for (int c = 0; c < 4; c++) {
            float acc[64];
            uint32_t fa[16], fb[16];
#pragma unroll
            for (int i = 0; i < 64; i++) acc[i] = 0.f;
            const uint32_t wa = sW + (c * WTAB + 64 + 16 * wq + g - 2 * t) * 4;
            const uint64_t du = make_desc(sU + c * OP_UCH, OP_ULD, 128, 0);
            conv_group<0>(acc, fa, fb, wa, du);
            conv_group<1>(acc, fa, fb, wa, du);
            conv_group<2>(acc, fa, fb, wa, du);
            conv_group<3>(acc, fa, fb, wa, du);
            named_sync(5, 128);
            wg_wait<0>();
            const uint32_t yb = (wq & 1) ? sW + c * WTAB * 4 : sK;
            const bool skip0 = wq >= 2 && t == 0;
            if (wq >= 2) {
                named_sync(6, 128);
#pragma unroll
                for (int hf = 0; hf < 2; hf++) {
                    float2 v[16];
#pragma unroll
                    for (int i = 0; i < 16; i++)
                        asm volatile("ld.shared.v2.f32 {%0,%1}, [%2];" : "=f"(v[i].x), "=f"(v[i].y)
                                     : "r"(yb + ypos((128 - 8 * (8 * hf + (i >> 1)) - 2 * t) & 127, g + 8 * (i & 1))));
#pragma unroll
                    for (int i = 0; i < 16; i++) { acc[32 * hf + 2 * i] += v[i].y; acc[32 * hf + 2 * i + 1] += v[i].x; }
                }
            }
#pragma unroll
            for (int i = 0; i < 32; i++) {
                const uint32_t p = yb + ypos(126 - 8 * (i >> 1) - 2 * t + (wq & 2), g + 8 * (i & 1));
                if (i >= 2 || !skip0) asm volatile("st.shared.v2.f32 [%0], {%1,%2};" ::"r"(p), "f"(acc[2 * i + 1]), "f"(acc[2 * i]) : "memory");
            }
            if (wq < 2) named_arrive(6, 128);
            named_sync(5, 128);
            const uint32_t dw = (c & 2) ? dsk.y : dsk.x;
            const float D = (c & 1) ? bhi(dw) : blo(dw);
            const int yb2 = (lane >> 3) + 4 * wq;
#pragma unroll
            for (int i = 0; i < 16; i++) {
                const int a = 8 * i + (lane & 7);
                float y = __uint_as_float(lds32(sW + c * WTAB * 4 + ypos((a - 1) & 127, yb2)));
                y = __uint_as_float(lds32(sK + ypos(a, yb2))) + (a == 0 ? 0.f : y);
                const float u = __uint_as_float(lds16(sU + c * OP_UCH + (wq >> 1) * OP_ULD + (127 - a) * 16 + (yb2 & 7) * 2) << 16);
                const uint32_t o = __bfloat16_as_ushort(__float2bfloat16_rn(rbf(y) + rbf(u * D)));
                res[i][0] = __byte_perm(res[i][0], res[i][1], 0x5432); res[i][1] = __byte_perm(res[i][1], o, 0x5432);
            }
        }
        STAMP(blockIdx.x == 10 && ct == 0, 1004);
        const int grp = blockIdx.x >> 2, me = blockIdx.x & 3;
#pragma unroll
        for (int i = 0; i < 8; i++)
            __stcg(g_y + (((grp * 4 + (i >> 1)) * 4 + me) * 2 + (i & 1)) * 128 + ct,
                   make_uint4(res[2 * i][0], res[2 * i][1], res[2 * i + 1][0], res[2 * i + 1][1]));
        named_sync(5, 128);
        if (ct == 0) {
            __threadfence();
            const unsigned int target = (atomicAdd(g_ycnt + grp, 1u) & ~3u) + 4u;
            uint32_t t0, t1, v;
            asm volatile("mov.u32 %0, %%globaltimer_lo;" : "=r"(t0));
            do {
                asm volatile("ld.acquire.gpu.global.u32 %0, [%1];" : "=r"(v) : "l"(g_ycnt + grp) : "memory");
                asm volatile("mov.u32 %0, %%globaltimer_lo;" : "=r"(t1));
            } while ((int)(v - target) < 0 && t1 - t0 < 4000000u);
        }
        named_sync(5, 128);
        uint4 y[8];
#pragma unroll
        for (int i = 0; i < 8; i++)
            y[i] = __ldcg(g_y + ((blockIdx.x * 4 + 2 * (t & 1) + ((i >> 1) & 1)) * 2 + (i & 1)) * 128 + (ct & ~1) + (i >> 2));
#pragma unroll
        for (int i = 0; i < 8; i++) {
            const int row = 128 * (4 * me + (i & 3)) + 16 * ((lane & 6) + (i >> 2)) + 4 * wq + (lane >> 3);
            const uint4 p = y[(i & 4) + ((i >> 1) & 1)], q = y[(i & 4) + 2 + ((i >> 1) & 1)];
            *reinterpret_cast<uint4*>(out + (size_t)row * 1024 + 512 + grp * 16 + (t & 1) * 8) =
                (i & 1) ? make_uint4(p.z, p.w, q.z, q.w) : make_uint4(p.x, p.y, q.x, q.y);
        }
      } else {
        named_arrive(4, 384);
        float acc[64];
#pragma unroll 1
        for (int it = 0; it < 32; it++) {
            const int st = it & (OP_NS - 1);
            mbar_wait(full + 8 * st, (it / OP_NS) & 1);
            STAMP(blockIdx.x == 10 && tid == 0, 1009 + it);
            wg_fence();
            const uint32_t base = sb + st * 32768;
            const uint64_t da = desc_kmajor(base + wg * 8192), db = desc_mnmajor(base + 16384, 8192);
#pragma unroll
            for (int k = 0; k < 4; k++) wgmma_ss128<1>(acc, da + k * 2, db + k * 128, (it | k) != 0);
            wg_commit();
            if (it > 0 && it + OP_NS - 1 < 32) {
                wg_wait<1>();
                if (lane == 0) mbar_arrive(empty + 8 * ((it - 1) & (OP_NS - 1)));
            }
        }
        wg_wait<0>();
        mbar_wait(xfree, 0);
        uint32_t peer, pbar;
        asm volatile("mapa.shared::cluster.u32 %0, %1, %2;" : "=r"(peer) : "r"(sX + tid * 16), "r"(rank ^ 1));
        asm volatile("mapa.shared::cluster.u32 %0, %1, %2;" : "=r"(pbar) : "r"(xfull), "r"(rank ^ 1));
#pragma unroll
        for (int i = 0; i < 8; i++) {
            const float* s = acc + 4 * i;
            const float a = kr ? s[0] : s[32], b = kr ? s[1] : s[33], c = kr ? s[2] : s[34], d = kr ? s[3] : s[35];
            asm volatile("st.async.weak.shared::cluster.mbarrier::complete_tx::bytes.v4.f32 [%0], {%1,%2,%3,%4}, [%5];"
                         ::"r"(peer + i * 4096), "f"(a), "f"(b), "f"(c), "f"(d), "r"(pbar) : "memory");
        }
        STAMP(blockIdx.x == 10 && tid == 0, 1006);
        mbar_wait(xfull, 0);
        STAMP(blockIdx.x == 10 && tid == 0, 1007);
        float r[32];
#pragma unroll
        for (int i = 0; i < 8; i++) {
            float a, b, c, d;
            asm volatile("ld.shared.v4.f32 {%0,%1,%2,%3}, [%4];" : "=f"(a), "=f"(b), "=f"(c), "=f"(d) : "r"(sX + tid * 16 + i * 4096));
            const float* s = acc + 4 * i;
            r[4 * i] = a + (kr ? s[32] : s[0]); r[4 * i + 1] = b + (kr ? s[33] : s[1]);
            r[4 * i + 2] = c + (kr ? s[34] : s[2]); r[4 * i + 3] = d + (kr ? s[35] : s[3]);
        }
        const uint32_t stg = sb + wg * 8192;
        store_slab64(stg, (warp & 3) * 16, r, 1.f, 1.f, lane);
        fence_proxy_async();
        named_sync(1 + wg, 128);
        if ((tid & 127) == 0) {
            tma_store_2d(&tm_out, stg, n0 + kr * 64, m0 + wg * 64);
            bulk_commit();
            bulk_wait<0>();
            STAMP(blockIdx.x == 10 && tid == 0, 1008);
        }
      }
    }
}

typedef CUresult (*EncodeFn)(CUtensorMap*, CUtensorMapDataType, cuuint32_t, void*, const cuuint64_t*, const cuuint64_t*,
                             const cuuint32_t*, const cuuint32_t*, CUtensorMapInterleave, CUtensorMapSwizzle,
                             CUtensorMapL2promotion, CUtensorMapFloatOOBfill);

static void make_map(EncodeFn fn, CUtensorMap* m, const void* p, uint64_t cols, uint64_t rows, uint32_t box_rows) {
    cuuint64_t dims[2] = {cols, rows};
    cuuint64_t strides[1] = {cols * 2};
    cuuint32_t box[2] = {64, box_rows};
    cuuint32_t es[2] = {1, 1};
    fn(m, CU_TENSOR_MAP_DATA_TYPE_BFLOAT16, 2, const_cast<void*>(p), dims, strides, box, es, CU_TENSOR_MAP_INTERLEAVE_NONE,
       CU_TENSOR_MAP_SWIZZLE_128B, CU_TENSOR_MAP_L2_PROMOTION_L2_256B, CU_TENSOR_MAP_FLOAT_OOB_FILL_NONE);
}

extern "C" void kernel_launch(void* const* d_in, const int* in_sizes, int n_in, void* d_out, int out_size) {
    void* fp = nullptr;
    cudaDriverEntryPointQueryResult qr;
    cudaGetDriverEntryPoint("cuTensorMapEncodeTiled", &fp, cudaEnableDefault, &qr);
    EncodeFn fn = (EncodeFn)fp;
    void *p_kv, *p_ctx;
    cudaGetSymbolAddress(&p_kv, g_kv);
    cudaGetSymbolAddress(&p_ctx, g_ctx);
    CUtensorMap tm_kv_st, tm_x, tm_c, tm_wq, tm_wk, tm_wv, tm_wo, tm_kv, tm_ctx, tm_out;
    make_map(fn, &tm_x, d_in[0], DM, SEQ, 128);
    make_map(fn, &tm_c, d_in[1], DM, SEQ, 128);
    make_map(fn, &tm_wq, d_in[2], HDALL, DM, 64);
    make_map(fn, &tm_wk, d_in[3], HDALL, DM, 64);
    make_map(fn, &tm_wv, d_in[4], HDALL, DM, 64);
    make_map(fn, &tm_wo, d_in[5], DM, HDALL, 64);
    make_map(fn, &tm_kv, p_kv, 2 * HDALL, SEQ, 128);
    make_map(fn, &tm_kv_st, p_kv, 2 * HDALL, SEQ, 64);
    make_map(fn, &tm_ctx, p_ctx, HDALL, SEQ, 64);
    make_map(fn, &tm_out, d_out, 1024, SEQ, 64);
    CUtensorMap tm_u;
    {
        cuuint64_t dims[2] = {512, 2048}, strides[1] = {1024};
        cuuint32_t box[2] = {8, 256}, es[2] = {1, 1};
        fn(&tm_u, CU_TENSOR_MAP_DATA_TYPE_BFLOAT16, 2, d_in[6], dims, strides, box, es, CU_TENSOR_MAP_INTERLEAVE_NONE,
           CU_TENSOR_MAP_SWIZZLE_NONE, CU_TENSOR_MAP_L2_PROMOTION_NONE, CU_TENSOR_MAP_FLOAT_OOB_FILL_NONE);
    }
    SsmParams sp;
    sp.u = (const bf16*)d_in[6]; sp.lar = (const bf16*)d_in[7]; sp.aim = (const bf16*)d_in[8];
    sp.cre = (const bf16*)d_in[9]; sp.cim = (const bf16*)d_in[10]; sp.ldt = (const bf16*)d_in[11]; sp.dskip = (const bf16*)d_in[12];
    cudaFuncSetAttribute(gemm_kv_kernel, cudaFuncAttributeMaxDynamicSharedMemorySize, G1_SMEM);
    cudaFuncSetAttribute(attn_kernel, cudaFuncAttributeMaxDynamicSharedMemorySize, AT_SMEM);
    cudaFuncSetAttribute(outproj_kernel, cudaFuncAttributeMaxDynamicSharedMemorySize, OP_SMEM);
    cudaStream_t st = cudaStreamPerThread;
    gemm_kv_kernel<<<128, G1_THREADS, G1_SMEM, st>>>(tm_c, tm_wk, tm_wv, tm_kv_st, (const bf16*)d_in[0], (const bf16*)d_in[2]);
    cudaLaunchAttribute at[1];
    at[0].id = cudaLaunchAttributeProgrammaticStreamSerialization;
    at[0].val.programmaticStreamSerializationAllowed = 1;
    cudaLaunchConfig_t cfg = {};
    cfg.stream = st; cfg.attrs = at; cfg.numAttrs = 1;
    cfg.gridDim = dim3(132); cfg.blockDim = dim3(384); cfg.dynamicSmemBytes = AT_SMEM;
    cudaLaunchKernelEx(&cfg, attn_kernel, tm_x, tm_wq, tm_kv, tm_ctx, sp, (const bf16*)d_in[5]);
    cfg.gridDim = dim3(128); cfg.blockDim = dim3(512); cfg.dynamicSmemBytes = OP_SMEM;
    cudaLaunchKernelEx(&cfg, outproj_kernel, tm_ctx, tm_wo, tm_out, tm_u, sp, (bf16*)d_out);
}
```
